```python
import torch

def _softmax(x, axis=-1):
    return torch.softmax(x, dim=axis)
def _gelu(x):
    return torch.nn.functional.gelu(x, approximate="tanh")
def _silu(x):
    return torch.nn.functional.silu(x)
def _sigmoid(x):
    return torch.sigmoid(x)
def _layernorm(x, axis=-1, eps=1e-5):
    m = x.mean(dim=axis, keepdim=True)
    v = x.var(dim=axis, keepdim=True, unbiased=False)
    return (x - m) / torch.sqrt(v + eps)
def _scatter_add(tgt, idx, src, axis=0):
    return tgt.clone().index_add_(axis, idx, src)
def _segment_sum(src, seg, n):
    out = torch.zeros((n,) + src.shape[1:], dtype=src.dtype)
    return out.index_add_(0, seg, src)
def _pad(x, pw):
    flat = tuple(v for pair in reversed(pw) for v in pair)
    return torch.nn.functional.pad(x, flat)

kernel_name = 'interleave_layers__sliding_local_dilated__moe_arch_mod__prompt'

def setup_inputs():

    _w = (lambda a: (lambda t: t.to(torch.bfloat16) if t.is_floating_point() else t)(torch.as_tensor(a)))
    def _A_setup():
        B, S, D = 1, 2048, 576
        return {
            "x": _w((lambda *s: torch.randn(*s, dtype=torch.bfloat16) * 0.05)(B, S, D)),
            "wqkv": _w((lambda *s: torch.randn(*s, dtype=torch.bfloat16) * 0.05)(D, 3 * D)),
            "wo": _w((lambda *s: torch.randn(*s, dtype=torch.bfloat16) * 0.05)(D, D)),
        }
    _A_in = _A_setup()

    def _B_setup():
        B, S, D, F, C = 1, 2048, 576, 4608, 1
        return {
            "x": _w((lambda *s: torch.randn(*s, dtype=torch.bfloat16) * 0.05)(B, S, D)),
            "w_r": _w((lambda *s: torch.randn(*s, dtype=torch.bfloat16) * 0.05)(D)),
            "w_gate": _w((lambda *s: torch.randn(*s, dtype=torch.bfloat16) * 0.05)(D, F)),
            "w_up": _w((lambda *s: torch.randn(*s, dtype=torch.bfloat16) * 0.05)(D, F)),
            "w_down": _w((lambda *s: torch.randn(*s, dtype=torch.bfloat16) * 0.05)(F, D)),
        }
    _B_in = _B_setup()

    return {
        "A_x": _A_in["x"],
        "A_wqkv": _A_in["wqkv"],
        "A_wo": _A_in["wo"],
        "B_x": _B_in["x"],
        "B_w_r": _B_in["w_r"],
        "B_w_gate": _B_in["w_gate"],
        "B_w_up": _B_in["w_up"],
        "B_w_down": _B_in["w_down"],
    }

def reference(A_x, A_wqkv, A_wo, B_x, B_w_r, B_w_gate, B_w_up, B_w_down):
    def _A_ref(x, wqkv, wo):
        B, S, D = x.shape
        H = 32; Dh = D // H
        W, dil = 8, 2
        qkv = (lambda x, *d: x.permute(*d))((x @ wqkv).reshape(B, S, 3, H, Dh), 2, 0, 3, 1, 4)
        q, k, v = qkv[0], qkv[1], qkv[2]
        scale = Dh ** -0.5
        pos = torch.arange(S)
        off = torch.arange(W) * dil
        idx = pos[:, None] - off[None, :]
        mask = idx >= 0
        idx_c = torch.where(mask, idx, 0).reshape(-1)
        kg = k[:, :, idx_c, :].reshape(B, H, S, W, Dh)
        vg = v[:, :, idx_c, :].reshape(B, H, S, W, Dh)
        logits = torch.einsum("bhsd,bhswd->bhsw", q, kg) * scale
        logits = torch.where(mask[None, None, :, :], logits, -1e9)
        attn = _softmax(logits, axis=-1)
        o = torch.einsum("bhsw,bhswd->bhsd", attn, vg)
        return (lambda x, *d: x.permute(*d))(o, 0, 2, 1, 3).reshape(B, S, D) @ wo

    def _B_ref(x, w_r, w_gate, w_up, w_down):
        B, S, D = x.shape
        C = 1
        r = x @ w_r
        idx = torch.argsort(-r, axis=-1)[:, :C]
        idx_e = (lambda x, n, axis: torch.repeat_interleave(x, n, dim=axis))(idx.reshape(B, C, 1), D, axis=2)
        x_sel = (lambda x, i, axis: torch.take_along_dim(x, i, dim=axis))(x, idx_e, axis=1)
        g = _silu(x_sel @ w_gate)
        u = x_sel @ w_up
        y = (g * u) @ w_down
        r_sel = _sigmoid((lambda x, i, axis: torch.take_along_dim(x, i, dim=axis))(r, idx, axis=1))
        y = y * r_sel.reshape(B, C, 1)
        b_off = (torch.arange(B) * S).reshape(B, 1)
        flat_idx = (idx + b_off).reshape(B * C)
        zero = (x * 0.0).reshape(B * S, D)
        upd = _scatter_add(zero, flat_idx, y.reshape(B * C, D), axis=0)
        return x + upd.reshape(B, S, D)

    x = A_x
    x = x + _A_ref(_layernorm(x, axis=-1), A_wqkv, A_wo)
    x = x + _B_ref(_layernorm(x, axis=-1), B_w_r, B_w_gate, B_w_up, B_w_down)
    x = x + _A_ref(_layernorm(x, axis=-1), A_wqkv, A_wo)
    x = x + _B_ref(_layernorm(x, axis=-1), B_w_r, B_w_gate, B_w_up, B_w_down)
    return x
```

```cpp
#include <cuda_runtime.h>
#include <cuda.h>
#include <cuda_bf16.h>
#include <stdint.h>
#include <stddef.h>

namespace {

constexpr int NPRE = 5;
#define X_NU 192
#define CAND_W 8
#define HALO_V 0
#define X_DELAY 200
#define X_STEP 100
#define HOLD_C 13
#define U_SCHED 0
#define NA0 3
#define B2_AT 0
#define LATE_WAIT 3
#define PF_WAIT 0
#define POLL_GAP 100
#define SPARE_DELAY 400
constexpr float EPS = 1e-5f;
constexpr int SPIN = 1 << 22;
#define TIMEOUT(line) __trap();

struct __align__(128) Scratch {
  uint32_t bflag[8][48][8];
  uint32_t cflag[32][32][8];
  uint32_t halo[32][8][672];
  uint32_t stats[32][4][8][64];
  uint32_t cand[8][32][CAND_W];
  uint32_t xcand[32][8][48];
  uint32_t ypart[72][128][8];
  uint32_t zpart[8][16][216];
  uint32_t st0[2048][4];
  uint32_t xsel[2][576];
  unsigned char wq[8][9][27648];
  unsigned char wo[8][3][27648];
  unsigned char obuf[32][73728];
  unsigned char xbuf[32][73728];
};
__device__ Scratch g_scratch;
#define OFF(f) ((uint32_t)offsetof(Scratch, f))
#define STAMPD(v, k) do {} while (0)
#define STAMPIF(c, k) do {} while (0)
#define STAMP(k) do {} while (0)

constexpr uint32_t sb = 1024;
constexpr uint32_t SM_A = 0;
constexpr uint32_t SM_B = 49152;
constexpr uint32_t SM_G = 132096;
constexpr uint32_t SM_BEXT = 224256;

constexpr uint32_t SM_WIN = 227712;
constexpr uint32_t SM_XW = 228320;
constexpr uint32_t SM_YRED = 228448;
constexpr uint32_t SM_X2S = 228576;
constexpr uint32_t SM_RED2 = 228736;
constexpr uint32_t SM_WR = 228864;
constexpr uint32_t SM_R = 229168;
constexpr uint32_t SM_BEST = 231760;
constexpr uint32_t SM_SEL = 231824;
constexpr uint32_t SM_BAR = 231840;
constexpr uint32_t SM_TOTAL = 232448;
constexpr uint32_t R_FPART = SM_R;
constexpr uint32_t BAR_FULL = SM_BAR  , BAR_AFULL = SM_BAR + 48  , BAR_WFULL = SM_BAR + 96  , BAR_GU = SM_BAR + 248,
                   BAR_FIX = SM_BAR + 256  , BAR_AEMPTY = SM_BAR + 272  , BAR_HDONE = SM_BAR + 320  ,
                   BAR_EMPTY = SM_BAR + 336  ;
enum { NB_WG = 1  , NB_STAG = 3, NB_AUX = 4, NB_FFN2 = 5, NB_FFN = 8, NB_START = 9, NB_GO = 6, NB_ORD = 7 };

struct Params {
  const __nv_bfloat16 *wqkv, *x, *wr, *wo;
  Scratch* sc;
  const __nv_bfloat16 *wd, *wg, *wu;
  __nv_bfloat16* out;
  signed char work[136];
  CUtensorMap mx, mg, mu, mg8, mu8;
};

__device__ __forceinline__ void mbar_init(uint32_t bar, int cnt) { asm volatile("mbarrier.init.shared::cta.b64 [%0], %1;" ::"r"(bar), "r"(cnt) : "memory"); }
__device__ __forceinline__ void mbar_arrive(uint32_t bar) { asm volatile("mbarrier.arrive.shared::cta.b64 _, [%0];" ::"r"(bar) : "memory"); }
__device__ __forceinline__ void mbar_wait(uint32_t bar, uint32_t par) {
  asm volatile("{\n.reg .pred p;\nLOOP:\nmbarrier.try_wait.parity.shared::cta.b64 p, [%0], %1;\n@!p bra.uni LOOP;\n}\n" ::"r"(bar), "r"(par) : "memory");
}
__device__ __forceinline__ uint32_t mbar_test(uint32_t bar, uint32_t par) {
  uint32_t ok;
  asm volatile("{\n.reg .pred p;\nmbarrier.test_wait.parity.shared::cta.b64 p, [%1], %2;\nselp.u32 %0,1,0,p;\n}" : "=r"(ok) : "r"(bar), "r"(par) : "memory");
  return ok;
}
__device__ __forceinline__ bool elect_one() {
  uint32_t ok;
  asm volatile("{\n.reg .pred p;\nelect.sync _|p, 0xffffffff;\nselp.u32 %0, 1, 0, p;\n}" : "=r"(ok));
  return ok;
}
__device__ __forceinline__ float ex2(float x) { float r; asm("ex2.approx.ftz.f32 %0, %1;" : "=f"(r) : "f"(x)); return r; }
__device__ __forceinline__ float rsq(float x) { float r; asm("rsqrt.approx.ftz.f32 %0, %1;" : "=f"(r) : "f"(x)); return r; }
__device__ __forceinline__ float rcp(float x) { float r; asm("rcp.approx.ftz.f32 %0, %1;" : "=f"(r) : "f"(x)); return r; }
__device__ __forceinline__ void w_expect(uint32_t bar, uint32_t bytes) {
  asm volatile("{\n.reg .pred p;\nelect.sync _|p, 0xffffffff;\n@p mbarrier.arrive.expect_tx.shared::cta.b64 _, [%0], %1;\n}" ::"r"(bar), "r"(bytes) : "memory");
}
__device__ __forceinline__ void w_bulk(uint32_t dst, const void* src, uint32_t bytes, uint32_t bar) {
  asm volatile("{\n.reg .pred p;\nelect.sync _|p, 0xffffffff;\n@p cp.async.bulk.shared::cluster.global.mbarrier::complete_tx::bytes [%0], [%1], %2, [%3];\n}" ::"r"(dst), "l"(src), "r"(bytes), "r"(bar) : "memory");
}
__device__ __forceinline__ void w_tma2d(uint32_t dst, const CUtensorMap* m, int c0, int c1, uint32_t bar) {
  asm volatile("{\n.reg .pred p;\nelect.sync _|p, 0xffffffff;\n@p cp.async.bulk.tensor.2d.shared::cluster.global.mbarrier::complete_tx::bytes [%0], [%1, {%3, %4}], [%2];\n}" ::"r"(dst), "l"(m), "r"(bar), "r"(c0), "r"(c1) : "memory");
}
__device__ __forceinline__ void w_tma3d(uint32_t dst, const CUtensorMap* m, int c0, int c1, int c2, uint32_t bar) {
  asm volatile("{\n.reg .pred p;\nelect.sync _|p, 0xffffffff;\n@p cp.async.bulk.tensor.3d.shared::cluster.global.mbarrier::complete_tx::bytes [%0], [%1, {%3, %4, %5}], [%2];\n}" ::"r"(dst), "l"(m), "r"(bar), "r"(c0), "r"(c1), "r"(c2) : "memory");
}
__device__ __forceinline__ void w_prefetch(const void* src, uint32_t bytes) {
  asm volatile("{\n.reg .pred p;\nelect.sync _|p, 0xffffffff;\n@p cp.async.bulk.prefetch.L2.global [%0], %1;\n}" ::"l"(src), "r"(bytes) : "memory");
}
__device__ __forceinline__ void nb_sync(int id, int n) { asm volatile("bar.sync %0, %1;" ::"r"(id), "r"(n) : "memory"); }
__device__ __forceinline__ void nb_arrive(int id, int n) { asm volatile("bar.arrive %0, %1;" ::"r"(id), "r"(n) : "memory"); }
__device__ __forceinline__ void fence_async_smem() { asm volatile("fence.proxy.async.shared::cta;" ::: "memory"); }
__device__ __forceinline__ void fence_async_glob() { asm volatile("fence.proxy.async.global;" ::: "memory"); }
__device__ __forceinline__ void flag_after(void* p, uint32_t readback, uint32_t T, bool writer) {
  asm volatile("{\n.reg .pred p;\n.reg .u32 v;\nsetp.ne.u32 p, %3, 0;\nor.b32 v, %1, %2;\nmin.u32 v, v, %2;\n@p st.relaxed.gpu.global.u32 [%0], v;\n}"
               ::"l"(p), "r"(readback), "r"(T), "r"((uint32_t)writer) : "memory");
}
__device__ __forceinline__ uint4 ldg_rlx128(const void* p) { uint4 v; asm volatile("ld.relaxed.gpu.global.v4.b32 {%0,%1,%2,%3}, [%4];" : "=r"(v.x), "=r"(v.y), "=r"(v.z), "=r"(v.w) : "l"(p) : "memory"); return v; }
__device__ __forceinline__ uint2 ldg_rlx64(const void* p) { uint2 v; asm volatile("ld.relaxed.gpu.global.v2.b32 {%0,%1}, [%2];" : "=r"(v.x), "=r"(v.y) : "l"(p) : "memory"); return v; }
__device__ __forceinline__ void rld128(uint4& v, const void* p) { asm volatile("ld.relaxed.gpu.global.v4.b32 {%0,%1,%2,%3}, [%4];" : "+r"(v.x), "+r"(v.y), "+r"(v.z), "+r"(v.w) : "l"(p) : "memory"); }
__device__ __forceinline__ uint32_t ldg_rlx32(const void* p) { uint32_t v; asm volatile("ld.relaxed.gpu.global.b32 %0, [%1];" : "=r"(v) : "l"(p) : "memory"); return v; }
__device__ __forceinline__ uint4 ldg_nc128(const void* p) { uint4 v; asm volatile("ld.global.nc.v4.b32 {%0,%1,%2,%3}, [%4];" : "=r"(v.x), "=r"(v.y), "=r"(v.z), "=r"(v.w) : "l"(p)); return v; }
__device__ __forceinline__ uint32_t ldg_nc32(const void* p) { uint32_t v; asm volatile("ld.global.nc.L1::no_allocate.b32 %0, [%1];" : "=r"(v) : "l"(p)); return v; }
__device__ __forceinline__ void stg128(void* p, uint32_t a, uint32_t b, uint32_t c, uint32_t d) { asm volatile("st.relaxed.gpu.global.v4.b32 [%0], {%1,%2,%3,%4};" ::"l"(p), "r"(a), "r"(b), "r"(c), "r"(d) : "memory"); }
__device__ __forceinline__ void stg64(void* p, uint32_t a, uint32_t b) { asm volatile("st.relaxed.gpu.global.v2.b32 [%0], {%1,%2};" ::"l"(p), "r"(a), "r"(b) : "memory"); }
__device__ __forceinline__ void stg32(void* p, uint32_t a) { asm volatile("st.relaxed.gpu.global.b32 [%0], %1;" ::"l"(p), "r"(a) : "memory"); }
__device__ __forceinline__ void sts128(uint32_t a, uint32_t x, uint32_t y, uint32_t z, uint32_t w) { asm volatile("st.shared.v4.b32 [%0], {%1,%2,%3,%4};" ::"r"(a), "r"(x), "r"(y), "r"(z), "r"(w) : "memory"); }
__device__ __forceinline__ void sts64(uint32_t a, uint32_t x, uint32_t y) { asm volatile("st.shared.v2.b32 [%0], {%1,%2};" ::"r"(a), "r"(x), "r"(y) : "memory"); }
__device__ __forceinline__ void sts32(uint32_t a, uint32_t x) { asm volatile("st.shared.b32 [%0], %1;" ::"r"(a), "r"(x) : "memory"); }
__device__ __forceinline__ void stsf(uint32_t a, float x) { sts32(a, __float_as_uint(x)); }
__device__ __forceinline__ uint4 lds128(uint32_t a) { uint4 v; asm volatile("ld.shared.v4.b32 {%0,%1,%2,%3}, [%4];" : "=r"(v.x), "=r"(v.y), "=r"(v.z), "=r"(v.w) : "r"(a) : "memory"); return v; }
__device__ __forceinline__ uint2 lds64(uint32_t a) { uint2 v; asm volatile("ld.shared.v2.b32 {%0,%1}, [%2];" : "=r"(v.x), "=r"(v.y) : "r"(a) : "memory"); return v; }
__device__ __forceinline__ uint32_t lds32(uint32_t a) { uint32_t v; asm volatile("ld.shared.b32 %0, [%1];" : "=r"(v) : "r"(a) : "memory"); return v; }
__device__ __forceinline__ uint32_t pack_bf16(float lo, float hi) { uint32_t r; asm("cvt.rn.bf16x2.f32 %0, %1, %2;" : "=r"(r) : "f"(hi), "f"(lo)); return r; }
__device__ __forceinline__ float bf_lo(uint32_t w) { return __uint_as_float(w << 16); }
__device__ __forceinline__ float bf_hi(uint32_t w) { return __uint_as_float(w & 0xFFFF0000u); }
__device__ __forceinline__ float rbf(float x) { return bf_lo(pack_bf16(x, 0.f)); }
__device__ __forceinline__ float asf(uint32_t u) { return __uint_as_float(u); }
__device__ __forceinline__ uint32_t asu(float f) { return __float_as_uint(f); }
__device__ __forceinline__ float shx(float v, int m) { return __shfl_xor_sync(0xffffffffu, v, m); }
__device__ __forceinline__ uint32_t movm(uint32_t a) { uint32_t o; asm volatile("movmatrix.sync.aligned.m8n8.trans.b16 %0, %1;" : "=r"(o) : "r"(a)); return o; }
__device__ __forceinline__ void ldsm2(uint32_t& a, uint32_t& b, uint32_t addr) { asm volatile("ldmatrix.sync.aligned.m8n8.x2.shared.b16 {%0,%1}, [%2];" : "=r"(a), "=r"(b) : "r"(addr) : "memory"); }
__device__ __forceinline__ void ldsm4t(uint32_t* r, uint32_t addr) { asm volatile("ldmatrix.sync.aligned.m8n8.x4.trans.shared.b16 {%0,%1,%2,%3}, [%4];" : "=r"(r[0]), "=r"(r[1]), "=r"(r[2]), "=r"(r[3]) : "r"(addr) : "memory"); }
__device__ __forceinline__ void stsm4(uint32_t addr, uint32_t a, uint32_t b, uint32_t c, uint32_t d) { asm volatile("stmatrix.sync.aligned.m8n8.x4.shared.b16 [%0], {%1,%2,%3,%4};" ::"r"(addr), "r"(a), "r"(b), "r"(c), "r"(d) : "memory"); }
__device__ __forceinline__ void stsm2(uint32_t addr, uint32_t a, uint32_t b) { asm volatile("stmatrix.sync.aligned.m8n8.x2.shared.b16 [%0], {%1,%2};" ::"r"(addr), "r"(a), "r"(b) : "memory"); }
__device__ __forceinline__ void mma16(float* d, uint32_t a0, uint32_t a1, uint32_t a2, uint32_t a3, uint32_t b0, uint32_t b1) {
  asm volatile("mma.sync.aligned.m16n8k16.row.col.f32.bf16.bf16.f32 {%0,%1,%2,%3},{%4,%5,%6,%7},{%8,%9},{%0,%1,%2,%3};"
               : "+f"(d[0]), "+f"(d[1]), "+f"(d[2]), "+f"(d[3]) : "r"(a0), "r"(a1), "r"(a2), "r"(a3), "r"(b0), "r"(b1));
}
__device__ __forceinline__ void mma16z(float* d, uint32_t a0, uint32_t a1, uint32_t a2, uint32_t a3, uint32_t b0, uint32_t b1) {
  asm volatile("mma.sync.aligned.m16n8k16.row.col.f32.bf16.bf16.f32 {%0,%1,%2,%3},{%4,%5,%6,%7},{%8,%9},{%10,%10,%10,%10};"
               : "=f"(d[0]), "=f"(d[1]), "=f"(d[2]), "=f"(d[3]) : "r"(a0), "r"(a1), "r"(a2), "r"(a3), "r"(b0), "r"(b1), "f"(0.f));
}
__device__ __forceinline__ void mma8(float* d, uint32_t a0, uint32_t a1, uint32_t b0) {
  asm volatile("mma.sync.aligned.m16n8k8.row.col.f32.bf16.bf16.f32 {%0,%1,%2,%3},{%4,%5},{%6},{%0,%1,%2,%3};"
               : "+f"(d[0]), "+f"(d[1]), "+f"(d[2]), "+f"(d[3]) : "r"(a0), "r"(a1), "r"(b0));
}
__device__ __forceinline__ uint32_t pin(uint32_t v) { uint32_t r; asm volatile("shfl.sync.bfly.b32 %0, %1, 0, 31, 0xffffffff;" : "=r"(r) : "r"(v)); return r; }
__device__ __forceinline__ uint32_t pin0(uint32_t v) { uint32_t r; asm volatile("{\n.reg .u32 t;\nor.b32 t, %1, 1;\nbfind.shiftamt.u32 %0, t;\nshr.u32 %0, %0, 5;\n}" : "=r"(r) : "r"(v)); return r; }
__device__ __forceinline__ void mma8z(float* d, uint32_t a0, uint32_t a1, uint32_t b0) {
  asm volatile("mma.sync.aligned.m16n8k8.row.col.f32.bf16.bf16.f32 {%0,%1,%2,%3},{%4,%5},{%6},{%7,%7,%7,%7};"
               : "=f"(d[0]), "=f"(d[1]), "=f"(d[2]), "=f"(d[3]) : "r"(a0), "r"(a1), "r"(b0), "f"(0.f));
}
__device__ __forceinline__ void wg_fence() { asm volatile("wgmma.fence.sync.aligned;" ::: "memory"); }
__device__ __forceinline__ void wg_commit() { asm volatile("wgmma.commit_group.sync.aligned;" ::: "memory"); }
template <int N> __device__ __forceinline__ void wg_wait() { asm volatile("wgmma.wait_group.sync.aligned %0;" ::"n"(N) : "memory"); }
template <int N> __device__ __forceinline__ void fence_regs(float* d) {
#pragma unroll
  for (int k = 0; k < N; k++) asm volatile("" : "+f"(d[k])::"memory");
}
__host__ __device__ constexpr uint32_t DLO(uint32_t addr, uint32_t lbo) { return (addr >> 4) | ((lbo >> 4) << 16); }
__host__ __device__ constexpr uint32_t DHI(uint32_t sbo, uint32_t swz) { return (sbo >> 4) | (swz << 30); }
template <int N>
__device__ __forceinline__ void wait_flags(const void* base, const uint32_t V, const int lane) {
  const unsigned char* p = (const unsigned char*)base + lane * 32;
  const unsigned char* p2 = p + (lane < N - 32 ? 1024 : 0);
  uint32_t a0 = ldg_rlx32(p), a1 = N > 32 ? ldg_rlx32(p2) : V;
  __nanosleep(POLL_GAP);
  int n = 0;
#pragma unroll 1
  while (true) {
    const uint32_t b0 = ldg_rlx32(p), b1 = N > 32 ? ldg_rlx32(p2) : V;
    if (__all_sync(0xffffffffu, (int)((a0 - V) | (a1 - V)) >= 0)) break;
    a0 = ldg_rlx32(p); a1 = N > 32 ? ldg_rlx32(p2) : V;
    if (__all_sync(0xffffffffu, (int)((b0 - V) | (b1 - V)) >= 0)) break;
    if (++n > SPIN) TIMEOUT(__LINE__)
  }
}
__device__ __forceinline__ uint32_t ftag(float v, uint32_t par) { return (asu(v) & ~1u) | par; }
__device__ __forceinline__ uint32_t selu(uint32_t c, uint32_t a, uint32_t b) { uint32_t r; asm("{\n.reg .pred p;\nsetp.ne.u32 p, %1, 0;\nselp.b32 %0, %2, %3, p;\n}" : "=r"(r) : "r"(c), "r"(a), "r"(b)); return r; }
__device__ __forceinline__ float self(uint32_t c, float a, float b) { return asf(selu(c, asu(a), asu(b))); }
__device__ __forceinline__ uint32_t orx(uint32_t acc, uint32_t a, uint32_t ref) { uint32_t r; asm("lop3.b32 %0, %1, %2, %3, 0xF6;" : "=r"(r) : "r"(acc), "r"(a), "r"(ref)); return r; }
__device__ __forceinline__ uint32_t fkey(float r) {
  uint32_t u = asu(r);
  u = (u & 0x80000000u) ? ~u : (u | 0x80000000u);
  return (r == r) ? u : 0u;
}
__host__ __device__ constexpr int GI(int part, int t) { return t < 8 ? part * 8 + t : 24 + part; }

__device__ __forceinline__ void wgmma_ss_216(float* d, uint32_t al, uint32_t ah, uint32_t bl, uint32_t bh) {
  asm volatile("{\n.reg .b64 da, db;\nmov.b64 da, {%108, %109};\nmov.b64 db, {%110, %111};\n"
      "wgmma.mma_async.sync.aligned.m64n216k16.f32.bf16.bf16 {"
      "%0,%1,%2,%3,%4,%5,%6,%7,%8,%9,%10,%11,%12,%13,%14,%15,%16,%17,%18,%19,%20,%21,%22,%23,%24,%25,%26,"
      "%27,%28,%29,%30,%31,%32,%33,%34,%35,%36,%37,%38,%39,%40,%41,%42,%43,%44,%45,%46,%47,%48,%49,%50,%51,%52,%53,"
      "%54,%55,%56,%57,%58,%59,%60,%61,%62,%63,%64,%65,%66,%67,%68,%69,%70,%71,%72,%73,%74,%75,%76,%77,%78,%79,%80,"
      "%81,%82,%83,%84,%85,%86,%87,%88,%89,%90,%91,%92,%93,%94,%95,%96,%97,%98,%99,%100,%101,%102,%103,%104,%105,%106,%107"
      "}, da, db, 1, 1, 1, 0, 1;\n}\n"
      : "+f"(d[0]), "+f"(d[1]), "+f"(d[2]), "+f"(d[3]), "+f"(d[4]), "+f"(d[5]), "+f"(d[6]), "+f"(d[7]), "+f"(d[8]),
        "+f"(d[9]), "+f"(d[10]), "+f"(d[11]), "+f"(d[12]), "+f"(d[13]), "+f"(d[14]), "+f"(d[15]), "+f"(d[16]), "+f"(d[17]),
        "+f"(d[18]), "+f"(d[19]), "+f"(d[20]), "+f"(d[21]), "+f"(d[22]), "+f"(d[23]), "+f"(d[24]), "+f"(d[25]), "+f"(d[26]),
        "+f"(d[27]), "+f"(d[28]), "+f"(d[29]), "+f"(d[30]), "+f"(d[31]), "+f"(d[32]), "+f"(d[33]), "+f"(d[34]), "+f"(d[35]),
        "+f"(d[36]), "+f"(d[37]), "+f"(d[38]), "+f"(d[39]), "+f"(d[40]), "+f"(d[41]), "+f"(d[42]), "+f"(d[43]), "+f"(d[44]),
        "+f"(d[45]), "+f"(d[46]), "+f"(d[47]), "+f"(d[48]), "+f"(d[49]), "+f"(d[50]), "+f"(d[51]), "+f"(d[52]), "+f"(d[53]),
        "+f"(d[54]), "+f"(d[55]), "+f"(d[56]), "+f"(d[57]), "+f"(d[58]), "+f"(d[59]), "+f"(d[60]), "+f"(d[61]), "+f"(d[62]),
        "+f"(d[63]), "+f"(d[64]), "+f"(d[65]), "+f"(d[66]), "+f"(d[67]), "+f"(d[68]), "+f"(d[69]), "+f"(d[70]), "+f"(d[71]),
        "+f"(d[72]), "+f"(d[73]), "+f"(d[74]), "+f"(d[75]), "+f"(d[76]), "+f"(d[77]), "+f"(d[78]), "+f"(d[79]), "+f"(d[80]),
        "+f"(d[81]), "+f"(d[82]), "+f"(d[83]), "+f"(d[84]), "+f"(d[85]), "+f"(d[86]), "+f"(d[87]), "+f"(d[88]), "+f"(d[89]),
        "+f"(d[90]), "+f"(d[91]), "+f"(d[92]), "+f"(d[93]), "+f"(d[94]), "+f"(d[95]), "+f"(d[96]), "+f"(d[97]), "+f"(d[98]),
        "+f"(d[99]), "+f"(d[100]), "+f"(d[101]), "+f"(d[102]), "+f"(d[103]), "+f"(d[104]), "+f"(d[105]), "+f"(d[106]), "+f"(d[107])
      : "r"(al), "r"(ah), "r"(bl), "r"(bh));
}
__device__ __forceinline__ void wgmma_ss_72(float* d, uint32_t al, uint32_t ah, uint32_t bl, uint32_t bh) {
  asm volatile("{\n.reg .b64 da, db;\nmov.b64 da, {%36, %37};\nmov.b64 db, {%38, %39};\n"
      "wgmma.mma_async.sync.aligned.m64n72k16.f32.bf16.bf16 {"
      "%0,%1,%2,%3,%4,%5,%6,%7,%8,%9,%10,%11,%12,%13,%14,%15,%16,%17,%18,%19,%20,%21,%22,%23,%24,%25,%26,"
      "%27,%28,%29,%30,%31,%32,%33,%34,%35"
      "}, da, db, 1, 1, 1, 0, 1;\n}\n"
      : "+f"(d[0]), "+f"(d[1]), "+f"(d[2]), "+f"(d[3]), "+f"(d[4]), "+f"(d[5]), "+f"(d[6]), "+f"(d[7]), "+f"(d[8]),
        "+f"(d[9]), "+f"(d[10]), "+f"(d[11]), "+f"(d[12]), "+f"(d[13]), "+f"(d[14]), "+f"(d[15]), "+f"(d[16]), "+f"(d[17]),
        "+f"(d[18]), "+f"(d[19]), "+f"(d[20]), "+f"(d[21]), "+f"(d[22]), "+f"(d[23]), "+f"(d[24]), "+f"(d[25]), "+f"(d[26]),
        "+f"(d[27]), "+f"(d[28]), "+f"(d[29]), "+f"(d[30]), "+f"(d[31]), "+f"(d[32]), "+f"(d[33]), "+f"(d[34]), "+f"(d[35])
      : "r"(al), "r"(ah), "r"(bl), "r"(bh));
}
template <uint32_t BH>
__device__ __forceinline__ void wgmma_rs_216(float* d, uint32_t a0, uint32_t a1, uint32_t a2, uint32_t a3, uint32_t bl) {
  asm volatile("{\n.reg .b64 db;\nmov.b64 db, {%112, %113};\n"
      "wgmma.mma_async.sync.aligned.m64n216k16.f32.bf16.bf16 {"
      "%0,%1,%2,%3,%4,%5,%6,%7,%8,%9,%10,%11,%12,%13,%14,%15,%16,%17,%18,%19,%20,%21,%22,%23,%24,%25,%26,"
      "%27,%28,%29,%30,%31,%32,%33,%34,%35,%36,%37,%38,%39,%40,%41,%42,%43,%44,%45,%46,%47,%48,%49,%50,%51,%52,%53,"
      "%54,%55,%56,%57,%58,%59,%60,%61,%62,%63,%64,%65,%66,%67,%68,%69,%70,%71,%72,%73,%74,%75,%76,%77,%78,%79,%80,"
      "%81,%82,%83,%84,%85,%86,%87,%88,%89,%90,%91,%92,%93,%94,%95,%96,%97,%98,%99,%100,%101,%102,%103,%104,%105,%106,%107"
      "}, {%108,%109,%110,%111}, db, 1, 1, 1, 1;\n}\n"
      : "+f"(d[0]), "+f"(d[1]), "+f"(d[2]), "+f"(d[3]), "+f"(d[4]), "+f"(d[5]), "+f"(d[6]), "+f"(d[7]), "+f"(d[8]),
        "+f"(d[9]), "+f"(d[10]), "+f"(d[11]), "+f"(d[12]), "+f"(d[13]), "+f"(d[14]), "+f"(d[15]), "+f"(d[16]), "+f"(d[17]),
        "+f"(d[18]), "+f"(d[19]), "+f"(d[20]), "+f"(d[21]), "+f"(d[22]), "+f"(d[23]), "+f"(d[24]), "+f"(d[25]), "+f"(d[26]),
        "+f"(d[27]), "+f"(d[28]), "+f"(d[29]), "+f"(d[30]), "+f"(d[31]), "+f"(d[32]), "+f"(d[33]), "+f"(d[34]), "+f"(d[35]),
        "+f"(d[36]), "+f"(d[37]), "+f"(d[38]), "+f"(d[39]), "+f"(d[40]), "+f"(d[41]), "+f"(d[42]), "+f"(d[43]), "+f"(d[44]),
        "+f"(d[45]), "+f"(d[46]), "+f"(d[47]), "+f"(d[48]), "+f"(d[49]), "+f"(d[50]), "+f"(d[51]), "+f"(d[52]), "+f"(d[53]),
        "+f"(d[54]), "+f"(d[55]), "+f"(d[56]), "+f"(d[57]), "+f"(d[58]), "+f"(d[59]), "+f"(d[60]), "+f"(d[61]), "+f"(d[62]),
        "+f"(d[63]), "+f"(d[64]), "+f"(d[65]), "+f"(d[66]), "+f"(d[67]), "+f"(d[68]), "+f"(d[69]), "+f"(d[70]), "+f"(d[71]),
        "+f"(d[72]), "+f"(d[73]), "+f"(d[74]), "+f"(d[75]), "+f"(d[76]), "+f"(d[77]), "+f"(d[78]), "+f"(d[79]), "+f"(d[80]),
        "+f"(d[81]), "+f"(d[82]), "+f"(d[83]), "+f"(d[84]), "+f"(d[85]), "+f"(d[86]), "+f"(d[87]), "+f"(d[88]), "+f"(d[89]),
        "+f"(d[90]), "+f"(d[91]), "+f"(d[92]), "+f"(d[93]), "+f"(d[94]), "+f"(d[95]), "+f"(d[96]), "+f"(d[97]), "+f"(d[98]),
        "+f"(d[99]), "+f"(d[100]), "+f"(d[101]), "+f"(d[102]), "+f"(d[103]), "+f"(d[104]), "+f"(d[105]), "+f"(d[106]), "+f"(d[107])
      : "r"(a0), "r"(a1), "r"(a2), "r"(a3), "r"(bl), "n"(BH));
}

struct Ctx {
  int i, j, cta;
};
#define TSTAMP(k) do {} while (0)
#define PSTAMP(k) do {} while (0)
#define PROF_DUMP() do {} while (0)
#define PROF_END() do {} while (0)
#define GSTAMP(k) do {} while (0)
#define CSTAMP(k) STAMPIF(1, L * 40 + p * 20 + (k))

__device__ __forceinline__ int ffn_c32(int cta) { return 32 * cta; }
__device__ __forceinline__ int ffn_c8(int cta) { return 4096 + 8 * (cta >> 1); }
__device__ __forceinline__ void load_gu(const Params& P, const int cta_, const int mat, const int b, const uint32_t bar) {
  const int cta = cta_;
  w_tma2d(sb + SM_G + mat * 46080 + b * 6144, &P.mg + mat, ffn_c32(cta), b * 96, bar);
  if (cta & 1) w_tma2d(sb + SM_G + mat * 46080 + 36864 + b * 1536, &P.mg8 + mat, ffn_c8(cta), b * 96, bar);
}

struct Winner { float r, m, rstd; int ci, rr; };

__device__ __forceinline__ Winner poll_winner(const void* p, uint4 v, const uint32_t tg) {
  int n = 0;
#pragma unroll 1
  while (!__all_sync(0xffffffffu, ((v.y ^ (tg << 6)) >> 6) == 0)) {
    rld128(v, p);
    if (++n > SPIN) TIMEOUT(__LINE__)
  }
  uint32_t key = fkey(asf(v.x));
  uint32_t mx = __reduce_max_sync(0xffffffffu, key);
  int src = __ffs(__ballot_sync(0xffffffffu, key == mx)) - 1;
  Winner w;
  w.ci = src;
  w.r = asf(__shfl_sync(0xffffffffu, v.x, src));
  w.rr = (int)__shfl_sync(0xffffffffu, v.y, src) & 63;
  w.m = asf(__shfl_sync(0xffffffffu, v.z, src));
  w.rstd = asf(__shfl_sync(0xffffffffu, v.w, src));
  return w;
}

__device__ __forceinline__ float2 row_stats(const Params& P, const int r, const int lane) {
  const unsigned char* src = (const unsigned char*)P.x + (((r & ~127) + 2 * (r & 63) + ((r >> 6) & 1)) * 1152 + (lane & 15) * 16);
  uint4 v[4];
#pragma unroll
  for (int m = 0; m < 4; m++) v[m] = ldg_nc128(src + m * 256);
  uint2 v4;
  asm volatile("ld.global.nc.v2.b32 {%0,%1}, [%2];" : "=r"(v4.x), "=r"(v4.y) : "l"(src + (1024 - (lane & 15) * 8)));
  nb_arrive(NB_START, 288 + pin0(v4.x));
  const float sft = __shfl_sync(0xffffffffu, bf_lo(v[0].x), lane & 16);
  float s1 = 0.f, s2 = 0.f, s3 = 0.f;
#pragma unroll
  for (int e = 0; e < 18; e++) {
    const uint32_t u = e < 16 ? (&v[0].x)[e] : (&v4.x)[e - 16];
    const float d0 = bf_lo(u) - sft, d1 = bf_hi(u) - sft;
    s1 += d0 + d1; s2 = fmaf(d0, d0, s2); s3 = fmaf(d1, d1, s3);
  }
  s2 += s3;
#pragma unroll
  for (int o = 1; o < 16; o <<= 1) { s1 += shx(s1, o); s2 += shx(s2, o); }
  s1 *= (1.f / 576.f);
  return make_float2(s1 + sft, rsq(fmaxf(s2 * (1.f / 576.f) - s1 * s1, 0.f) + EPS));
}

struct Unit { uint4 v[3]; };
__device__ __forceinline__ Unit unit_load(const unsigned char* src) {
  Unit u;
#pragma unroll
  for (int m = 0; m < 3; m++) u.v[m] = ldg_nc128(src + m * 48);
  return u;
}
__device__ __forceinline__ uint32_t unit_store(unsigned char* sc, const Unit& u, const int lane, const uint32_t o0, const uint32_t o1, const uint32_t o2) {
  stg128(sc + o0, u.v[0].x, u.v[0].y, u.v[0].z, u.v[0].w);
  stg128(sc + o1, u.v[1].x, u.v[1].y, u.v[1].z, u.v[1].w);
  stg128(sc + o2, u.v[2].x, u.v[2].y, u.v[2].z, u.v[2].w);
  return ldg_rlx32(sc + ((lane & 3) == 0 ? o0 : (lane & 3) == 1 ? o1 : o2));
}

__device__ __forceinline__ void consumer_role(const Ctx& cx, const Params& P, const unsigned char* smem, const int p, const int w, const int lane_) {
  int lane = lane_;
#define g (lane >> 2)
#define q (lane & 3)
#define first_lane (lane == 0)
  const int i = cx.i, j = cx.j, ip = i * 2 + p;
  unsigned char* const sc = (unsigned char*)P.sc;
  float m_lo = 0.f, m_hi = 0.f, rs_lo = 0.f, rs_hi = 0.f;
  uint32_t T = ldg_rlx32(P.sc->cflag[ip][j * 4 + w]);
  nb_sync(NB_ORD, 352);
  if (X_DELAY) { const int c0 = clock(); while ((int)(clock() - c0) < X_DELAY + (p * 4 + w) * X_STEP) {} }
  {
    const int t = min(w * 32 + lane, 95);
    uint32_t u0 = 0, u1 = 0, u2 = 0, u = 0;
    if (p == 0) {
      u0 = ldg_nc32((const uint32_t*)P.wr + t); u1 = ldg_nc32((const uint32_t*)P.wr + 96 + t); u2 = ldg_nc32((const uint32_t*)P.wr + 192 + t);
      u = ldg_nc32((const uint32_t*)P.wr + 36 * j + min(t, 35));
    }
    const int r = cx.cta * 16 + (p * 4 + w) * 2 + (lane >> 4);
    const float2 st = row_stats(P, r, lane);
    T = __shfl_sync(0xffffffffu, (T >> 3) + 1, 0);
    if ((lane & 15) == 0) stg128(sc + (OFF(st0) + r * 16), asu(st.x), asu(st.y), T, 0u);
    STAMPIF(1, 111);
    if (p == 0) {
      float s = (bf_lo(u0) + bf_hi(u0)) + (bf_lo(u1) + bf_hi(u1)) + (bf_lo(u2) + bf_hi(u2));
#pragma unroll
      for (int o = 1; o < 32; o <<= 1) s += shx(s, o);
      stsf(sb + SM_WR + 288 + w * 4, s);
      sts64(sb + SM_WR + min(t, 35) * 8, u << 16, u & 0xFFFF0000u);
    }
  }
#pragma unroll 1
  for (int L = 0; L < 2; L++) {
    lane = pin(lane);
    const uint32_t tg = 2 * T + L;
    float c_lo = 0.f, c_hi = 0.f;
    bool sel_lo = false, sel_hi = false;
    float acc[108];
#pragma unroll
    for (int k = 0; k < 108; k++) acc[k] = 0.f;
    fence_regs<108>(acc);
    {
      const uint32_t ah = L == 0 ? DHI(1024, 1) : DHI(128, 0);
      const uint32_t astep = L == 0 ? 2 : 128;
      const uint32_t a0 = (L == 0 ? DLO(sb + SM_A, 16) : DLO(sb + SM_A, 1024)) + p * 512;
      constexpr uint32_t bh = DHI(512, 0);
      if (L == 1) {
        const float ul = 1.f + rs_lo, uh = 1.f + rs_hi;
        const float vl = fmaxf(rcp(rs_lo * rs_lo) - EPS, 0.f), vh = fmaxf(rcp(rs_hi * rs_hi) - EPS, 0.f);
        c_lo = ul * rsq(vl * ul * ul + EPS);
        c_hi = uh * rsq(vh * uh * uh + EPS);
      }
      if (L == 1) mbar_wait(sb + BAR_AFULL + p * 8, 0);
      mbar_wait(sb + BAR_FULL, 0);
      if (L == 1 && p == 1) nb_sync(NB_FFN2, 224);
      CSTAMP(0); GSTAMP(120 + 2 * L);
      uint32_t e0 = 0, e1 = 0;
      bool prepped = false, gone = false;
      auto prep_ext = [&]() {
        const int row = p * 64 + w * 16 + g;
        if (L == 0) {
          const uint2 u0 = lds64(sb + SM_R + row * 8), u1 = lds64(sb + SM_R + row * 8 + 64);
          m_lo = asf(u0.x); c_lo = asf(u0.y); m_hi = asf(u1.x); c_hi = asf(u1.y);
        } else {
          const uint4 sv = lds128(sb + SM_SEL);
          sel_lo = (int)sv.x == row; sel_hi = (int)sv.x == row + 8;
          if (sel_lo) { m_lo = asf(sv.z); c_lo = asf(sv.w); }
          if (sel_hi) { m_hi = asf(sv.z); c_hi = asf(sv.w); }
        }
        const float hl = rbf(-m_lo), hh = rbf(-m_hi);
        const uint32_t em = selu(lane & 1, 0x0000FFFFu, 0xFFFFFFFFu);
        e0 = selu(lane & 2, selu(sel_lo && !(lane & 1), 0x3F803F80u, 0u), pack_bf16(hl, -m_lo - hl) & em);
        e1 = selu(lane & 2, selu(sel_hi && !(lane & 1), 0x3F803F80u, 0u), pack_bf16(hh, -m_hi - hh) & em);
      };
      bool pend = false;
#pragma unroll 1
      for (int r = 0; r < 3; r++) {
#pragma unroll
        for (int h = 0; h < 6; h++) {
          const uint32_t al = a0 + (h >> 1) * 1024 + (h & 1) * 2 * astep, bl = DLO(sb + SM_B, 128) + h * 864;
          const uint32_t nb = sb + BAR_FULL + ((h + 1) % 6) * 8, np = (r + (h == 5)) & 1;
          TSTAMP((6 * r + h) * 2);
          wg_fence();
          wgmma_ss_216(acc, al, ah, bl, bh);
          wgmma_ss_216(acc, al + astep, ah, bl + 16, bh);
          wg_commit();
          if (h == 5 && r == 2) break;
          const uint32_t ok = mbar_test(nb, np);
          if ((h == 1 || h == 3) && r == 0 && L == 1) mbar_wait(sb + BAR_AFULL + (h + 1 + p) * 8, 0);
          if (h == 0 && r == 1 && L == 0) {
          if (lane < 16) stg128(sc + (OFF(stats) + (ip * 4 + w) * 2048 + j * 256 + lane * 16), 0u, 0u, 0u, 0u);
          if (w == 3 && i < 15 && lane < 28) {
#pragma unroll
            for (int e = 0; e < 6; e++) stg128(sc + (OFF(halo) + ((ip + 2) * 8 + j) * 2688 + lane * 16) + e * 448, 0u, 0u, 0u, 0u);
          }
          if (w == 0 && lane < 2) stg128(sc + (OFF(cand) + (j * 32 + ip) * (CAND_W * 4) + lane * 16), 0u, 0u, 0u, 0u);
          }
          wg_wait<1>();
          if (first_lane && pend) mbar_arrive(sb + BAR_EMPTY + ((h + 5) % 6) * 8);
          pend = true;
          const bool hold = h == HOLD_C % 6 && r == HOLD_C / 6 && p == 1;
          if (hold || (!ok && !mbar_test(nb, np))) {
            wg_wait<0>();
            if (first_lane) mbar_arrive(sb + BAR_EMPTY + h * 8);
            pend = false;
            TSTAMP((6 * r + h) * 2 + 1);
            mbar_wait(nb, np);
            if (hold) {
              if (mbar_test(sb + BAR_FIX + 8, L)) { prep_ext(); prepped = true; }
              nb_sync(NB_STAG, 256);
            }
          }
        }
      }
      if (!prepped) {
        if (p == 0 && !gone && !mbar_test(sb + BAR_FIX, L)) { nb_arrive(NB_STAG, 256); gone = true; }
        mbar_wait(sb + BAR_FIX + p * 8, L);
        prep_ext();
      }
      wg_fence();
      wgmma_rs_216<DHI(128, 0)>(acc, e0, e1, 0u, 0u, DLO(sb + SM_BEXT, 0));
      wg_commit();
      if (p == 0 && !gone) nb_arrive(NB_STAG, 256);
      wg_wait<2>();
      if (first_lane && pend) mbar_arrive(sb + BAR_EMPTY + 32);
    }
    lane = pin(lane);
    const uint32_t fragoff = ip * 73728 + (9 * j) * 1024 + w * 256 + lane * 4;
    const uint32_t rboff = (min(lane, 17) >> 1) * 1024 + (lane < 18 ? lane & 1 : 0) * 128;
    const uint32_t hl16 = (lane < 4 ? lane : lane - 4) * 16;
    const uint32_t o_halo = pin(OFF(halo) + ((ip + (w == 3 ? 2 : 0)) * 8 + j) * 2688 + hl16);
    const uint32_t o_o = pin(OFF(obuf) + fragoff);
    nb_sync(NB_WG + p, 128);
    if ((o_halo | o_o) == 0xFFFFFFFFu) __trap();
    wg_wait<0>();
    fence_regs<108>(acc);
    if (first_lane) mbar_arrive(sb + BAR_EMPTY + 40);
    CSTAMP(1); GSTAMP(121 + 2 * L);
    {
      uint32_t Kh[9], Vh[9], Kl[9], Vl[9], Kx[9], Vx[9], Ql[9], Qh[9];
#pragma unroll
      for (int t = 0; t < 9; t++) {
        Kh[t] = pack_bf16(acc[4 * GI(1, t) + 2] * c_hi, acc[4 * GI(1, t) + 3] * c_hi);
        Vh[t] = pack_bf16(acc[4 * GI(2, t) + 2] * c_hi, acc[4 * GI(2, t) + 3] * c_hi);
        Ql[t] = pack_bf16(acc[4 * GI(0, t)], acc[4 * GI(0, t) + 1]);
        Qh[t] = pack_bf16(acc[4 * GI(0, t) + 2], acc[4 * GI(0, t) + 3]);
      }
      const uint32_t hbuf = sb + SM_A + p * 8192 + w * 2688 + hl16;
      if (w < 3) {
        if (lane >= 4) {
#pragma unroll
          for (int e = 0; e < 4; e++) sts128(hbuf + e * 448, Kh[2 * e], Kh[2 * e + 1], Vh[e], tg);
          sts128(hbuf + 4 * 448, Kh[8], Vh[4], Vh[5], tg);
          sts128(hbuf + 5 * 448, Vh[6], Vh[7], Vh[8], tg);
        }
      } else if (i < 15 && lane >= 4) {
#pragma unroll
        for (int e = 0; e < 4; e++) stg128(sc + o_halo + e * 448, Kh[2 * e], Kh[2 * e + 1], Vh[e], tg);
        stg128(sc + o_halo + 4 * 448, Kh[8], Vh[4], Vh[5], tg);
        stg128(sc + o_halo + 5 * 448, Vh[6], Vh[7], Vh[8], tg);
      }
      nb_sync(NB_WG + p, 128);
#pragma unroll
      for (int t = 0; t < 9; t++) {
        Kl[t] = pack_bf16(acc[4 * GI(1, t)] * c_lo, acc[4 * GI(1, t) + 1] * c_lo);
      }
#pragma unroll
      for (int t = 0; t < HALO_V; t++) Vl[t] = pack_bf16(acc[4 * GI(2, t)] * c_lo, acc[4 * GI(2, t) + 1] * c_lo);
      uint32_t dep = (Kl[0] ^ Kl[1] ^ Kl[2]) | (Kl[3] ^ Kl[4] ^ Kl[5]) | (Kl[6] ^ Kl[7] ^ Kl[8]);
#pragma unroll
      for (int t = 0; t < HALO_V; t += 3) dep |= Vl[t] ^ Vl[t + 1] ^ Vl[t + 2];
      const unsigned char* hp = (w > 0 ? smem + (hbuf - 2688 - sb) : sc + o_halo) + pin0(dep);
      uint4 hv[6];
#pragma unroll
      for (int e = 0; e < 6; e++)
        asm volatile("ld.relaxed.gpu.v4.b32 {%0,%1,%2,%3}, [%4];" : "=r"(hv[e].x), "=r"(hv[e].y), "=r"(hv[e].z), "=r"(hv[e].w) : "l"(hp + e * 448) : "memory");
      CSTAMP(2);
#pragma unroll
      for (int t = 0; t < 9; t++) {
        if (t >= HALO_V) Vl[t] = pack_bf16(acc[4 * GI(2, t)] * c_lo, acc[4 * GI(2, t) + 1] * c_lo);
        Vl[t] = movm(Vl[t]);
        Vh[t] = movm(Vh[t]);
      }
      uint32_t qa[4][2], qb[4][2];
      float s1[4][4], s2[4][4];
#pragma unroll
      for (int h = 0; h < 4; h++) {
        qa[h][0] = q >= h ? Ql[2 * h] : 0u; qa[h][1] = q >= h ? Qh[2 * h] : 0u;
        qb[h][0] = q <= h ? Ql[2 * h + 2] : 0u; qb[h][1] = q <= h ? Qh[2 * h + 2] : 0u;
      }
      const bool first = (i == 0 && w == 0);
      if (w == 0 && i > 0) {
        int n = 0;
#pragma unroll 1
        while (__any_sync(0xffffffffu, (orx(orx(orx(0, hv[0].w, tg), hv[1].w, tg), hv[2].w, tg) | orx(orx(orx(0, hv[3].w, tg), hv[4].w, tg), hv[5].w, tg)) != 0)) {
#pragma unroll
          for (int e = 0; e < 6; e++) rld128(hv[e], sc + o_halo + e * 448);
          if (++n > SPIN) TIMEOUT(__LINE__)
        }
      }
#pragma unroll
      for (int e = 0; e < 4; e++) { Kx[2 * e] = hv[e].x; Kx[2 * e + 1] = hv[e].y; Vx[e] = hv[e].z; }
      Kx[8] = hv[4].x; Vx[4] = hv[4].y; Vx[5] = hv[4].z; Vx[6] = hv[5].x; Vx[7] = hv[5].y; Vx[8] = hv[5].z;
      CSTAMP(3);
#pragma unroll
      for (int t = 0; t < 9; t++) Vx[t] = movm(Vx[t]);
#pragma unroll
      for (int h = 0; h < 4; h++) { mma8z(s1[h], qb[h][0], qb[h][1], Kl[2 * h + 2]); mma8z(s2[h], qb[h][0], qb[h][1], Kh[2 * h + 2]); }
#pragma unroll
      for (int h = 0; h < 4; h++) {
        mma16(s1[h], qa[h][0], qa[h][1], Ql[2 * h + 1], Qh[2 * h + 1], Kl[2 * h], Kl[2 * h + 1]);
        mma16(s2[h], qa[h][0], qa[h][1], Ql[2 * h + 1], Qh[2 * h + 1], Kh[2 * h], Kh[2 * h + 1]);
      }
      float s0[4][4];
#pragma unroll
      for (int h = 0; h < 4; h++) mma8z(s0[h], qb[h][0], qb[h][1], Kx[2 * h + 2]);
#pragma unroll
      for (int h = 0; h < 4; h++) mma16(s0[h], qa[h][0], qa[h][1], Ql[2 * h + 1], Qh[2 * h + 1], Kx[2 * h], Kx[2 * h + 1]);
      const bool pv0 = 2 * q > g, pv1 = 2 * q + 1 > g;
      const uint32_t PM = (pv0 ? 0x0000FFFFu : 0u) | (pv1 ? 0xFFFF0000u : 0u);
      const float kS = 0.23570226039551584f * 1.4426950408889634f;
      const float sc_lo = c_lo * kS, sc_hi = c_hi * kS;
      float sl[4][2], sh[4][2], ml[4], mh[4];
#pragma unroll
      for (int h = 0; h < 4; h++) {
        sh[h][0] = pv0 ? s1[h][2] : s2[h][2];
        sh[h][1] = pv1 ? s1[h][3] : s2[h][3];
        mh[h] = fmaxf(sh[h][0], sh[h][1]);
        sl[h][0] = pv0 ? (first ? -INFINITY : s0[h][0]) : s1[h][0];
        sl[h][1] = pv1 ? (first ? -INFINITY : s0[h][1]) : s1[h][1];
        ml[h] = fmaxf(sl[h][0], sl[h][1]);
      }
#pragma unroll
      for (int s = 1; s <= 2; s <<= 1) {
        float tl[4], th[4];
#pragma unroll
        for (int h = 0; h < 4; h++) { th[h] = shx(mh[h], s); tl[h] = shx(ml[h], s); }
#pragma unroll
        for (int h = 0; h < 4; h++) { mh[h] = fmaxf(mh[h], th[h]); ml[h] = fmaxf(ml[h], tl[h]); }
      }
      float o[4][3][4], den[4][4];
      uint32_t px[4];
#pragma unroll
      for (int h = 0; h < 4; h++) {
        const float bl = -ml[h] * sc_lo, bh = -mh[h] * sc_hi;
        const uint32_t pl = pack_bf16(ex2(fmaf(sl[h][0], sc_lo, bl)), ex2(fmaf(sl[h][1], sc_lo, bl)));
        const uint32_t ph = pack_bf16(ex2(fmaf(sh[h][0], sc_hi, bh)), ex2(fmaf(sh[h][1], sc_hi, bh)));
        mma8z(den[h], pl, ph, 0x3F803F80u);
        px[h] = pl & PM;
#pragma unroll
        for (int u = 0; u < 3; u++) mma16z(o[h][u], pl & ~PM, ph & PM, 0u, ph & ~PM, Vl[2 * h + u], Vh[2 * h + u]);
      }
#pragma unroll
      for (int h = 0; h < 4; h++)
#pragma unroll
        for (int u = 0; u < 3; u++) mma8(o[h][u], px[h], 0u, Vx[2 * h + u]);
      float il[4], ih[4];
#pragma unroll
      for (int h = 0; h < 4; h++) { il[h] = rcp(den[h][0]); ih[h] = rcp(den[h][2]); }
#pragma unroll
      for (int t = 0; t < 9; t++) {
        const int h = t == 8 ? 3 : t >> 1, u = t == 8 ? 2 : t & 1;
        float v0 = o[h][u][0], v1 = o[h][u][1], v2 = o[h][u][2], v3 = o[h][u][3], kl = il[h], kh = ih[h];
        if (u == 0 && h > 0 && q < h) {
          v0 = o[h - 1][2][0]; v1 = o[h - 1][2][1]; v2 = o[h - 1][2][2]; v3 = o[h - 1][2][3]; kl = il[h - 1]; kh = ih[h - 1];
        }
        stg32(sc + o_o + t * 1024, pack_bf16(v0 * kl, v1 * kl));
        stg32(sc + o_o + t * 1024 + 128, pack_bf16(v2 * kh, v3 * kh));
      }
    }
    CSTAMP(4);
    const uint32_t rbo = ldg_rlx32(sc + (o_o + rboff));
    lane = pin(lane);
    const uint32_t o_x = o_o + (OFF(xbuf) - OFF(obuf)), o_xrb = o_x + rboff;
    const uint32_t o_cf = OFF(cflag) + (ip * 32 + j * 4 + w) * 32 + lane * 4;
    if (L == 1 && first_lane) mbar_arrive(sb + BAR_HDONE + p * 8);
    flag_after(sc + o_cf, rbo, 8 * T + 2 * L, lane < 8);
    STAMPD(asf(rbo), L * 40 + p * 20 + 13);
    uint32_t resid[18];
    mbar_wait(sb + BAR_FULL + 16, 1); mbar_wait(sb + BAR_FULL + 32, 1);
    if (L == 0) {
      const uint32_t ra = sb + SM_A + (2 + p) * 8192 + (w * 16 + (lane & 15)) * 128;
#pragma unroll
      for (int t = 0; t < 9; t++) ldsm2(resid[2 * t], resid[2 * t + 1], ra + ((j + t) >> 3) * 16384 + ((((j + t) ^ lane) & 7) << 4));
      if (first_lane) mbar_arrive(sb + BAR_HDONE + p * 8 + pin0(resid[17]));
    } else {
#pragma unroll
      for (int t = 0; t < 9; t++) { resid[2 * t] = ldg_rlx32(sc + o_x + t * 1024); resid[2 * t + 1] = ldg_rlx32(sc + o_x + t * 1024 + 128); }
    }
    const uint32_t o_st = OFF(stats) + (ip * 4 + w) * 2048;
    const uint32_t o_stw = pin(o_st + j * 256 + (g + 8 * (q & 1)) * 16), o_str = pin(o_st + q * 512 + g * 16);
    const uint32_t o_cand = pin(OFF(cand) + (j * 32 + ip) * (CAND_W * 4) + q * 16);
    const uint32_t o_xc = pin(OFF(xcand) + (ip * 8 + j) * 192 + q * 16);
    float accw[36];
    float wr[18];
#pragma unroll
    for (int t = 0; t < 9; t++) { const uint2 u = lds64(sb + SM_WR + t * 32 + q * 8); wr[2 * t] = asf(u.x); wr[2 * t + 1] = asf(u.y); }
    const uint4 ws4 = lds128(sb + SM_WR + 288);
    const float wsum = asf(pin(asu(asf(ws4.x) + asf(ws4.y) + asf(ws4.z))));
    {
      float ul = 1.f, uh = 1.f, vl = 0.f, vh = 0.f;
      if (L == 1) {
        ul += rs_lo; uh += rs_hi; vl = -m_lo * rs_lo; vh = -m_hi * rs_hi;
        if (sel_lo || sel_hi) {
#pragma unroll
          for (int t = 0; t < 9; t++) {
            const uint32_t z = lds32(sb + SM_X2S + t * 16 + q * 4);
            if (sel_hi) resid[2 * t + 1] = z; else resid[2 * t] = z;
          }
          if (sel_hi) { uh = 1.f; vh = 0.f; } else { ul = 1.f; vl = 0.f; }
        }
        __syncwarp();
      }
#pragma unroll
      for (int t = 0; t < 9; t++) {
        accw[4 * t] = fmaf(bf_lo(resid[2 * t]), ul, vl); accw[4 * t + 1] = fmaf(bf_hi(resid[2 * t]), ul, vl);
        accw[4 * t + 2] = fmaf(bf_lo(resid[2 * t + 1]), uh, vh); accw[4 * t + 3] = fmaf(bf_hi(resid[2 * t + 1]), uh, vh);
      }
    }
    fence_regs<36>(accw);
    mbar_wait(sb + BAR_FULL, 1); mbar_wait(sb + BAR_FULL + 8, 1); mbar_wait(sb + BAR_FULL + 24, 1); mbar_wait(sb + BAR_FULL + 40, 1);
    {
      uint32_t wf = sb + BAR_WFULL + p * 72;
      uint32_t bl = DLO(sb + SM_B, 128);
      uint32_t half = p;
      mbar_wait(wf, L);
      CSTAMP(5);
#pragma unroll 1
      for (int c3 = 0; c3 < 3; c3++) {
        const uint32_t al = DLO(sb + SM_A, 1024) + half * 512;
        const uint32_t ae = sb + BAR_AEMPTY + half * 24;
#pragma unroll
        for (int cc = 0; cc < 3; cc++) {
          TSTAMP(36 + (c3 * 3 + cc) * 2);
          wg_fence();
          wgmma_ss_72(accw, al + cc * 1024, DHI(128, 0), bl + cc * 576, DHI(256, 0));
          wgmma_ss_72(accw, al + cc * 1024 + 128, DHI(128, 0), bl + cc * 576 + 144, DHI(256, 0));
          const uint32_t ok = mbar_test(wf + cc * 8 + 8, L);
          wgmma_ss_72(accw, al + cc * 1024 + 256, DHI(128, 0), bl + cc * 576 + 288, DHI(256, 0));
          wgmma_ss_72(accw, al + cc * 1024 + 384, DHI(128, 0), bl + cc * 576 + 432, DHI(256, 0));
          wg_commit();
          wg_wait<1>();
          if (cc > 0) { if (first_lane) { mbar_arrive(ae + cc * 8 - 8); if (cc == 2) mbar_arrive(sb + BAR_EMPTY + c3 * 16); } }
          else if (first_lane && c3 > 0) { mbar_arrive(sb + BAR_AEMPTY + 40 - half * 24); mbar_arrive(sb + BAR_EMPTY + c3 * 16 - 8); }
          if (!ok && (cc < 2 || c3 < 2)) mbar_wait(wf + cc * 8 + 8, L);
        }
        wf += 24; bl += 1728; half ^= 1;
      }
    }
    wg_wait<0>();
    fence_regs<36>(accw);
    if (first_lane) { mbar_arrive(sb + BAR_AEMPTY + (2 + 3 * p) * 8); mbar_arrive(sb + BAR_EMPTY + 40); }
    CSTAMP(6);
    uint32_t xw[18];
    uint32_t rb = 0;
    if (L == 0 && p == 0) {
#pragma unroll
      for (int t = 0; t < 9; t++) {
        stg32(sc + o_x + t * 1024, pack_bf16(accw[4 * t], accw[4 * t + 1]));
        stg32(sc + o_x + t * 1024 + 128, pack_bf16(accw[4 * t + 2], accw[4 * t + 3]));
      }
      rb = ldg_rlx32(sc + o_xrb);
      fence_regs<36>(accw);
    }
    {
      float a0[2] = {0.f, 0.f}, a1[2] = {0.f, 0.f}, a2[2] = {0.f, 0.f}, b0[2] = {0.f, 0.f}, b1[2] = {0.f, 0.f}, b2[2] = {0.f, 0.f};
#pragma unroll
      for (int t = 0; t < 9; t++) {
#pragma unroll
        for (int e = 0; e < 2; e++) {
          const float x = accw[4 * t + e], y = accw[4 * t + 2 + e];
          a0[e] += x; a1[e] = fmaf(x, x, a1[e]); a2[e] = fmaf(x, wr[2 * t + e], a2[e]);
          b0[e] += y; b1[e] = fmaf(y, y, b1[e]); b2[e] = fmaf(y, wr[2 * t + e], b2[e]);
        }
      }
      const bool od = q & 1;
      const float A0 = a0[0] + a0[1], A1 = a1[0] + a1[1], A2 = a2[0] + a2[1], B0 = b0[0] + b0[1], B1 = b1[0] + b1[1], B2 = b2[0] + b2[1];
      float k0 = od ? B0 : A0, k1 = od ? B1 : A1, k2 = od ? B2 : A2;
      k0 += shx(od ? A0 : B0, 1); k1 += shx(od ? A1 : B1, 1); k2 += shx(od ? A2 : B2, 1);
      k0 += shx(k0, 2); k1 += shx(k1, 2); k2 += shx(k2, 2);
      if (q < 2) stg128(sc + o_stw, asu(k0), asu(k1), asu(k2), tg);
      STAMPD(k0, L * 40 + p * 20 + 14);
    }
#pragma unroll
    for (int t = 0; t < 9; t++) {
      xw[2 * t] = pack_bf16(accw[4 * t], accw[4 * t + 1]);
      xw[2 * t + 1] = pack_bf16(accw[4 * t + 2], accw[4 * t + 3]);
    }
    float r_lo, r_hi;
    {
      uint4 u0 = ldg_rlx128(sc + o_str), u1 = ldg_rlx128(sc + o_str + 256), u2 = ldg_rlx128(sc + o_str + 128), u3 = ldg_rlx128(sc + o_str + 384);
      flag_after(sc + o_cf, rb, 8 * T + 1, lane < 8 && L == 0 && p == 0);
      STAMPD(asf(u3.w), L * 40 + p * 20 + 15);
      int n = 0;
#pragma unroll 1
      while (__any_sync(0xffffffffu, orx(orx(orx(orx(0, u0.w, tg), u1.w, tg), u2.w, tg), u3.w, tg) != 0)) {
        rld128(u0, sc + o_str); rld128(u1, sc + o_str + 256); rld128(u2, sc + o_str + 128); rld128(u3, sc + o_str + 384);
        if (++n > SPIN) TIMEOUT(__LINE__)
      }
      float a0 = asf(u0.x) + asf(u1.x), a1 = asf(u0.y) + asf(u1.y), a2 = asf(u0.z) + asf(u1.z);
      float b0 = asf(u2.x) + asf(u3.x), b1 = asf(u2.y) + asf(u3.y), b2 = asf(u2.z) + asf(u3.z);
#pragma unroll
      for (int s = 1; s <= 2; s <<= 1) {
        const float t0 = shx(a0, s), t1 = shx(a1, s), t2 = shx(a2, s), t3 = shx(b0, s), t4 = shx(b1, s), t5 = shx(b2, s);
        a0 += t0; a1 += t1; a2 += t2; b0 += t3; b1 += t4; b2 += t5;
      }
      m_lo = a0 * (1.f / 576.f); m_hi = b0 * (1.f / 576.f);
      rs_lo = rsq(fmaxf(a1 * (1.f / 576.f) - m_lo * m_lo, 0.f) + EPS);
      rs_hi = rsq(fmaxf(b1 * (1.f / 576.f) - m_hi * m_hi, 0.f) + EPS);
      r_lo = (a2 - m_lo * wsum) * rs_lo; r_hi = (b2 - m_hi * wsum) * rs_hi;
    }
    CSTAMP(7);
    int candrow = -1;
    {
      const uint32_t kl = fkey(r_lo), kh = fkey(r_hi);
      const bool hi = kh > kl;
      const uint32_t kb = hi ? kh : kl;
      const uint32_t mx = __reduce_max_sync(0xffffffffu, kb);
      if (first_lane) sts32(sb + SM_BEST + p * 16 + w * 4, mx);
      const uint32_t bal = __ballot_sync(0xffffffffu, kb == mx);
      const bool mine = (bal & ((1u << (lane & 28)) - 1u)) == 0u && kb == mx;
      const uint32_t x0 = hi ? xw[1] : xw[0], x1 = hi ? xw[3] : xw[2], x2 = hi ? xw[5] : xw[4], x3 = hi ? xw[7] : xw[6], x4 = hi ? xw[9] : xw[8];
      const uint32_t x5 = hi ? xw[11] : xw[10], x6 = hi ? xw[13] : xw[12], x7 = hi ? xw[15] : xw[14], x8 = hi ? xw[17] : xw[16];
      nb_sync(NB_WG + p, 128);
      const uint4 bs = lds128(sb + SM_BEST + p * 16);
      const bool best = (w > 0 ? bs.x < mx : true) && (w > 1 ? bs.y < mx : bs.y <= mx) && (w > 2 ? bs.z < mx : bs.z <= mx) && bs.w <= mx;
      if (best && mine) {
        if (q < 2) stg128(sc + o_cand, asu(hi ? r_hi : r_lo), (tg << 6) + (uint32_t)(w * 16 + g + (hi ? 8 : 0)), asu(hi ? m_hi : m_lo), asu(hi ? rs_hi : rs_lo));
        stg128(sc + o_xc, x0, x1, x2, tg);
        stg128(sc + o_xc + 64, x3, x4, x5, tg);
        stg128(sc + o_xc + 128, x6, x7, x8, tg);
      }
      candrow = __reduce_max_sync(0xffffffffu, best && mine ? g + (hi ? 8 : 0) : -1);
    }
    if (L == 0 && p == 1) {
#pragma unroll
      for (int t = 0; t < 9; t++) { stg32(sc + o_x + t * 1024, xw[2 * t]); stg32(sc + o_x + t * 1024 + 128, xw[2 * t + 1]); }
      rb = ldg_rlx32(sc + o_xrb);
    }
    const uint32_t stg = sb + SM_B + p * 13824 + w * 2304;
    unsigned char* obase = (unsigned char*)P.out + ((128 * i + 32 * w + p) * 1152 + 144 * j);
    if (L == 1) {
      const float ul = 1.f + rs_lo, uh = 1.f + rs_hi, vl = -m_lo * rs_lo, vh = -m_hi * rs_hi;
#pragma unroll
      for (int t = 0; t < 9; t++) {
        xw[2 * t] = pack_bf16(fmaf(accw[4 * t], ul, vl), fmaf(accw[4 * t + 1], ul, vl));
        xw[2 * t + 1] = pack_bf16(fmaf(accw[4 * t + 2], uh, vh), fmaf(accw[4 * t + 3], uh, vh));
      }
      mbar_wait(sb + BAR_EMPTY + p * 8, 1);
      const uint32_t sa = stg + (lane & 15) * 144;
#pragma unroll
      for (int t = 0; t < 8; t += 2) stsm4(sa + (lane >> 4) * 16 + t * 16, xw[2 * t], xw[2 * t + 1], xw[2 * t + 2], xw[2 * t + 3]);
      stsm2(sa + 128, xw[16], xw[17]);
      __syncwarp();
#pragma unroll
      for (int m = 0; m < 5; m++) {
        const int e = lane + 32 * m, r = (e * 57) >> 9;
        const uint4 v = lds128(stg + min(e, 143) * 16);
        if (e < 144 && r != candrow) *(uint4*)(obase + (r * (2304 - 144) + e * 16)) = v;
      }
    }
    CSTAMP(8);
    lane = pin(lane);
    const unsigned char* cp = sc + (OFF(cand) + (j * 32 + lane) * (CAND_W * 4));
    if (p == 0) {
      if (L == 1 && candrow >= 0) {
        const Winner wn = poll_winner(cp, ldg_rlx128(cp), tg);
        if (lane < 9 && wn.ci != ip) *(uint4*)(obase + (candrow * 2304 + lane * 16)) = lds128(stg + candrow * 144 + lane * 16);
      }
    } else {
      const uint32_t gr = w * 144 + (lane & 7) + (lane >> 4) * 8, gm = sb + SM_G + ((lane >> 3) & 1) * 46080;
      const uint32_t ga = gm + gr * 64 + (((lane >> 1) & 3) << 4), gl = gm + 36864 + gr * 16;
#define GADDR(s, u) ((u) < 4 ? (ga ^ ((u) << 4)) + (s) * 1024 : gl + (s) * 256)
      uint32_t wf[NPRE][5][4];
      mbar_wait(sb + BAR_GU, 0);
#pragma unroll
      for (int s = 0; s < NPRE - 2; s++)
#pragma unroll
        for (int u = 0; u < 5; u++) ldsm4t(wf[s][u], GADDR(s, u));
      const uint4 c0 = ldg_rlx128(cp);
#pragma unroll
      for (int s = NPRE - 2; s < NPRE; s++)
#pragma unroll
        for (int u = 0; u < 5; u++) ldsm4t(wf[s][u], GADDR(s, u));
      flag_after(sc + o_cf, rb, 8 * T + 1, lane < 8 && L == 0);
      const Winner wn = poll_winner(cp, c0, tg);
      if (w == 0 && first_lane) sts128(sb + SM_WIN, asu(wn.r), asu(wn.m), asu(wn.rstd), (uint32_t)(wn.ci * 64 + wn.rr));
      CSTAMP(9);
      if (L == 1 && candrow >= 0 && lane < 9 && wn.ci != ip) *(uint4*)(obase + (candrow * 2304 + lane * 16)) = lds128(stg + candrow * 144 + lane * 16);
      {
        uint32_t hb[18];
        const unsigned char* xc = sc + (OFF(xcand) + wn.ci * 1536 + q * 16);
        const int fp = min(cx.cta / 3, 23);
        uint4 u[7];
        int n = 0;
#pragma unroll 1
        while (true) {
          uint32_t d = 0;
#pragma unroll
          for (int e = 0; e < 7; e++) u[e] = ldg_rlx128(xc + (e < 6 ? w * 384 + e * 64 : fp * 64));
#pragma unroll
          for (int e = 0; e < 7; e++) d = orx(d, u[e].w, tg);
          if (__all_sync(0xffffffffu, d == 0)) break;
          if (++n > SPIN) TIMEOUT(__LINE__)
        }
#pragma unroll
        for (int e = 0; e < 6; e++) { hb[3 * e] = u[e].x; hb[3 * e + 1] = u[e].y; hb[3 * e + 2] = u[e].z; }
        if (w == 0) sts128(sb + SM_XW + q * 16, u[6].x, u[6].y, u[6].z, u[6].w);
        const float nb = -wn.m * wn.rstd;
#pragma unroll
        for (int b = 0; b < 18; b++) hb[b] = pack_bf16(fmaf(bf_lo(hb[b]), wn.rstd, nb), fmaf(bf_hi(hb[b]), wn.rstd, nb));
        CSTAMP(10);
        float d[5][4];
#pragma unroll
        for (int u = 0; u < 5; u++) d[u][0] = d[u][1] = d[u][2] = d[u][3] = 0.f;
#pragma unroll
        for (int s = 0; s < 9; s++) {
#pragma unroll
          for (int u = 0; u < 5; u++) {
            uint32_t* f = wf[s % NPRE][u];
            mma16(d[u], f[0], f[1], f[2], f[3], hb[2 * s], hb[2 * s + 1]);
            if (s + NPRE < 9) ldsm4t(f, GADDR(s + NPRE, u));
          }
        }
        if (q == 0) {
#pragma unroll
          for (int u = 0; u < 5; u++) sts64(sb + R_FPART + w * 320 + (u * 8 + g) * 8, asu(d[u][0]), asu(d[u][2]));
        }
        nb_arrive(NB_FFN, 224);
        CSTAMP(11);
      }
    }
  }
  STAMPIF(w == 0 && lane == 0, 40 + p * 20 + 12);
  PROF_DUMP();
#undef g
#undef q
#undef first_lane
}

__device__ __forceinline__ void load_wo_a(const Ctx& cx, const Params& P, const uint32_t T, const int L, const int p, const int lane) {
  const unsigned char* src = P.sc->obuf[cx.i * 2 + p];
#pragma unroll
  for (int c = 0; c < 9; c++) w_expect(sb + BAR_WFULL + (9 * p + c) * 8, 8192);
  mbar_wait(sb + BAR_HDONE + p * 8, L);
  wait_flags<32>(P.sc->cflag[cx.i * 2 + p], 8 * T + 2 * L, lane);
  fence_async_glob();
  STAMP(100 + L * 2 + p);
#pragma unroll
  for (int c = 0; c < 9; c++) {
    const int e = 9 * p + c, s = e % 6;
    if (e == 3) mbar_wait(sb + BAR_HDONE + 8, L);
    if (e >= 6) mbar_wait(sb + BAR_AEMPTY + s * 8, (L ^ (e / 6) ^ 1) & 1);
    w_bulk(sb + SM_A + (2 * (s % 3) + s / 3) * 8192, src + c * 8192, 8192, sb + BAR_WFULL + e * 8);
    PSTAMP(48 + L * 36 + 18 + e);
  }
}

__device__ __forceinline__ void finalize_row(const Params& P, const Winner& wn, const uint32_t T, const int L, const int grp, const int a, const int lane) {
  const unsigned char* yp = (const unsigned char*)P.sc->ypart[grp] + (a * 32 + lane) * 16;
  const uint32_t par = L ^ 1;
  uint4 u0 = ldg_rlx128(yp), u1 = ldg_rlx128(yp + 1536), u2 = make_uint4(par, 0, 0, 0);
  if (a < 2) rld128(u2, yp + 3072);
  const int col = lane & 7;
  const uint32_t xw = lds32(sb + SM_XW + (col >> 1) * 16 + (grp % 3) * 4);
  const float xsel = (col & 1) ? bf_hi(xw) : bf_lo(xw);
  const float sg = rbf(rcp(1.f + ex2(-1.4426950408889634f * rbf(wn.r))));
  const float h = rbf((xsel - wn.m) * wn.rstd);
  unsigned char* dst = L == 0 ? (unsigned char*)P.sc->xsel + (((lane >> 3) & 1) * 576 + grp * 8 + col) * 4
                              : (unsigned char*)P.out + ((128 * (wn.ci >> 1) + 2 * wn.rr + (wn.ci & 1)) * 576 + grp * 8 + col) * 2;
  int n = 0;
#pragma unroll 1
  while (__any_sync(0xffffffffu, orx(orx(orx(0, u0.x, par), u1.x, par), u2.x, par) & 1)) {
    rld128(u0, yp); rld128(u1, yp + 1536);
    if (a < 2) rld128(u2, yp + 3072);
    if (++n > SPIN) TIMEOUT(__LINE__)
  }
  const float s0 = asf(u0.x) + asf(u1.x) + asf(u2.x), s1 = asf(u0.y) + asf(u1.y) + asf(u2.y);
  const float s2 = asf(u0.z) + asf(u1.z) + asf(u2.z), s3 = asf(u0.w) + asf(u1.w) + asf(u2.w);
  const float k0 = self(lane & 2, s2, s0) + shx(self(lane & 2, s0, s2), 2), k1 = self(lane & 2, s3, s1) + shx(self(lane & 2, s1, s3), 2);
  float k = self(lane & 4, k1, k0) + shx(self(lane & 4, k0, k1), 4);
  k += shx(k, 8); k += shx(k, 16);
  if (lane < 8) stsf(sb + SM_YRED + ((lane & 1) * 4 + (lane & 2) + (lane >> 2)) * 16 + a * 4, k);
  nb_sync(NB_AUX, 96);
  if (a == 0) {
    const uint4 yy = lds128(sb + SM_YRED + col * 16);
    const float xn = rbf(xsel + rbf(h + rbf(rbf(asf(yy.x) + asf(yy.y) + asf(yy.z)) * sg)));
    if (L == 0) { if (lane < 16) stg32(dst, ftag(lane < 8 ? xn : xn - xsel, T & 1)); }
    else if (lane < 8) *(unsigned short*)dst = (unsigned short)(asu(xn) >> 16);
  }
}

__device__ __forceinline__ void aux_role(const Ctx& cx, const Params& P, const int a, const int lane_) {
  int lane = lane_;
#define t (a * 32 + lane)
#define g (lane >> 2)
#define q (lane & 3)
  const int i = cx.i, j = cx.j, cta = cx.cta;
  unsigned char* const sc = (unsigned char*)P.sc;
  const int rk = 36 * i + 12 * a;
  const uint32_t o_bf = OFF(bflag) + (j * 48 + i * 3 + a) * 32 + (lane & 7) * 4;
  uint32_t T;
  {
    const int k0 = lane & 7, tt = min(lane >> 3, 2), col = (9 * j + tt) * 16;
    const unsigned char* src = (const unsigned char*)P.wqkv + ((i * 8 + k0) * 3456 + a * 1152 + col);
    const Unit b0 = unit_load(src), b1 = unit_load(src + 128 * 3456);
    T = ldg_rlx32(sc + o_bf);
    nb_arrive(NB_ORD, 352);
    STAMPIF(1, 96);
    const uint32_t d2 = tt == 2 ? (22 - 7 * a) * 512 : 3072;
    const uint32_t o = OFF(wq) + (j * 18 + (i >> 2)) * 13824 + ((i & 3) * 8 + k0) * 16 + (a * 8 + tt) * 512;
    const uint32_t r0 = unit_store(sc, b0, lane, o, o + 1536, o + d2);
    STAMPIF(1, 80);
    const uint32_t r1 = unit_store(sc, b1, lane, o + 55296, o + 55296 + 1536, o + 55296 + d2);
    T = __shfl_sync(0xffffffffu, (T >> 3) + 1, 0);
    flag_after(sc + o_bf, r0 ^ r1, 8 * T + 1, lane < 8);
    STAMPIF(1, 98);
    const Unit b2 = unit_load(src + 256 * 3456), b3 = unit_load(src + 384 * 3456);
    const bool qkv = k0 < 4;
    const int q0 = rk + k0 - 4, q1 = rk + 4 + k0;
    const Unit u0 = unit_load(qkv ? (const unsigned char*)P.wqkv + ((512 + 4 * i + k0) * 3456 + a * 1152 + col) : (const unsigned char*)P.wo + (q0 * 1152 + col));
    const Unit u1 = unit_load((const unsigned char*)P.wo + (q1 * 1152 + col));
    const uint32_t r2 = unit_store(sc, b2, lane, o + 2 * 55296, o + 2 * 55296 + 1536, o + 2 * 55296 + d2);
    const uint32_t r3 = unit_store(sc, b3, lane, o + 3 * 55296, o + 3 * 55296 + 1536, o + 3 * 55296 + d2);
    float cs[3][8];
#pragma unroll
    for (int m = 0; m < 3; m++) {
      const uint32_t* w0 = &b0.v[m].x; const uint32_t* w1 = &b1.v[m].x; const uint32_t* w2 = &b2.v[m].x; const uint32_t* w3 = &b3.v[m].x; const uint32_t* w4 = &u0.v[m].x;
#pragma unroll
      for (int e = 0; e < 4; e++) {
        const uint32_t z = qkv ? w4[e] : 0u;
        cs[m][2 * e] = (bf_lo(w0[e]) + bf_lo(w1[e])) + (bf_lo(w2[e]) + bf_lo(w3[e])) + bf_lo(z);
        cs[m][2 * e + 1] = (bf_hi(w0[e]) + bf_hi(w1[e])) + (bf_hi(w2[e]) + bf_hi(w3[e])) + bf_hi(z);
      }
    }
    flag_after(sc + o_bf, r2 ^ r3, 8 * T + 3, lane < 8);
    STAMPIF(1, 82);
#pragma unroll
    for (int st = 4; st >= 1; st >>= 1) {
      const bool up = lane & st;
#pragma unroll
      for (int m = 0; m < 3; m++)
#pragma unroll
        for (int e = 0; e < st; e++) cs[m][e] = (up ? cs[m][e + st] : cs[m][e]) + shx(up ? cs[m][e] : cs[m][e + st], st);
    }
    {
      const uint32_t oz = OFF(zpart) + j * 13824 + i * 864 + (a * 8 + tt) * 32 + k0 * 4;
      stg32(sc + oz, ftag(cs[0][0], 1)); stg32(sc + (oz + 96), ftag(cs[1][0], 1)); stg32(sc + (oz + (d2 >> 4)), ftag(cs[2][0], 1));
    }
    STAMPIF(1, 81);
    nb_sync(NB_GO, 128);
    mbar_wait(sb + BAR_FULL + LATE_WAIT * 8, 0);
    const uint32_t ow = OFF(wo) + j * 82944 + tt * 256;
    const uint32_t oa = qkv ? OFF(wq) + (j * 18 + 16 + (i >> 3)) * 13824 + (4 * (i & 7) + k0) * 16 + (a * 8 + tt) * 512 : ow + (q0 >> 4) * 2304 + (q0 & 15) * 16;
    const uint32_t ob = ow + (q1 >> 4) * 2304 + (q1 & 15) * 16;
    const uint32_t ra = unit_store(sc, u0, lane, oa, oa + (qkv ? 1536 : 768), oa + (qkv ? d2 : 1536));
    const uint32_t rb = unit_store(sc, u1, lane, ob, ob + 768, ob + 1536);
    STAMPIF(1, 113);
#pragma unroll
    for (int S = 0; S < 3; S++) stg64(sc + (OFF(ypart) + (a * 24 + g) * 4096 + cta * 32 + q * 8) + S * 32768, 0u, 0u);
    if (cta < 72 && t < 16) stg32(sc + (OFF(xsel) + (lane >> 3) * 2304 + cta * 32 + (lane & 7) * 4), (T & 1) ^ 1);
    uint4 sv, sw;
    int n = 0;
#pragma unroll 1
    while (true) {
      sv = ldg_rlx128(sc + (OFF(st0) + i * 2048 + t * 16)); sw = ldg_rlx128(sc + (OFF(st0) + i * 2048 + 1536 + lane * 16));
      if (__all_sync(0xffffffffu, ((sv.z ^ T) | (sw.z ^ T)) == 0)) break;
      if (++n > SPIN) TIMEOUT(__LINE__)
    }
    flag_after(sc + o_bf, ra ^ rb, 8 * T + 4, lane < 8);
    sts64(sb + SM_R + t * 8, sv.x, sv.y);
    sts64(sb + SM_R + 768 + lane * 8, sw.x, sw.y);
    STAMPIF(1, 94);
  }
  Winner wn;
  bool owner = false;
  uint32_t wd[5][3][8];
  auto load_wd = [&](uint32_t (*d)[8], const unsigned char* sk) {
#pragma unroll
    for (int S = 0; S < 3; S++) {
      const uint4 v0 = ldg_nc128(sk + S * 128), v1 = ldg_nc128(sk + S * 128 + 1152);
      d[S][0] = v0.x; d[S][1] = v1.x; d[S][2] = v0.y; d[S][3] = v1.y; d[S][4] = v0.z; d[S][5] = v1.z; d[S][6] = v0.w; d[S][7] = v1.w;
    }
  };
  auto perm_wd = [&](uint32_t (*d)[8]) {
#pragma unroll
    for (int S = 0; S < 3; S++)
#pragma unroll
      for (int u = 0; u < 4; u++) {
        const uint32_t x = d[S][2 * u], y = d[S][2 * u + 1];
        asm volatile("prmt.b32 %0, %2, %3, 0x5410;\nprmt.b32 %1, %2, %3, 0x7632;" : "=&r"(d[S][2 * u]), "=r"(d[S][2 * u + 1]) : "r"(x), "r"(y));
      }
  };
#pragma unroll
  for (int kb = 0; kb < 3; kb++)
#pragma unroll
    for (int S = 0; S < 3; S++)
#pragma unroll
      for (int e = 0; e < 8; e++) wd[kb][S][e] = 0u;
#pragma unroll 1
  for (int L = 0; L < 2; L++) {
    lane = pin(lane);
    const uint32_t o_part = OFF(zpart) + j * 13824, par = L ^ 1;
    const int pk = a * 18 + min(lane, 17);
    if (L == 1) {
      if (cta < 72) finalize_row(P, wn, T, 0, cta, a, lane);
      const int gi = min(lane, 26);
      uint4 wv[12];
      {
        const int pc = gi < 24 ? gi >> 3 : gi - 24, tc = gi < 24 ? gi & 7 : 8;
        const unsigned char* se = (const unsigned char*)P.wqkv + (rk * 3456 + pc * 1152 + (9 * j + tc) * 16);
#pragma unroll
        for (int r = 0; r < 12; r++) wv[r] = ldg_nc128(se + r * 3456);
      }
      STAMPIF(1, 85);
      nb_sync(NB_AUX, 96);
      uint4 xq[3];
      {
        const unsigned char* dp = sc + (OFF(xsel) + 2304 + rk * 4);
        int n = 0;
#pragma unroll 1
        while (true) {
#pragma unroll
          for (int e = 0; e < 3; e++) xq[e] = ldg_rlx128(dp + e * 16);
          if (__all_sync(0xffffffffu, (orx(orx(orx(0, xq[0].x, T), xq[1].x, T), xq[2].x, T) & 1) == 0)) break;
          if (++n > SPIN) TIMEOUT(__LINE__)
        }
        if (t == 0) {
          sts32(sb + SM_SEL, owner ? (wn.ci & 1) * 64 + wn.rr : 0x7FFFFFFFu);
          if (wn.ci != 2 * i) mbar_arrive(sb + BAR_FIX);
          if (wn.ci != 2 * i + 1) mbar_arrive(sb + BAR_FIX + 8);
        }
        STAMPIF(1, 88);
      }
      float s[8];
#pragma unroll
      for (int e = 0; e < 8; e++) s[e] = 0.f;
#pragma unroll
      for (int r = 0; r < 12; r++) {
        const float x = asf((&xq[0].x)[r]);
        s[0] = fmaf(x, bf_lo(wv[r].x), s[0]); s[1] = fmaf(x, bf_hi(wv[r].x), s[1]);
        s[2] = fmaf(x, bf_lo(wv[r].y), s[2]); s[3] = fmaf(x, bf_hi(wv[r].y), s[3]);
        s[4] = fmaf(x, bf_lo(wv[r].z), s[4]); s[5] = fmaf(x, bf_hi(wv[r].z), s[5]);
        s[6] = fmaf(x, bf_lo(wv[r].w), s[6]); s[7] = fmaf(x, bf_hi(wv[r].w), s[7]);
      }
      sts128(sb + SM_R + a * 864 + gi * 32, asu(s[0]), asu(s[1]), asu(s[2]), asu(s[3]));
      sts128(sb + SM_R + a * 864 + gi * 32 + 16, asu(s[4]), asu(s[5]), asu(s[6]), asu(s[7]));
      nb_sync(NB_AUX, 96);
      const uint32_t ad = sb + SM_R + pk * 16;
      const uint4 u0 = lds128(ad), u1 = lds128(ad + 864), u2 = lds128(ad + 1728);
      stg128(sc + (o_part + i * 864 + pk * 16), ftag(asf(u0.x) + asf(u1.x) + asf(u2.x), par), ftag(asf(u0.y) + asf(u1.y) + asf(u2.y), par),
             ftag(asf(u0.z) + asf(u1.z) + asf(u2.z), par), ftag(asf(u0.w) + asf(u1.w) + asf(u2.w), par));
      STAMPIF(1, 86);
    }
    if (owner) {
      uint2 u[3];
      int n = 0;
#pragma unroll 1
      while (true) {
#pragma unroll
        for (int m = 0; m < 3; m++) u[m] = ldg_rlx64(sc + (OFF(xsel) + t * 8) + m * 768);
        if (__all_sync(0xffffffffu, (orx(orx(orx(0, u[0].x, T), u[1].x, T), u[2].x, T) & 1) == 0)) break;
        if (++n > SPIN) TIMEOUT(__LINE__)
      }
      STAMPIF(1, 109);
      float s1 = 0.f, s2 = 0.f;
#pragma unroll
      for (int m = 0; m < 3; m++) {
        const float x0 = asf(u[m].x), x1 = asf(u[m].y);
        s1 += x0 + x1; s2 = fmaf(x0, x0, fmaf(x1, x1, s2));
        const unsigned cc = 96 * m + t - 36 * j;
        if (cc < 36u) sts32(sb + SM_X2S + cc * 4, __byte_perm(u[m].x, u[m].y, 0x7632));
      }
      wn.m = s1; wn.rstd = s2;
    }
    if (L == 0 || owner) {
      uint4 u[16];
      int n = 0;
#pragma unroll 1
      while (true) {
        uint32_t d0 = 0, d1 = 0;
#pragma unroll
        for (int e = 0; e < 16; e++) u[e] = ldg_rlx128(sc + (o_part + pk * 16) + e * 864);
        if (L == 1 && n == 0) {
#pragma unroll
          for (int s = 1; s < 32; s <<= 1) { wn.m += shx(wn.m, s); wn.rstd += shx(wn.rstd, s); }
          if (lane == 0) sts64(sb + SM_RED2 + a * 8, asu(wn.m), asu(wn.rstd));
        }
#pragma unroll
        for (int e = 0; e < 8; e++) { d0 = orx(d0, u[e].x, par); d1 = orx(d1, u[8 + e].x, par); }
        if (__all_sync(0xffffffffu, ((d0 | d1) & 1) == 0)) break;
        if (++n > SPIN) TIMEOUT(__LINE__)
      }
      STAMPIF(1, 118 + L);
      float4 z = make_float4(0.f, 0.f, 0.f, 0.f);
#pragma unroll
      for (int e = 0; e < 16; e++) { z.x += asf(u[e].x); z.y += asf(u[e].y); z.z += asf(u[e].z); z.w += asf(u[e].w); }
      const uint32_t h0 = pack_bf16(z.x, z.y), h1 = pack_bf16(z.z, z.w);
      const uint32_t l0 = pack_bf16(z.x - bf_lo(h0), z.y - bf_hi(h0)), l1 = pack_bf16(z.z - bf_lo(h1), z.w - bf_hi(h1));
      const uint32_t ad = sb + SM_BEXT + (pk >> 1) * 128 + (pk & 1) * 8;
      if (L == 0) {
        sts64(ad, h0, h1);
#pragma unroll
        for (int r = 3; r < 8; r++) sts64(ad + r * 16, 0u, 0u);
      }
      sts64(ad + 16 + L * 48, h0, h1); sts64(ad + 32 + L * 48, l0, l1);
      fence_async_smem();
      nb_sync(NB_AUX, 96);
      if (t == 0) {
        if (L == 1) {
          const uint4 ra = lds128(sb + SM_RED2);
          const uint2 rb = lds64(sb + SM_RED2 + 16);
          const float m2 = (asf(ra.x) + asf(ra.z) + asf(rb.x)) * (1.f / 576.f);
          const float rs2 = rsq(fmaxf((asf(ra.y) + asf(ra.w) + asf(rb.y)) * (1.f / 576.f) - m2 * m2, 0.f) + EPS);
          sts64(sb + SM_SEL + 8, asu(m2), asu(rs2));
          mbar_arrive(sb + BAR_FIX + (wn.ci & 1) * 8);
        } else {
          mbar_arrive(sb + BAR_FIX); mbar_arrive(sb + BAR_FIX + 8);
        }
        STAMP(83 + L * 4);
      }
    }
    lane = pin(lane);
    const unsigned char* const wsrc = (const unsigned char*)P.wd + ((ffn_c32(cta) + 2 * q) * 1152 + a * 384 + g * 16);
    if (L == 0) {
#pragma unroll
      for (int kb = 0; kb < 3; kb++) { load_wd(wd[kb], wsrc + (kb * 9216 + (kb ? pin0(wd[kb - 1][2][7]) : 0u))); perm_wd(wd[kb]); }
    }
    load_wd(wd[3], wsrc + 3 * 9216);
    load_wd(wd[4], wsrc + ((cta & 1) ? (ffn_c8(cta) - ffn_c32(cta)) * 1152 : 24 * 1152));
    perm_wd(wd[3]); perm_wd(wd[4]);
    const uint32_t o_y = pin(OFF(ypart) + (a * 24 + g) * 4096 + cta * 32 + q * 8 + pin0(wd[4][2][7]));
    STAMPIF(1, 89 + L);
    if (a == 2) load_wo_a(cx, P, T, L, 1, lane);
    nb_sync(NB_FFN, 224);
    {
      const uint32_t ad = sb + R_FPART + min(lane, 19) * 16;
      const uint4 u0 = lds128(ad), u1 = lds128(ad + 320), u2 = lds128(ad + 640), u3 = lds128(ad + 960);
      const uint4 wv = lds128(sb + SM_WIN);
      const float g0 = rbf((asf(u0.x) + asf(u1.x)) + (asf(u2.x) + asf(u3.x))), g1 = rbf((asf(u0.z) + asf(u1.z)) + (asf(u2.z) + asf(u3.z)));
      const float v0 = rbf((asf(u0.y) + asf(u1.y)) + (asf(u2.y) + asf(u3.y))), v1 = rbf((asf(u0.w) + asf(u1.w)) + (asf(u2.w) + asf(u3.w)));
      const float s0 = rbf(g0 * rcp(1.f + ex2(-1.4426950408889634f * g0))), s1 = rbf(g1 * rcp(1.f + ex2(-1.4426950408889634f * g1)));
      const uint32_t act = lane < 16 + (cta & 1) * 4 ? pack_bf16(s0 * v0, s1 * v1) : 0u;
      uint32_t b[5];
#pragma unroll
      for (int kb = 0; kb < 5; kb++) b[kb] = __shfl_sync(0xffffffffu, act, 4 * kb + q);
#pragma unroll
      for (int S = 0; S < 3; S++) {
        float y[4][4];
#pragma unroll
        for (int u = 0; u < 4; u++) mma8z(y[u], wd[2][S][2 * u], wd[2][S][2 * u + 1], b[2]);
#pragma unroll
        for (int u = 0; u < 4; u++) mma16(y[u], wd[0][S][2 * u], wd[0][S][2 * u + 1], wd[1][S][2 * u], wd[1][S][2 * u + 1], b[0], b[1]);
#pragma unroll
        for (int u = 0; u < 4; u++) mma16(y[u], wd[3][S][2 * u], wd[3][S][2 * u + 1], wd[4][S][2 * u], wd[4][S][2 * u + 1], b[3], b[4]);
        const float y0 = self(lane & 2, self(lane & 1, y[3][0], y[2][0]), self(lane & 1, y[1][0], y[0][0]));
        const float y1 = self(lane & 2, self(lane & 1, y[3][2], y[2][2]), self(lane & 1, y[1][2], y[0][2]));
        stg64(sc + o_y + S * 32768, ftag(y0, par), ftag(y1, par));
      }
      if (L == 0) nb_arrive(NB_FFN2, 224);
      wn.r = asf(wv.x); wn.m = asf(wv.y); wn.rstd = asf(wv.z); wn.ci = wv.w >> 6; wn.rr = wv.w & 63;
    }
    STAMPIF(1, 84 + L * 8);
    owner = (wn.ci >> 1) == i;
  }
  if (cta < 72) finalize_row(P, wn, T, 1, cta, a, lane);
  STAMPIF(1, 93);
  PROF_END();
#undef t
#undef g
#undef q
}

__device__ __forceinline__ void producer_role(const Ctx& cx, const Params& P, const int lane) {
  const int i = cx.i, j = cx.j;
  if (elect_one()) asm volatile("prefetch.tensormap [%0];" ::"l"(&P.mx) : "memory");
  const uint32_t T = __shfl_sync(0xffffffffu, (ldg_rlx32(P.sc->cflag[i * 2][j * 4]) >> 3) + 1, 0);
  const unsigned char* const wq = P.sc->wq[j][0];
  nb_sync(NB_START, 288);
#pragma unroll
  for (int s = 0; s < 2 * NA0; s++) w_tma3d(sb + SM_A + s * 8192, &P.mx, (s >> 1) * 64, s & 1, i * 64, sb + BAR_FULL + (s >> 1) * 16);
#pragma unroll
  for (int h = 0; h < 6; h++) w_expect(sb + BAR_FULL + h * 8, h & 1 ? 13824 : 13824 + 16384);
  STAMP(97);
  wait_flags<48>(P.sc->bflag[j], 8 * T + 1, lane);
  fence_async_glob();
  STAMP(120);
#pragma unroll
  for (int h = 0; h < 6; h++) {
    w_bulk(sb + SM_B + h * 13824, wq + h * 13824, 13824, sb + BAR_FULL + h * 8);
    if (!(h & 1) && h >= 2 * NA0) {
      w_tma3d(sb + SM_A + h * 8192, &P.mx, h * 32, 0, i * 64, sb + BAR_FULL + h * 8);
      w_tma3d(sb + SM_A + h * 8192 + 8192, &P.mx, h * 32, 1, i * 64, sb + BAR_FULL + h * 8);
    }
  }
  PSTAMP(0);
  nb_arrive(NB_GO, 128);
  mbar_wait(sb + BAR_FULL + PF_WAIT * 8, 0);
  w_prefetch((const unsigned char*)P.wd + cx.cta * 41472, 10368);
  const unsigned char* const xb = P.sc->xbuf[i * 2];
  const unsigned char* const fp = (const unsigned char*)P.sc->bflag[j] + lane * 32;
  uint32_t f0 = 0, f1 = 0;
#pragma unroll 1
  for (int L = 0; L < 2; L++) {
    if (L == 1) {
#pragma unroll 1
      for (int p = 0; p < 2; p++) {
        mbar_wait(sb + BAR_AEMPTY + (2 + 3 * p) * 8, 0);
        wait_flags<32>(P.sc->cflag[i * 2 + p], 8 * T + 1, lane);
        fence_async_glob();
        STAMP(104 + p);
#pragma unroll
        for (int a = 0; a < 3; a++) {
          const int s = 2 * a + p;
          w_expect(sb + BAR_AFULL + s * 8, 8192);
          w_bulk(sb + SM_A + s * 8192, xb + (p * 73728 + a * 8192), 8192, sb + BAR_AFULL + s * 8);
          PSTAMP(48 + 36 + 3 * p + a);
        }
      }
    }
#pragma unroll 1
    for (int a = 3; a < 15; a++) {
      if (a == 12) {
        load_wo_a(cx, P, T, L, 0, lane);
        if (L == 1) break;
      }
      const int r = (a * 11) >> 5, s = a - 3 * r;
      const uint32_t fb = sb + BAR_FULL + s * 16, da = sb + SM_A + s * 16384, db = sb + SM_B + s * 27648;
      const unsigned char* bsrc = wq + (a < 9 ? a : a < 12 ? 72 - 6 * j + s : s) * 27648;
      const unsigned char* asrc = xb + a * 8192;
      const int kc = (a < 9 ? a : j + a - 10) * 64;
      const int amode = a == 9 || a > 11 ? 0 : L == 0 ? 1 : a < 9 ? 2 : 0;
      mbar_wait(sb + BAR_EMPTY + s * 16, (r & 1) ^ 1);
      if (L == 0) {
        if (a == 4 || a == 8) {
          const uint32_t need = 8 * T + (a == 4 ? 3 : 4);
          if (__any_sync(0xffffffffu, (int)((f0 - need) | (f1 - need)) < 0)) wait_flags<48>(P.sc->bflag[j], need, lane);
          fence_async_glob();
          STAMP(120 + (a >> 1));
        }
        if (a == 3 || a == 7) { f0 = ldg_rlx32(fp); f1 = ldg_rlx32(fp + (lane < 16 ? 1024 : 0)); }
      }
      w_bulk(db, bsrc, 13824, fb);
      w_expect(fb, amode ? 13824 + 16384 : 13824);
      mbar_wait(sb + BAR_EMPTY + s * 16 + 8, (r & 1) ^ 1);
      if (amode == 1) {
        w_tma3d(da, &P.mx, kc, 0, i * 64, fb);
        w_tma3d(da + 8192, &P.mx, kc, 1, i * 64, fb);
      } else if (amode == 2) {
        w_bulk(da, asrc, 8192, fb);
        w_bulk(da + 8192, asrc + 73728, 8192, fb);
      }
      w_bulk(db + 13824, bsrc + 13824, 13824, fb + 8);
      w_expect(fb + 8, 13824);
      PSTAMP(a < 12 ? L * 24 + a : 12 + a);
      if (L == 0) {
        if (a < 12) w_prefetch(a < 6 ? (const unsigned char*)P.wd + (cx.cta * 4 + a - 2) * 10368 : (const unsigned char*)P.wg + ((a - 6) * 128 + cx.cta) * 6912, a < 6 ? 10368 : 6912);
        if (a == 3) w_expect(sb + BAR_GU, 12 * (6144 + (cx.cta & 1) * 1536));
        if (a >= 9) load_gu(P, cx.cta, 0, a - 9, sb + BAR_GU);
        if (a >= 3 && a < 13 && ((a & 1) || a == 12)) load_gu(P, cx.cta, 1, (a - 2) >> 1, sb + BAR_GU);
      }
    }
  }
}

template <bool BY_SMID>
__global__ void __launch_bounds__(384, 1) fused_kernel(const __grid_constant__ Params P) {
  extern __shared__ __align__(1024) unsigned char smem[];
  Ctx cx;
  STAMPIF(threadIdx.x == 64, 125);
  unsigned id;
  if (BY_SMID) asm volatile("mov.u32 %0, %%smid;" : "=r"(id)); else id = blockIdx.x;
  const int work = __shfl_sync(0xffffffffu, (int)P.work[min(id, 131u)], 0);
  const int warp = __shfl_sync(0xffffffffu, (int)(threadIdx.x >> 5), 0), lane = threadIdx.x & 31;
  if (work < 0) {
    if (warp == 0) {
      const int sp = -1 - work;
      if (lane == 0) { mbar_init(sb, 1); fence_async_smem(); }
      __syncwarp();
      __nanosleep(SPARE_DELAY);
#pragma unroll 1
      for (int k = 32 + sp; k < 72; k += 4) w_prefetch((const unsigned char*)P.wqkv + k * 27648, 27648);
#pragma unroll 1
      for (int k = sp; k < 24; k += 4) w_prefetch((const unsigned char*)P.wo + k * 27648, 27648);
#pragma unroll 1
      for (int k = sp; k < X_NU; k += 4) w_prefetch((const unsigned char*)P.wu + k * 27648, 27648);
      w_expect(sb, 16);
      w_bulk(sb + 128, P.wr, 16, sb);
      mbar_wait(sb, 0);
    }
    return;
  }
  cx.cta = work; cx.i = work >> 3; cx.j = work & 7;
  STAMPIF(threadIdx.x == 32, 95);
  if (warp < 8) {
    if (warp == 0) {
      if (elect_one()) {
        if ((uint32_t)__cvta_generic_to_shared(smem) != sb) __trap();
#pragma unroll
        for (int b = 0; b < 48; b++) mbar_init(sb + SM_BAR + b * 8, b < 34 ? 1 : b < 42 ? 4 : 8);
        fence_async_smem();
      }
      __syncwarp();
    }
    consumer_role(cx, P, smem, warp >> 2, warp & 3, lane);
  } else if (warp < 11) {
    aux_role(cx, P, warp - 8, lane);
  } else {
    producer_role(cx, P, lane);
  }
}

int work_of_smid(int smid) {
  const int t = smid >> 1;
  int gpc, x;
  if (t < 32) { gpc = t & 7; x = t >> 3; }
  else if (t < 60) { gpc = 1 + (t - 32) % 7; x = 4 + (t - 32) / 7; }
  else { gpc = t < 62 ? t - 54 : t - 60; x = 8; }
  x = 2 * x + (smid & 1);
  if (gpc == 0) return (12 + (x >> 2)) * 8 + 4 + (x & 3);
  if (x < 16) { const int b = gpc - 1; return ((b >> 1) * 4 + (x >> 2)) * 8 + (b & 1) * 4 + (x & 3); }
  const int e = gpc == 2 ? 0 : gpc == 4 ? 1 : gpc == 6 ? 2 : gpc == 7 ? 3 : -1;
  if (e < 0) return -1 - ((gpc == 5) * 2 + (x & 1));
  return (14 + (e >> 1)) * 8 + 4 + (e & 1) * 2 + (x & 1);
}

typedef CUresult (*EncodeFn)(CUtensorMap*, CUtensorMapDataType, cuuint32_t, void*, const cuuint64_t*, const cuuint64_t*,
                             const cuuint32_t*, const cuuint32_t*, CUtensorMapInterleave, CUtensorMapSwizzle,
                             CUtensorMapL2promotion, CUtensorMapFloatOOBfill);

void make_map(EncodeFn enc, CUtensorMap* m, const void* base, int rank, const cuuint64_t* dims, const cuuint64_t* strides,
              const cuuint32_t* box, CUtensorMapSwizzle sw, CUtensorMapL2promotion promo = CU_TENSOR_MAP_L2_PROMOTION_L2_128B) {
  const cuuint32_t es[3] = {1, 1, 1};
  enc(m, CU_TENSOR_MAP_DATA_TYPE_BFLOAT16, rank, const_cast<void*>(base), dims, strides, box, es, CU_TENSOR_MAP_INTERLEAVE_NONE, sw,
      promo, CU_TENSOR_MAP_FLOAT_OOB_FILL_NONE);
}

}

extern "C" void kernel_launch(void* const* d_in, const int* in_sizes, int n_in, void* d_out, int out_size) {
  (void)in_sizes; (void)n_in; (void)out_size;
  static EncodeFn enc = nullptr;
  static int nsm = 0;
  static void* scr = nullptr;
  if (!enc) {
    void* f = nullptr;
    cudaDriverEntryPointQueryResult qr;
    cudaGetDriverEntryPoint("cuTensorMapEncodeTiled", &f, cudaEnableDefault, &qr);
    enc = (EncodeFn)f;
    cudaGetSymbolAddress(&scr, g_scratch);
    int dev = 0;
    cudaGetDevice(&dev);
    cudaDeviceGetAttribute(&nsm, cudaDevAttrMultiProcessorCount, dev);
    cudaFuncSetAttribute(fused_kernel<true>, cudaFuncAttributeMaxDynamicSharedMemorySize, SM_TOTAL);
    cudaFuncSetAttribute(fused_kernel<false>, cudaFuncAttributeMaxDynamicSharedMemorySize, SM_TOTAL);
  }
  Params P;
  P.x = (const __nv_bfloat16*)d_in[0];
  P.wqkv = (const __nv_bfloat16*)d_in[1];
  P.wo = (const __nv_bfloat16*)d_in[2];
  P.wr = (const __nv_bfloat16*)d_in[4];
  P.wg = (const __nv_bfloat16*)d_in[5];
  P.wu = (const __nv_bfloat16*)d_in[6];
  P.wd = (const __nv_bfloat16*)d_in[7];
  P.out = (__nv_bfloat16*)d_out;
  P.sc = (Scratch*)scr;
  for (int k = 0; k < 136; k++) P.work[k] = (signed char)(nsm == 132 ? (k < 132 ? work_of_smid(k) : -1) : (k < 128 ? k : k < 132 ? 127 - k : -1));
  {
    const cuuint64_t dims[3] = {576, 2, 1024}, str[2] = {1152, 2304};
    const cuuint32_t box[3] = {64, 1, 64};
    make_map(enc, &P.mx, P.x, 3, dims, str, box, CU_TENSOR_MAP_SWIZZLE_128B);
  }
  {
    const cuuint64_t dims[2] = {4608, 576}, str[1] = {9216};
    const cuuint32_t box[2] = {32, 96}, box8[2] = {8, 96};
    make_map(enc, &P.mg, d_in[5], 2, dims, str, box, CU_TENSOR_MAP_SWIZZLE_64B);
    make_map(enc, &P.mu, d_in[6], 2, dims, str, box, CU_TENSOR_MAP_SWIZZLE_64B);
    make_map(enc, &P.mg8, d_in[5], 2, dims, str, box8, CU_TENSOR_MAP_SWIZZLE_NONE);
    make_map(enc, &P.mu8, d_in[6], 2, dims, str, box8, CU_TENSOR_MAP_SWIZZLE_NONE);
  }
  if (nsm == 132) fused_kernel<true><<<132, 384, SM_TOTAL>>>(P);
  else fused_kernel<false><<<132, 384, SM_TOTAL>>>(P);
}
```

```cpp
#include <cuda_runtime.h>
#include <cuda.h>
#include <cuda_bf16.h>
#include <stdint.h>
#include <stddef.h>

namespace {

constexpr int NPRE = 5;
#define X_NU 192
#define CAND_W 8
#define HALO_V 0
#define X_DELAY 200
#define X_STEP 100
#define HOLD_C 13
#define U_SCHED 0
#define NA0 3
#define B2_AT 0
#define LATE_WAIT 3
#define OUT_LATE 0
#define PF_WAIT 0
#define POLL_GAP 100
#define SPARE_DELAY 400
constexpr float EPS = 1e-5f;
constexpr int SPIN = 1 << 22;
#define TIMEOUT(line) __trap();

struct __align__(128) Scratch {
  uint32_t bflag[8][48][8];
  uint32_t cflag[32][32][8];
  uint32_t halo[32][8][672];
  uint32_t stats[32][4][8][64];
  uint32_t cand[8][32][CAND_W];
  uint32_t xcand[32][8][48];
  uint32_t ypart[72][128][8];
  uint32_t zpart[8][16][216];
  uint32_t st0[2048][4];
  uint32_t xsel[2][576];
  unsigned char wq[8][9][27648];
  unsigned char wo[8][3][27648];
  unsigned char obuf[32][73728];
  unsigned char xbuf[32][73728];
};
__device__ Scratch g_scratch;
#define OFF(f) ((uint32_t)offsetof(Scratch, f))
#define STAMPD(v, k) do {} while (0)
#define STAMPIF(c, k) do {} while (0)
#define STAMP(k) do {} while (0)

constexpr uint32_t sb = 1024;
constexpr uint32_t SM_A = 0;
constexpr uint32_t SM_B = 49152;
constexpr uint32_t SM_G = 132096;
constexpr uint32_t SM_BEXT = 224256;

constexpr uint32_t SM_WIN = 227712;
constexpr uint32_t SM_XW = 228320;
constexpr uint32_t SM_YRED = 228448;
constexpr uint32_t SM_X2S = 228576;
constexpr uint32_t SM_RED2 = 228736;
constexpr uint32_t SM_WR = 228864;
constexpr uint32_t SM_R = 229168;
constexpr uint32_t SM_BEST = 231760;
constexpr uint32_t SM_SEL = 231824;
constexpr uint32_t SM_BAR = 231840;
constexpr uint32_t SM_TOTAL = 232448;
constexpr uint32_t R_FPART = SM_R;
constexpr uint32_t BAR_FULL = SM_BAR  , BAR_AFULL = SM_BAR + 48  , BAR_WFULL = SM_BAR + 96  , BAR_GU = SM_BAR + 248,
                   BAR_FIX = SM_BAR + 256  , BAR_AEMPTY = SM_BAR + 272  , BAR_HDONE = SM_BAR + 320  ,
                   BAR_EMPTY = SM_BAR + 336  ;
enum { NB_WG = 1  , NB_STAG = 3, NB_AUX = 4, NB_FFN2 = 5, NB_FFN = 8, NB_START = 9, NB_GO = 6, NB_ORD = 7 };

struct Params {
  const __nv_bfloat16 *wqkv, *x, *wr, *wo;
  Scratch* sc;
  const __nv_bfloat16 *wd, *wg, *wu;
  __nv_bfloat16* out;
  signed char work[136];
  CUtensorMap mx, mg, mu, mg8, mu8;
};

__device__ __forceinline__ void mbar_init(uint32_t bar, int cnt) { asm volatile("mbarrier.init.shared::cta.b64 [%0], %1;" ::"r"(bar), "r"(cnt) : "memory"); }
__device__ __forceinline__ void mbar_arrive(uint32_t bar) { asm volatile("mbarrier.arrive.shared::cta.b64 _, [%0];" ::"r"(bar) : "memory"); }
__device__ __forceinline__ void mbar_wait(uint32_t bar, uint32_t par) {
  asm volatile("{\n.reg .pred p;\nLOOP:\nmbarrier.try_wait.parity.shared::cta.b64 p, [%0], %1;\n@!p bra.uni LOOP;\n}\n" ::"r"(bar), "r"(par) : "memory");
}
__device__ __forceinline__ uint32_t mbar_test(uint32_t bar, uint32_t par) {
  uint32_t ok;
  asm volatile("{\n.reg .pred p;\nmbarrier.test_wait.parity.shared::cta.b64 p, [%1], %2;\nselp.u32 %0,1,0,p;\n}" : "=r"(ok) : "r"(bar), "r"(par) : "memory");
  return ok;
}
__device__ __forceinline__ bool elect_one() {
  uint32_t ok;
  asm volatile("{\n.reg .pred p;\nelect.sync _|p, 0xffffffff;\nselp.u32 %0, 1, 0, p;\n}" : "=r"(ok));
  return ok;
}
__device__ __forceinline__ float ex2(float x) { float r; asm("ex2.approx.ftz.f32 %0, %1;" : "=f"(r) : "f"(x)); return r; }
__device__ __forceinline__ float rsq(float x) { float r; asm("rsqrt.approx.ftz.f32 %0, %1;" : "=f"(r) : "f"(x)); return r; }
__device__ __forceinline__ float rcp(float x) { float r; asm("rcp.approx.ftz.f32 %0, %1;" : "=f"(r) : "f"(x)); return r; }
__device__ __forceinline__ void w_expect(uint32_t bar, uint32_t bytes) {
  asm volatile("{\n.reg .pred p;\nelect.sync _|p, 0xffffffff;\n@p mbarrier.arrive.expect_tx.shared::cta.b64 _, [%0], %1;\n}" ::"r"(bar), "r"(bytes) : "memory");
}
__device__ __forceinline__ void w_bulk(uint32_t dst, const void* src, uint32_t bytes, uint32_t bar) {
  asm volatile("{\n.reg .pred p;\nelect.sync _|p, 0xffffffff;\n@p cp.async.bulk.shared::cluster.global.mbarrier::complete_tx::bytes [%0], [%1], %2, [%3];\n}" ::"r"(dst), "l"(src), "r"(bytes), "r"(bar) : "memory");
}
__device__ __forceinline__ void w_tma2d(uint32_t dst, const CUtensorMap* m, int c0, int c1, uint32_t bar) {
  asm volatile("{\n.reg .pred p;\nelect.sync _|p, 0xffffffff;\n@p cp.async.bulk.tensor.2d.shared::cluster.global.mbarrier::complete_tx::bytes [%0], [%1, {%3, %4}], [%2];\n}" ::"r"(dst), "l"(m), "r"(bar), "r"(c0), "r"(c1) : "memory");
}
__device__ __forceinline__ void w_tma3d(uint32_t dst, const CUtensorMap* m, int c0, int c1, int c2, uint32_t bar) {
  asm volatile("{\n.reg .pred p;\nelect.sync _|p, 0xffffffff;\n@p cp.async.bulk.tensor.3d.shared::cluster.global.mbarrier::complete_tx::bytes [%0], [%1, {%3, %4, %5}], [%2];\n}" ::"r"(dst), "l"(m), "r"(bar), "r"(c0), "r"(c1), "r"(c2) : "memory");
}
__device__ __forceinline__ void w_prefetch(const void* src, uint32_t bytes) {
  asm volatile("{\n.reg .pred p;\nelect.sync _|p, 0xffffffff;\n@p cp.async.bulk.prefetch.L2.global [%0], %1;\n}" ::"l"(src), "r"(bytes) : "memory");
}
__device__ __forceinline__ void nb_sync(int id, int n) { asm volatile("bar.sync %0, %1;" ::"r"(id), "r"(n) : "memory"); }
__device__ __forceinline__ void nb_arrive(int id, int n) { asm volatile("bar.arrive %0, %1;" ::"r"(id), "r"(n) : "memory"); }
__device__ __forceinline__ void fence_async_smem() { asm volatile("fence.proxy.async.shared::cta;" ::: "memory"); }
__device__ __forceinline__ void fence_async_glob() { asm volatile("fence.proxy.async.global;" ::: "memory"); }
__device__ __forceinline__ void flag_after(void* p, uint32_t readback, uint32_t T, bool writer) {
  asm volatile("{\n.reg .pred p;\n.reg .u32 v;\nsetp.ne.u32 p, %3, 0;\nor.b32 v, %1, %2;\nmin.u32 v, v, %2;\n@p st.relaxed.gpu.global.u32 [%0], v;\n}"
               ::"l"(p), "r"(readback), "r"(T), "r"((uint32_t)writer) : "memory");
}
__device__ __forceinline__ uint4 ldg_rlx128(const void* p) { uint4 v; asm volatile("ld.relaxed.gpu.global.v4.b32 {%0,%1,%2,%3}, [%4];" : "=r"(v.x), "=r"(v.y), "=r"(v.z), "=r"(v.w) : "l"(p) : "memory"); return v; }
__device__ __forceinline__ uint2 ldg_rlx64(const void* p) { uint2 v; asm volatile("ld.relaxed.gpu.global.v2.b32 {%0,%1}, [%2];" : "=r"(v.x), "=r"(v.y) : "l"(p) : "memory"); return v; }
__device__ __forceinline__ void rld128(uint4& v, const void* p) { asm volatile("ld.relaxed.gpu.global.v4.b32 {%0,%1,%2,%3}, [%4];" : "+r"(v.x), "+r"(v.y), "+r"(v.z), "+r"(v.w) : "l"(p) : "memory"); }
__device__ __forceinline__ uint32_t ldg_rlx32(const void* p) { uint32_t v; asm volatile("ld.relaxed.gpu.global.b32 %0, [%1];" : "=r"(v) : "l"(p) : "memory"); return v; }
__device__ __forceinline__ uint4 ldg_nc128(const void* p) { uint4 v; asm volatile("ld.global.nc.v4.b32 {%0,%1,%2,%3}, [%4];" : "=r"(v.x), "=r"(v.y), "=r"(v.z), "=r"(v.w) : "l"(p)); return v; }
__device__ __forceinline__ uint32_t ldg_nc32(const void* p) { uint32_t v; asm volatile("ld.global.nc.L1::no_allocate.b32 %0, [%1];" : "=r"(v) : "l"(p)); return v; }
__device__ __forceinline__ void stg128(void* p, uint32_t a, uint32_t b, uint32_t c, uint32_t d) { asm volatile("st.relaxed.gpu.global.v4.b32 [%0], {%1,%2,%3,%4};" ::"l"(p), "r"(a), "r"(b), "r"(c), "r"(d) : "memory"); }
__device__ __forceinline__ void stg64(void* p, uint32_t a, uint32_t b) { asm volatile("st.relaxed.gpu.global.v2.b32 [%0], {%1,%2};" ::"l"(p), "r"(a), "r"(b) : "memory"); }
__device__ __forceinline__ void stg32(void* p, uint32_t a) { asm volatile("st.relaxed.gpu.global.b32 [%0], %1;" ::"l"(p), "r"(a) : "memory"); }
__device__ __forceinline__ void sts128(uint32_t a, uint32_t x, uint32_t y, uint32_t z, uint32_t w) { asm volatile("st.shared.v4.b32 [%0], {%1,%2,%3,%4};" ::"r"(a), "r"(x), "r"(y), "r"(z), "r"(w) : "memory"); }
__device__ __forceinline__ void sts64(uint32_t a, uint32_t x, uint32_t y) { asm volatile("st.shared.v2.b32 [%0], {%1,%2};" ::"r"(a), "r"(x), "r"(y) : "memory"); }
__device__ __forceinline__ void sts32(uint32_t a, uint32_t x) { asm volatile("st.shared.b32 [%0], %1;" ::"r"(a), "r"(x) : "memory"); }
__device__ __forceinline__ void stsf(uint32_t a, float x) { sts32(a, __float_as_uint(x)); }
__device__ __forceinline__ uint4 lds128(uint32_t a) { uint4 v; asm volatile("ld.shared.v4.b32 {%0,%1,%2,%3}, [%4];" : "=r"(v.x), "=r"(v.y), "=r"(v.z), "=r"(v.w) : "r"(a) : "memory"); return v; }
__device__ __forceinline__ uint2 lds64(uint32_t a) { uint2 v; asm volatile("ld.shared.v2.b32 {%0,%1}, [%2];" : "=r"(v.x), "=r"(v.y) : "r"(a) : "memory"); return v; }
__device__ __forceinline__ uint32_t lds32(uint32_t a) { uint32_t v; asm volatile("ld.shared.b32 %0, [%1];" : "=r"(v) : "r"(a) : "memory"); return v; }
__device__ __forceinline__ uint32_t pack_bf16(float lo, float hi) { uint32_t r; asm("cvt.rn.bf16x2.f32 %0, %1, %2;" : "=r"(r) : "f"(hi), "f"(lo)); return r; }
__device__ __forceinline__ float bf_lo(uint32_t w) { return __uint_as_float(w << 16); }
__device__ __forceinline__ float bf_hi(uint32_t w) { return __uint_as_float(w & 0xFFFF0000u); }
__device__ __forceinline__ float rbf(float x) { return bf_lo(pack_bf16(x, 0.f)); }
__device__ __forceinline__ float asf(uint32_t u) { return __uint_as_float(u); }
__device__ __forceinline__ uint32_t asu(float f) { return __float_as_uint(f); }
__device__ __forceinline__ float shx(float v, int m) { return __shfl_xor_sync(0xffffffffu, v, m); }
__device__ __forceinline__ uint32_t movm(uint32_t a) { uint32_t o; asm volatile("movmatrix.sync.aligned.m8n8.trans.b16 %0, %1;" : "=r"(o) : "r"(a)); return o; }
__device__ __forceinline__ void ldsm2(uint32_t& a, uint32_t& b, uint32_t addr) { asm volatile("ldmatrix.sync.aligned.m8n8.x2.shared.b16 {%0,%1}, [%2];" : "=r"(a), "=r"(b) : "r"(addr) : "memory"); }
__device__ __forceinline__ void ldsm4t(uint32_t* r, uint32_t addr) { asm volatile("ldmatrix.sync.aligned.m8n8.x4.trans.shared.b16 {%0,%1,%2,%3}, [%4];" : "=r"(r[0]), "=r"(r[1]), "=r"(r[2]), "=r"(r[3]) : "r"(addr) : "memory"); }
__device__ __forceinline__ void stsm4(uint32_t addr, uint32_t a, uint32_t b, uint32_t c, uint32_t d) { asm volatile("stmatrix.sync.aligned.m8n8.x4.shared.b16 [%0], {%1,%2,%3,%4};" ::"r"(addr), "r"(a), "r"(b), "r"(c), "r"(d) : "memory"); }
__device__ __forceinline__ void stsm2(uint32_t addr, uint32_t a, uint32_t b) { asm volatile("stmatrix.sync.aligned.m8n8.x2.shared.b16 [%0], {%1,%2};" ::"r"(addr), "r"(a), "r"(b) : "memory"); }
__device__ __forceinline__ void mma16(float* d, uint32_t a0, uint32_t a1, uint32_t a2, uint32_t a3, uint32_t b0, uint32_t b1) {
  asm volatile("mma.sync.aligned.m16n8k16.row.col.f32.bf16.bf16.f32 {%0,%1,%2,%3},{%4,%5,%6,%7},{%8,%9},{%0,%1,%2,%3};"
               : "+f"(d[0]), "+f"(d[1]), "+f"(d[2]), "+f"(d[3]) : "r"(a0), "r"(a1), "r"(a2), "r"(a3), "r"(b0), "r"(b1));
}
__device__ __forceinline__ void mma16z(float* d, uint32_t a0, uint32_t a1, uint32_t a2, uint32_t a3, uint32_t b0, uint32_t b1) {
  asm volatile("mma.sync.aligned.m16n8k16.row.col.f32.bf16.bf16.f32 {%0,%1,%2,%3},{%4,%5,%6,%7},{%8,%9},{%10,%10,%10,%10};"
               : "=f"(d[0]), "=f"(d[1]), "=f"(d[2]), "=f"(d[3]) : "r"(a0), "r"(a1), "r"(a2), "r"(a3), "r"(b0), "r"(b1), "f"(0.f));
}
__device__ __forceinline__ void mma8(float* d, uint32_t a0, uint32_t a1, uint32_t b0) {
  asm volatile("mma.sync.aligned.m16n8k8.row.col.f32.bf16.bf16.f32 {%0,%1,%2,%3},{%4,%5},{%6},{%0,%1,%2,%3};"
               : "+f"(d[0]), "+f"(d[1]), "+f"(d[2]), "+f"(d[3]) : "r"(a0), "r"(a1), "r"(b0));
}
__device__ __forceinline__ uint32_t pin(uint32_t v) { uint32_t r; asm volatile("shfl.sync.bfly.b32 %0, %1, 0, 31, 0xffffffff;" : "=r"(r) : "r"(v)); return r; }
__device__ __forceinline__ uint32_t pin0(uint32_t v) { uint32_t r; asm volatile("{\n.reg .u32 t;\nor.b32 t, %1, 1;\nbfind.shiftamt.u32 %0, t;\nshr.u32 %0, %0, 5;\n}" : "=r"(r) : "r"(v)); return r; }
__device__ __forceinline__ void mma8z(float* d, uint32_t a0, uint32_t a1, uint32_t b0) {
  asm volatile("mma.sync.aligned.m16n8k8.row.col.f32.bf16.bf16.f32 {%0,%1,%2,%3},{%4,%5},{%6},{%7,%7,%7,%7};"
               : "=f"(d[0]), "=f"(d[1]), "=f"(d[2]), "=f"(d[3]) : "r"(a0), "r"(a1), "r"(b0), "f"(0.f));
}
__device__ __forceinline__ void wg_fence() { asm volatile("wgmma.fence.sync.aligned;" ::: "memory"); }
__device__ __forceinline__ void wg_commit() { asm volatile("wgmma.commit_group.sync.aligned;" ::: "memory"); }
template <int N> __device__ __forceinline__ void wg_wait() { asm volatile("wgmma.wait_group.sync.aligned %0;" ::"n"(N) : "memory"); }
template <int N> __device__ __forceinline__ void fence_regs(float* d) {
#pragma unroll
  for (int k = 0; k < N; k++) asm volatile("" : "+f"(d[k])::"memory");
}
__host__ __device__ constexpr uint32_t DLO(uint32_t addr, uint32_t lbo) { return (addr >> 4) | ((lbo >> 4) << 16); }
__host__ __device__ constexpr uint32_t DHI(uint32_t sbo, uint32_t swz) { return (sbo >> 4) | (swz << 30); }
template <int N>
__device__ __forceinline__ void wait_flags(const void* base, const uint32_t V, const int lane) {
  const unsigned char* p = (const unsigned char*)base + lane * 32;
  const unsigned char* p2 = p + (lane < N - 32 ? 1024 : 0);
  uint32_t a0 = ldg_rlx32(p), a1 = N > 32 ? ldg_rlx32(p2) : V;
  __nanosleep(POLL_GAP);
  int n = 0;
#pragma unroll 1
  while (true) {
    const uint32_t b0 = ldg_rlx32(p), b1 = N > 32 ? ldg_rlx32(p2) : V;
    if (__all_sync(0xffffffffu, (int)((a0 - V) | (a1 - V)) >= 0)) break;
    a0 = ldg_rlx32(p); a1 = N > 32 ? ldg_rlx32(p2) : V;
    if (__all_sync(0xffffffffu, (int)((b0 - V) | (b1 - V)) >= 0)) break;
    if (++n > SPIN) TIMEOUT(__LINE__)
  }
}
__device__ __forceinline__ uint32_t ftag(float v, uint32_t par) { return (asu(v) & ~1u) | par; }
__device__ __forceinline__ uint32_t selu(uint32_t c, uint32_t a, uint32_t b) { uint32_t r; asm("{\n.reg .pred p;\nsetp.ne.u32 p, %1, 0;\nselp.b32 %0, %2, %3, p;\n}" : "=r"(r) : "r"(c), "r"(a), "r"(b)); return r; }
__device__ __forceinline__ float self(uint32_t c, float a, float b) { return asf(selu(c, asu(a), asu(b))); }
__device__ __forceinline__ uint32_t orx(uint32_t acc, uint32_t a, uint32_t ref) { uint32_t r; asm("lop3.b32 %0, %1, %2, %3, 0xF6;" : "=r"(r) : "r"(acc), "r"(a), "r"(ref)); return r; }
__device__ __forceinline__ uint32_t fkey(float r) {
  uint32_t u = asu(r);
  u = (u & 0x80000000u) ? ~u : (u | 0x80000000u);
  return (r == r) ? u : 0u;
}
__host__ __device__ constexpr int GI(int part, int t) { return t < 8 ? part * 8 + t : 24 + part; }

__device__ __forceinline__ void wgmma_ss_216(float* d, uint32_t al, uint32_t ah, uint32_t bl, uint32_t bh) {
  asm volatile("{\n.reg .b64 da, db;\nmov.b64 da, {%108, %109};\nmov.b64 db, {%110, %111};\n"
      "wgmma.mma_async.sync.aligned.m64n216k16.f32.bf16.bf16 {"
      "%0,%1,%2,%3,%4,%5,%6,%7,%8,%9,%10,%11,%12,%13,%14,%15,%16,%17,%18,%19,%20,%21,%22,%23,%24,%25,%26,"
      "%27,%28,%29,%30,%31,%32,%33,%34,%35,%36,%37,%38,%39,%40,%41,%42,%43,%44,%45,%46,%47,%48,%49,%50,%51,%52,%53,"
      "%54,%55,%56,%57,%58,%59,%60,%61,%62,%63,%64,%65,%66,%67,%68,%69,%70,%71,%72,%73,%74,%75,%76,%77,%78,%79,%80,"
      "%81,%82,%83,%84,%85,%86,%87,%88,%89,%90,%91,%92,%93,%94,%95,%96,%97,%98,%99,%100,%101,%102,%103,%104,%105,%106,%107"
      "}, da, db, 1, 1, 1, 0, 1;\n}\n"
      : "+f"(d[0]), "+f"(d[1]), "+f"(d[2]), "+f"(d[3]), "+f"(d[4]), "+f"(d[5]), "+f"(d[6]), "+f"(d[7]), "+f"(d[8]),
        "+f"(d[9]), "+f"(d[10]), "+f"(d[11]), "+f"(d[12]), "+f"(d[13]), "+f"(d[14]), "+f"(d[15]), "+f"(d[16]), "+f"(d[17]),
        "+f"(d[18]), "+f"(d[19]), "+f"(d[20]), "+f"(d[21]), "+f"(d[22]), "+f"(d[23]), "+f"(d[24]), "+f"(d[25]), "+f"(d[26]),
        "+f"(d[27]), "+f"(d[28]), "+f"(d[29]), "+f"(d[30]), "+f"(d[31]), "+f"(d[32]), "+f"(d[33]), "+f"(d[34]), "+f"(d[35]),
        "+f"(d[36]), "+f"(d[37]), "+f"(d[38]), "+f"(d[39]), "+f"(d[40]), "+f"(d[41]), "+f"(d[42]), "+f"(d[43]), "+f"(d[44]),
        "+f"(d[45]), "+f"(d[46]), "+f"(d[47]), "+f"(d[48]), "+f"(d[49]), "+f"(d[50]), "+f"(d[51]), "+f"(d[52]), "+f"(d[53]),
        "+f"(d[54]), "+f"(d[55]), "+f"(d[56]), "+f"(d[57]), "+f"(d[58]), "+f"(d[59]), "+f"(d[60]), "+f"(d[61]), "+f"(d[62]),
        "+f"(d[63]), "+f"(d[64]), "+f"(d[65]), "+f"(d[66]), "+f"(d[67]), "+f"(d[68]), "+f"(d[69]), "+f"(d[70]), "+f"(d[71]),
        "+f"(d[72]), "+f"(d[73]), "+f"(d[74]), "+f"(d[75]), "+f"(d[76]), "+f"(d[77]), "+f"(d[78]), "+f"(d[79]), "+f"(d[80]),
        "+f"(d[81]), "+f"(d[82]), "+f"(d[83]), "+f"(d[84]), "+f"(d[85]), "+f"(d[86]), "+f"(d[87]), "+f"(d[88]), "+f"(d[89]),
        "+f"(d[90]), "+f"(d[91]), "+f"(d[92]), "+f"(d[93]), "+f"(d[94]), "+f"(d[95]), "+f"(d[96]), "+f"(d[97]), "+f"(d[98]),
        "+f"(d[99]), "+f"(d[100]), "+f"(d[101]), "+f"(d[102]), "+f"(d[103]), "+f"(d[104]), "+f"(d[105]), "+f"(d[106]), "+f"(d[107])
      : "r"(al), "r"(ah), "r"(bl), "r"(bh));
}
__device__ __forceinline__ void wgmma_ss_72(float* d, uint32_t al, uint32_t ah, uint32_t bl, uint32_t bh) {
  asm volatile("{\n.reg .b64 da, db;\nmov.b64 da, {%36, %37};\nmov.b64 db, {%38, %39};\n"
      "wgmma.mma_async.sync.aligned.m64n72k16.f32.bf16.bf16 {"
      "%0,%1,%2,%3,%4,%5,%6,%7,%8,%9,%10,%11,%12,%13,%14,%15,%16,%17,%18,%19,%20,%21,%22,%23,%24,%25,%26,"
      "%27,%28,%29,%30,%31,%32,%33,%34,%35"
      "}, da, db, 1, 1, 1, 0, 1;\n}\n"
      : "+f"(d[0]), "+f"(d[1]), "+f"(d[2]), "+f"(d[3]), "+f"(d[4]), "+f"(d[5]), "+f"(d[6]), "+f"(d[7]), "+f"(d[8]),
        "+f"(d[9]), "+f"(d[10]), "+f"(d[11]), "+f"(d[12]), "+f"(d[13]), "+f"(d[14]), "+f"(d[15]), "+f"(d[16]), "+f"(d[17]),
        "+f"(d[18]), "+f"(d[19]), "+f"(d[20]), "+f"(d[21]), "+f"(d[22]), "+f"(d[23]), "+f"(d[24]), "+f"(d[25]), "+f"(d[26]),
        "+f"(d[27]), "+f"(d[28]), "+f"(d[29]), "+f"(d[30]), "+f"(d[31]), "+f"(d[32]), "+f"(d[33]), "+f"(d[34]), "+f"(d[35])
      : "r"(al), "r"(ah), "r"(bl), "r"(bh));
}
template <uint32_t BH>
__device__ __forceinline__ void wgmma_rs_216(float* d, uint32_t a0, uint32_t a1, uint32_t a2, uint32_t a3, uint32_t bl) {
  asm volatile("{\n.reg .b64 db;\nmov.b64 db, {%112, %113};\n"
      "wgmma.mma_async.sync.aligned.m64n216k16.f32.bf16.bf16 {"
      "%0,%1,%2,%3,%4,%5,%6,%7,%8,%9,%10,%11,%12,%13,%14,%15,%16,%17,%18,%19,%20,%21,%22,%23,%24,%25,%26,"
      "%27,%28,%29,%30,%31,%32,%33,%34,%35,%36,%37,%38,%39,%40,%41,%42,%43,%44,%45,%46,%47,%48,%49,%50,%51,%52,%53,"
      "%54,%55,%56,%57,%58,%59,%60,%61,%62,%63,%64,%65,%66,%67,%68,%69,%70,%71,%72,%73,%74,%75,%76,%77,%78,%79,%80,"
      "%81,%82,%83,%84,%85,%86,%87,%88,%89,%90,%91,%92,%93,%94,%95,%96,%97,%98,%99,%100,%101,%102,%103,%104,%105,%106,%107"
      "}, {%108,%109,%110,%111}, db, 1, 1, 1, 1;\n}\n"
      : "+f"(d[0]), "+f"(d[1]), "+f"(d[2]), "+f"(d[3]), "+f"(d[4]), "+f"(d[5]), "+f"(d[6]), "+f"(d[7]), "+f"(d[8]),
        "+f"(d[9]), "+f"(d[10]), "+f"(d[11]), "+f"(d[12]), "+f"(d[13]), "+f"(d[14]), "+f"(d[15]), "+f"(d[16]), "+f"(d[17]),
        "+f"(d[18]), "+f"(d[19]), "+f"(d[20]), "+f"(d[21]), "+f"(d[22]), "+f"(d[23]), "+f"(d[24]), "+f"(d[25]), "+f"(d[26]),
        "+f"(d[27]), "+f"(d[28]), "+f"(d[29]), "+f"(d[30]), "+f"(d[31]), "+f"(d[32]), "+f"(d[33]), "+f"(d[34]), "+f"(d[35]),
        "+f"(d[36]), "+f"(d[37]), "+f"(d[38]), "+f"(d[39]), "+f"(d[40]), "+f"(d[41]), "+f"(d[42]), "+f"(d[43]), "+f"(d[44]),
        "+f"(d[45]), "+f"(d[46]), "+f"(d[47]), "+f"(d[48]), "+f"(d[49]), "+f"(d[50]), "+f"(d[51]), "+f"(d[52]), "+f"(d[53]),
        "+f"(d[54]), "+f"(d[55]), "+f"(d[56]), "+f"(d[57]), "+f"(d[58]), "+f"(d[59]), "+f"(d[60]), "+f"(d[61]), "+f"(d[62]),
        "+f"(d[63]), "+f"(d[64]), "+f"(d[65]), "+f"(d[66]), "+f"(d[67]), "+f"(d[68]), "+f"(d[69]), "+f"(d[70]), "+f"(d[71]),
        "+f"(d[72]), "+f"(d[73]), "+f"(d[74]), "+f"(d[75]), "+f"(d[76]), "+f"(d[77]), "+f"(d[78]), "+f"(d[79]), "+f"(d[80]),
        "+f"(d[81]), "+f"(d[82]), "+f"(d[83]), "+f"(d[84]), "+f"(d[85]), "+f"(d[86]), "+f"(d[87]), "+f"(d[88]), "+f"(d[89]),
        "+f"(d[90]), "+f"(d[91]), "+f"(d[92]), "+f"(d[93]), "+f"(d[94]), "+f"(d[95]), "+f"(d[96]), "+f"(d[97]), "+f"(d[98]),
        "+f"(d[99]), "+f"(d[100]), "+f"(d[101]), "+f"(d[102]), "+f"(d[103]), "+f"(d[104]), "+f"(d[105]), "+f"(d[106]), "+f"(d[107])
      : "r"(a0), "r"(a1), "r"(a2), "r"(a3), "r"(bl), "n"(BH));
}

struct Ctx {
  int i, j, cta;
};
#define TSTAMP(k) do {} while (0)
#define PSTAMP(k) do {} while (0)
#define PROF_DUMP() do {} while (0)
#define PROF_END() do {} while (0)
#define GSTAMP(k) do {} while (0)
#define CSTAMP(k) STAMPIF(1, L * 40 + p * 20 + (k))

__device__ __forceinline__ int ffn_c32(int cta) { return 32 * cta; }
__device__ __forceinline__ int ffn_c8(int cta) { return 4096 + 8 * (cta >> 1); }
__device__ __forceinline__ void load_gu(const Params& P, const int cta_, const int mat, const int b, const uint32_t bar) {
  const int cta = cta_;
  w_tma2d(sb + SM_G + mat * 46080 + b * 6144, &P.mg + mat, ffn_c32(cta), b * 96, bar);
  if (cta & 1) w_tma2d(sb + SM_G + mat * 46080 + 36864 + b * 1536, &P.mg8 + mat, ffn_c8(cta), b * 96, bar);
}

struct Winner { float r, m, rstd; int ci, rr; };

__device__ __forceinline__ Winner poll_winner(const void* p, uint4 v, const uint32_t tg) {
  int n = 0;
#pragma unroll 1
  while (!__all_sync(0xffffffffu, ((v.y ^ (tg << 6)) >> 6) == 0)) {
    rld128(v, p);
    if (++n > SPIN) TIMEOUT(__LINE__)
  }
  uint32_t key = fkey(asf(v.x));
  uint32_t mx = __reduce_max_sync(0xffffffffu, key);
  int src = __ffs(__ballot_sync(0xffffffffu, key == mx)) - 1;
  Winner w;
  w.ci = src;
  w.r = asf(__shfl_sync(0xffffffffu, v.x, src));
  w.rr = (int)__shfl_sync(0xffffffffu, v.y, src) & 63;
  w.m = asf(__shfl_sync(0xffffffffu, v.z, src));
  w.rstd = asf(__shfl_sync(0xffffffffu, v.w, src));
  return w;
}

__device__ __forceinline__ float2 row_stats(const Params& P, const int r, const int lane) {
  const unsigned char* src = (const unsigned char*)P.x + (((r & ~127) + 2 * (r & 63) + ((r >> 6) & 1)) * 1152 + (lane & 15) * 16);
  uint4 v[4];
#pragma unroll
  for (int m = 0; m < 4; m++) v[m] = ldg_nc128(src + m * 256);
  uint2 v4;
  asm volatile("ld.global.nc.v2.b32 {%0,%1}, [%2];" : "=r"(v4.x), "=r"(v4.y) : "l"(src + (1024 - (lane & 15) * 8)));
  nb_arrive(NB_START, 288 + pin0(v4.x));
  const float sft = __shfl_sync(0xffffffffu, bf_lo(v[0].x), lane & 16);
  float s1 = 0.f, s2 = 0.f, s3 = 0.f;
#pragma unroll
  for (int e = 0; e < 18; e++) {
    const uint32_t u = e < 16 ? (&v[0].x)[e] : (&v4.x)[e - 16];
    const float d0 = bf_lo(u) - sft, d1 = bf_hi(u) - sft;
    s1 += d0 + d1; s2 = fmaf(d0, d0, s2); s3 = fmaf(d1, d1, s3);
  }
  s2 += s3;
#pragma unroll
  for (int o = 1; o < 16; o <<= 1) { s1 += shx(s1, o); s2 += shx(s2, o); }
  s1 *= (1.f / 576.f);
  return make_float2(s1 + sft, rsq(fmaxf(s2 * (1.f / 576.f) - s1 * s1, 0.f) + EPS));
}

struct Unit { uint4 v[3]; };
__device__ __forceinline__ Unit unit_load(const unsigned char* src) {
  Unit u;
#pragma unroll
  for (int m = 0; m < 3; m++) u.v[m] = ldg_nc128(src + m * 48);
  return u;
}
__device__ __forceinline__ uint32_t unit_store(unsigned char* sc, const Unit& u, const int lane, const uint32_t o0, const uint32_t o1, const uint32_t o2) {
  stg128(sc + o0, u.v[0].x, u.v[0].y, u.v[0].z, u.v[0].w);
  stg128(sc + o1, u.v[1].x, u.v[1].y, u.v[1].z, u.v[1].w);
  stg128(sc + o2, u.v[2].x, u.v[2].y, u.v[2].z, u.v[2].w);
  return ldg_rlx32(sc + ((lane & 3) == 0 ? o0 : (lane & 3) == 1 ? o1 : o2));
}

__device__ __forceinline__ void store_rows(const uint32_t stg, unsigned char* obase, const int skip, const int lane) {
#pragma unroll
  for (int m = 0; m < 5; m++) {
    const int e = lane + 32 * m, r = (e * 57) >> 9;
    const uint4 v = lds128(stg + min(e, 143) * 16);
    if (e < 144 && r != skip) *(uint4*)(obase + (r * (2304 - 144) + e * 16)) = v;
  }
}

__device__ __forceinline__ void consumer_role(const Ctx& cx, const Params& P, const unsigned char* smem, const int p, const int w, const int lane_) {
  int lane = lane_;
#define g (lane >> 2)
#define q (lane & 3)
#define first_lane (lane == 0)
  const int i = cx.i, j = cx.j, ip = i * 2 + p;
  unsigned char* const sc = (unsigned char*)P.sc;
  float m_lo = 0.f, m_hi = 0.f, rs_lo = 0.f, rs_hi = 0.f;
  uint32_t T = ldg_rlx32(P.sc->cflag[ip][j * 4 + w]);
  nb_sync(NB_ORD, 352);
  if (X_DELAY) { const int c0 = clock(); while ((int)(clock() - c0) < X_DELAY + (p * 4 + w) * X_STEP) {} }
  {
    const int t = min(w * 32 + lane, 95);
    uint32_t u0 = 0, u1 = 0, u2 = 0, u = 0;
    if (p == 0) {
      u0 = ldg_nc32((const uint32_t*)P.wr + t); u1 = ldg_nc32((const uint32_t*)P.wr + 96 + t); u2 = ldg_nc32((const uint32_t*)P.wr + 192 + t);
      u = ldg_nc32((const uint32_t*)P.wr + 36 * j + min(t, 35));
    }
    const int r = cx.cta * 16 + (p * 4 + w) * 2 + (lane >> 4);
    const float2 st = row_stats(P, r, lane);
    T = __shfl_sync(0xffffffffu, (T >> 3) + 1, 0);
    if ((lane & 15) == 0) stg128(sc + (OFF(st0) + r * 16), asu(st.x), asu(st.y), T, 0u);
    STAMPIF(1, 111);
    if (p == 0) {
      float s = (bf_lo(u0) + bf_hi(u0)) + (bf_lo(u1) + bf_hi(u1)) + (bf_lo(u2) + bf_hi(u2));
#pragma unroll
      for (int o = 1; o < 32; o <<= 1) s += shx(s, o);
      stsf(sb + SM_WR + 288 + w * 4, s);
      sts64(sb + SM_WR + min(t, 35) * 8, u << 16, u & 0xFFFF0000u);
    }
  }
#pragma unroll 1
  for (int L = 0; L < 2; L++) {
    lane = pin(lane);
    const uint32_t tg = 2 * T + L;
    float c_lo = 0.f, c_hi = 0.f;
    bool sel_lo = false, sel_hi = false;
    float acc[108];
#pragma unroll
    for (int k = 0; k < 108; k++) acc[k] = 0.f;
    fence_regs<108>(acc);
    {
      const uint32_t ah = L == 0 ? DHI(1024, 1) : DHI(128, 0);
      const uint32_t astep = L == 0 ? 2 : 128;
      const uint32_t a0 = (L == 0 ? DLO(sb + SM_A, 16) : DLO(sb + SM_A, 1024)) + p * 512;
      constexpr uint32_t bh = DHI(512, 0);
      if (L == 1) {
        const float ul = 1.f + rs_lo, uh = 1.f + rs_hi;
        const float vl = fmaxf(rcp(rs_lo * rs_lo) - EPS, 0.f), vh = fmaxf(rcp(rs_hi * rs_hi) - EPS, 0.f);
        c_lo = ul * rsq(vl * ul * ul + EPS);
        c_hi = uh * rsq(vh * uh * uh + EPS);
      }
      if (L == 1) mbar_wait(sb + BAR_AFULL + p * 8, 0);
      mbar_wait(sb + BAR_FULL, 0);
      if (L == 1 && p == 1) nb_sync(NB_FFN2, 224);
      CSTAMP(0); GSTAMP(120 + 2 * L);
      uint32_t e0 = 0, e1 = 0;
      bool prepped = false, gone = false;
      auto prep_ext = [&]() {
        const int row = p * 64 + w * 16 + g;
        if (L == 0) {
          const uint2 u0 = lds64(sb + SM_R + row * 8), u1 = lds64(sb + SM_R + row * 8 + 64);
          m_lo = asf(u0.x); c_lo = asf(u0.y); m_hi = asf(u1.x); c_hi = asf(u1.y);
        } else {
          const uint4 sv = lds128(sb + SM_SEL);
          sel_lo = (int)sv.x == row; sel_hi = (int)sv.x == row + 8;
          if (sel_lo) { m_lo = asf(sv.z); c_lo = asf(sv.w); }
          if (sel_hi) { m_hi = asf(sv.z); c_hi = asf(sv.w); }
        }
        const float hl = rbf(-m_lo), hh = rbf(-m_hi);
        const uint32_t em = selu(lane & 1, 0x0000FFFFu, 0xFFFFFFFFu);
        e0 = selu(lane & 2, selu(sel_lo && !(lane & 1), 0x3F803F80u, 0u), pack_bf16(hl, -m_lo - hl) & em);
        e1 = selu(lane & 2, selu(sel_hi && !(lane & 1), 0x3F803F80u, 0u), pack_bf16(hh, -m_hi - hh) & em);
      };
      bool pend = false;
#pragma unroll 1
      for (int r = 0; r < 3; r++) {
#pragma unroll
        for (int h = 0; h < 6; h++) {
          const uint32_t al = a0 + (h >> 1) * 1024 + (h & 1) * 2 * astep, bl = DLO(sb + SM_B, 128) + h * 864;
          const uint32_t nb = sb + BAR_FULL + ((h + 1) % 6) * 8, np = (r + (h == 5)) & 1;
          TSTAMP((6 * r + h) * 2);
          wg_fence();
          wgmma_ss_216(acc, al, ah, bl, bh);
          wgmma_ss_216(acc, al + astep, ah, bl + 16, bh);
          wg_commit();
          if (h == 5 && r == 2) break;
          const uint32_t ok = mbar_test(nb, np);
          if ((h == 1 || h == 3) && r == 0 && L == 1) mbar_wait(sb + BAR_AFULL + (h + 1 + p) * 8, 0);
          if (h == 0 && r == 1 && L == 0) {
          if (lane < 16) stg128(sc + (OFF(stats) + (ip * 4 + w) * 2048 + j * 256 + lane * 16), 0u, 0u, 0u, 0u);
          if (w == 3 && i < 15 && lane < 28) {
#pragma unroll
            for (int e = 0; e < 6; e++) stg128(sc + (OFF(halo) + ((ip + 2) * 8 + j) * 2688 + lane * 16) + e * 448, 0u, 0u, 0u, 0u);
          }
          if (w == 0 && lane < 2) stg128(sc + (OFF(cand) + (j * 32 + ip) * (CAND_W * 4) + lane * 16), 0u, 0u, 0u, 0u);
          }
          wg_wait<1>();
          if (first_lane && pend) mbar_arrive(sb + BAR_EMPTY + ((h + 5) % 6) * 8);
          pend = true;
          const bool hold = h == HOLD_C % 6 && r == HOLD_C / 6 && p == 1;
          if (hold || (!ok && !mbar_test(nb, np))) {
            wg_wait<0>();
            if (first_lane) mbar_arrive(sb + BAR_EMPTY + h * 8);
            pend = false;
            TSTAMP((6 * r + h) * 2 + 1);
            mbar_wait(nb, np);
            if (hold) {
              if (mbar_test(sb + BAR_FIX + 8, L)) { prep_ext(); prepped = true; }
              nb_sync(NB_STAG, 256);
            }
          }
        }
      }
      if (!prepped) {
        if (p == 0 && !gone && !mbar_test(sb + BAR_FIX, L)) { nb_arrive(NB_STAG, 256); gone = true; }
        mbar_wait(sb + BAR_FIX + p * 8, L);
        prep_ext();
      }
      wg_fence();
      wgmma_rs_216<DHI(128, 0)>(acc, e0, e1, 0u, 0u, DLO(sb + SM_BEXT, 0));
      wg_commit();
      if (p == 0 && !gone) nb_arrive(NB_STAG, 256);
      wg_wait<2>();
      if (first_lane && pend) mbar_arrive(sb + BAR_EMPTY + 32);
    }
    lane = pin(lane);
    const uint32_t fragoff = ip * 73728 + (9 * j) * 1024 + w * 256 + lane * 4;
    const uint32_t rboff = (min(lane, 17) >> 1) * 1024 + (lane < 18 ? lane & 1 : 0) * 128;
    const uint32_t hl16 = (lane < 4 ? lane : lane - 4) * 16;
    const uint32_t o_halo = pin(OFF(halo) + ((ip + (w == 3 ? 2 : 0)) * 8 + j) * 2688 + hl16);
    const uint32_t o_o = pin(OFF(obuf) + fragoff);
    nb_sync(NB_WG + p, 128);
    if ((o_halo | o_o) == 0xFFFFFFFFu) __trap();
    wg_wait<0>();
    fence_regs<108>(acc);
    if (first_lane) mbar_arrive(sb + BAR_EMPTY + 40);
    CSTAMP(1); GSTAMP(121 + 2 * L);
    {
      uint32_t Kh[9], Vh[9], Kl[9], Vl[9], Kx[9], Vx[9], Ql[9], Qh[9];
#pragma unroll
      for (int t = 0; t < 9; t++) {
        Kh[t] = pack_bf16(acc[4 * GI(1, t) + 2] * c_hi, acc[4 * GI(1, t) + 3] * c_hi);
        Vh[t] = pack_bf16(acc[4 * GI(2, t) + 2] * c_hi, acc[4 * GI(2, t) + 3] * c_hi);
        Ql[t] = pack_bf16(acc[4 * GI(0, t)], acc[4 * GI(0, t) + 1]);
        Qh[t] = pack_bf16(acc[4 * GI(0, t) + 2], acc[4 * GI(0, t) + 3]);
      }
      const uint32_t hbuf = sb + SM_A + p * 8192 + w * 2688 + hl16;
      if (w < 3) {
        if (lane >= 4) {
#pragma unroll
          for (int e = 0; e < 4; e++) sts128(hbuf + e * 448, Kh[2 * e], Kh[2 * e + 1], Vh[e], tg);
          sts128(hbuf + 4 * 448, Kh[8], Vh[4], Vh[5], tg);
          sts128(hbuf + 5 * 448, Vh[6], Vh[7], Vh[8], tg);
        }
      } else if (i < 15 && lane >= 4) {
#pragma unroll
        for (int e = 0; e < 4; e++) stg128(sc + o_halo + e * 448, Kh[2 * e], Kh[2 * e + 1], Vh[e], tg);
        stg128(sc + o_halo + 4 * 448, Kh[8], Vh[4], Vh[5], tg);
        stg128(sc + o_halo + 5 * 448, Vh[6], Vh[7], Vh[8], tg);
      }
      nb_sync(NB_WG + p, 128);
#pragma unroll
      for (int t = 0; t < 9; t++) {
        Kl[t] = pack_bf16(acc[4 * GI(1, t)] * c_lo, acc[4 * GI(1, t) + 1] * c_lo);
      }
#pragma unroll
      for (int t = 0; t < HALO_V; t++) Vl[t] = pack_bf16(acc[4 * GI(2, t)] * c_lo, acc[4 * GI(2, t) + 1] * c_lo);
      uint32_t dep = (Kl[0] ^ Kl[1] ^ Kl[2]) | (Kl[3] ^ Kl[4] ^ Kl[5]) | (Kl[6] ^ Kl[7] ^ Kl[8]);
#pragma unroll
      for (int t = 0; t < HALO_V; t += 3) dep |= Vl[t] ^ Vl[t + 1] ^ Vl[t + 2];
      const unsigned char* hp = (w > 0 ? smem + (hbuf - 2688 - sb) : sc + o_halo) + pin0(dep);
      uint4 hv[6];
#pragma unroll
      for (int e = 0; e < 6; e++)
        asm volatile("ld.relaxed.gpu.v4.b32 {%0,%1,%2,%3}, [%4];" : "=r"(hv[e].x), "=r"(hv[e].y), "=r"(hv[e].z), "=r"(hv[e].w) : "l"(hp + e * 448) : "memory");
      CSTAMP(2);
#pragma unroll
      for (int t = 0; t < 9; t++) {
        if (t >= HALO_V) Vl[t] = pack_bf16(acc[4 * GI(2, t)] * c_lo, acc[4 * GI(2, t) + 1] * c_lo);
        Vl[t] = movm(Vl[t]);
        Vh[t] = movm(Vh[t]);
      }
      uint32_t qa[4][2], qb[4][2];
      float s1[4][4], s2[4][4];
#pragma unroll
      for (int h = 0; h < 4; h++) {
        qa[h][0] = q >= h ? Ql[2 * h] : 0u; qa[h][1] = q >= h ? Qh[2 * h] : 0u;
        qb[h][0] = q <= h ? Ql[2 * h + 2] : 0u; qb[h][1] = q <= h ? Qh[2 * h + 2] : 0u;
      }
      const bool first = (i == 0 && w == 0);
      if (w == 0 && i > 0) {
        int n = 0;
#pragma unroll 1
        while (__any_sync(0xffffffffu, (orx(orx(orx(0, hv[0].w, tg), hv[1].w, tg), hv[2].w, tg) | orx(orx(orx(0, hv[3].w, tg), hv[4].w, tg), hv[5].w, tg)) != 0)) {
#pragma unroll
          for (int e = 0; e < 6; e++) rld128(hv[e], sc + o_halo + e * 448);
          if (++n > SPIN) TIMEOUT(__LINE__)
        }
      }
#pragma unroll
      for (int e = 0; e < 4; e++) { Kx[2 * e] = hv[e].x; Kx[2 * e + 1] = hv[e].y; Vx[e] = hv[e].z; }
      Kx[8] = hv[4].x; Vx[4] = hv[4].y; Vx[5] = hv[4].z; Vx[6] = hv[5].x; Vx[7] = hv[5].y; Vx[8] = hv[5].z;
      CSTAMP(3);
#pragma unroll
      for (int t = 0; t < 9; t++) Vx[t] = movm(Vx[t]);
#pragma unroll
      for (int h = 0; h < 4; h++) { mma8z(s1[h], qb[h][0], qb[h][1], Kl[2 * h + 2]); mma8z(s2[h], qb[h][0], qb[h][1], Kh[2 * h + 2]); }
#pragma unroll
      for (int h = 0; h < 4; h++) {
        mma16(s1[h], qa[h][0], qa[h][1], Ql[2 * h + 1], Qh[2 * h + 1], Kl[2 * h], Kl[2 * h + 1]);
        mma16(s2[h], qa[h][0], qa[h][1], Ql[2 * h + 1], Qh[2 * h + 1], Kh[2 * h], Kh[2 * h + 1]);
      }
      float s0[4][4];
#pragma unroll
      for (int h = 0; h < 4; h++) mma8z(s0[h], qb[h][0], qb[h][1], Kx[2 * h + 2]);
#pragma unroll
      for (int h = 0; h < 4; h++) mma16(s0[h], qa[h][0], qa[h][1], Ql[2 * h + 1], Qh[2 * h + 1], Kx[2 * h], Kx[2 * h + 1]);
      const bool pv0 = 2 * q > g, pv1 = 2 * q + 1 > g;
      const uint32_t PM = (pv0 ? 0x0000FFFFu : 0u) | (pv1 ? 0xFFFF0000u : 0u);
      const float kS = 0.23570226039551584f * 1.4426950408889634f;
      const float sc_lo = c_lo * kS, sc_hi = c_hi * kS;
      float sl[4][2], sh[4][2], ml[4], mh[4];
#pragma unroll
      for (int h = 0; h < 4; h++) {
        sh[h][0] = pv0 ? s1[h][2] : s2[h][2];
        sh[h][1] = pv1 ? s1[h][3] : s2[h][3];
        mh[h] = fmaxf(sh[h][0], sh[h][1]);
        sl[h][0] = pv0 ? (first ? -INFINITY : s0[h][0]) : s1[h][0];
        sl[h][1] = pv1 ? (first ? -INFINITY : s0[h][1]) : s1[h][1];
        ml[h] = fmaxf(sl[h][0], sl[h][1]);
      }
#pragma unroll
      for (int s = 1; s <= 2; s <<= 1) {
        float tl[4], th[4];
#pragma unroll
        for (int h = 0; h < 4; h++) { th[h] = shx(mh[h], s); tl[h] = shx(ml[h], s); }
#pragma unroll
        for (int h = 0; h < 4; h++) { mh[h] = fmaxf(mh[h], th[h]); ml[h] = fmaxf(ml[h], tl[h]); }
      }
      float o[4][3][4], den[4][4];
      uint32_t px[4];
#pragma unroll
      for (int h = 0; h < 4; h++) {
        const float bl = -ml[h] * sc_lo, bh = -mh[h] * sc_hi;
        const uint32_t pl = pack_bf16(ex2(fmaf(sl[h][0], sc_lo, bl)), ex2(fmaf(sl[h][1], sc_lo, bl)));
        const uint32_t ph = pack_bf16(ex2(fmaf(sh[h][0], sc_hi, bh)), ex2(fmaf(sh[h][1], sc_hi, bh)));
        mma8z(den[h], pl, ph, 0x3F803F80u);
        px[h] = pl & PM;
#pragma unroll
        for (int u = 0; u < 3; u++) mma16z(o[h][u], pl & ~PM, ph & PM, 0u, ph & ~PM, Vl[2 * h + u], Vh[2 * h + u]);
      }
#pragma unroll
      for (int h = 0; h < 4; h++)
#pragma unroll
        for (int u = 0; u < 3; u++) mma8(o[h][u], px[h], 0u, Vx[2 * h + u]);
      float il[4], ih[4];
#pragma unroll
      for (int h = 0; h < 4; h++) { il[h] = rcp(den[h][0]); ih[h] = rcp(den[h][2]); }
#pragma unroll
      for (int t = 0; t < 9; t++) {
        const int h = t == 8 ? 3 : t >> 1, u = t == 8 ? 2 : t & 1;
        float v0 = o[h][u][0], v1 = o[h][u][1], v2 = o[h][u][2], v3 = o[h][u][3], kl = il[h], kh = ih[h];
        if (u == 0 && h > 0 && q < h) {
          v0 = o[h - 1][2][0]; v1 = o[h - 1][2][1]; v2 = o[h - 1][2][2]; v3 = o[h - 1][2][3]; kl = il[h - 1]; kh = ih[h - 1];
        }
        stg32(sc + o_o + t * 1024, pack_bf16(v0 * kl, v1 * kl));
        stg32(sc + o_o + t * 1024 + 128, pack_bf16(v2 * kh, v3 * kh));
      }
    }
    CSTAMP(4);
    const uint32_t rbo = ldg_rlx32(sc + (o_o + rboff));
    lane = pin(lane);
    const uint32_t o_x = o_o + (OFF(xbuf) - OFF(obuf)), o_xrb = o_x + rboff;
    const uint32_t o_cf = OFF(cflag) + (ip * 32 + j * 4 + w) * 32 + lane * 4;
    if (L == 1 && first_lane) mbar_arrive(sb + BAR_HDONE + p * 8);
    flag_after(sc + o_cf, rbo, 8 * T + 2 * L, lane < 8);
    STAMPD(asf(rbo), L * 40 + p * 20 + 13);
    uint32_t resid[18];
    mbar_wait(sb + BAR_FULL + 16, 1); mbar_wait(sb + BAR_FULL + 32, 1);
    if (L == 0) {
      const uint32_t ra = sb + SM_A + (2 + p) * 8192 + (w * 16 + (lane & 15)) * 128;
#pragma unroll
      for (int t = 0; t < 9; t++) ldsm2(resid[2 * t], resid[2 * t + 1], ra + ((j + t) >> 3) * 16384 + ((((j + t) ^ lane) & 7) << 4));
      if (first_lane) mbar_arrive(sb + BAR_HDONE + p * 8 + pin0(resid[17]));
    } else {
#pragma unroll
      for (int t = 0; t < 9; t++) { resid[2 * t] = ldg_rlx32(sc + o_x + t * 1024); resid[2 * t + 1] = ldg_rlx32(sc + o_x + t * 1024 + 128); }
    }
    const uint32_t o_st = OFF(stats) + (ip * 4 + w) * 2048;
    const uint32_t o_stw = pin(o_st + j * 256 + (g + 8 * (q & 1)) * 16), o_str = pin(o_st + q * 512 + g * 16);
    const uint32_t o_cand = pin(OFF(cand) + (j * 32 + ip) * (CAND_W * 4) + q * 16);
    const uint32_t o_xc = pin(OFF(xcand) + (ip * 8 + j) * 192 + q * 16);
    float accw[36];
    float wr[18];
#pragma unroll
    for (int t = 0; t < 9; t++) { const uint2 u = lds64(sb + SM_WR + t * 32 + q * 8); wr[2 * t] = asf(u.x); wr[2 * t + 1] = asf(u.y); }
    const uint4 ws4 = lds128(sb + SM_WR + 288);
    const float wsum = asf(pin(asu(asf(ws4.x) + asf(ws4.y) + asf(ws4.z))));
    {
      float ul = 1.f, uh = 1.f, vl = 0.f, vh = 0.f;
      if (L == 1) {
        ul += rs_lo; uh += rs_hi; vl = -m_lo * rs_lo; vh = -m_hi * rs_hi;
        if (sel_lo || sel_hi) {
#pragma unroll
          for (int t = 0; t < 9; t++) {
            const uint32_t z = lds32(sb + SM_X2S + t * 16 + q * 4);
            if (sel_hi) resid[2 * t + 1] = z; else resid[2 * t] = z;
          }
          if (sel_hi) { uh = 1.f; vh = 0.f; } else { ul = 1.f; vl = 0.f; }
        }
        __syncwarp();
      }
#pragma unroll
      for (int t = 0; t < 9; t++) {
        accw[4 * t] = fmaf(bf_lo(resid[2 * t]), ul, vl); accw[4 * t + 1] = fmaf(bf_hi(resid[2 * t]), ul, vl);
        accw[4 * t + 2] = fmaf(bf_lo(resid[2 * t + 1]), uh, vh); accw[4 * t + 3] = fmaf(bf_hi(resid[2 * t + 1]), uh, vh);
      }
    }
    fence_regs<36>(accw);
    mbar_wait(sb + BAR_FULL, 1); mbar_wait(sb + BAR_FULL + 8, 1); mbar_wait(sb + BAR_FULL + 24, 1); mbar_wait(sb + BAR_FULL + 40, 1);
    {
      uint32_t wf = sb + BAR_WFULL + p * 72;
      uint32_t bl = DLO(sb + SM_B, 128);
      uint32_t half = p;
      mbar_wait(wf, L);
      CSTAMP(5);
#pragma unroll 1
      for (int c3 = 0; c3 < 3; c3++) {
        const uint32_t al = DLO(sb + SM_A, 1024) + half * 512;
        const uint32_t ae = sb + BAR_AEMPTY + half * 24;
#pragma unroll
        for (int cc = 0; cc < 3; cc++) {
          TSTAMP(36 + (c3 * 3 + cc) * 2);
          wg_fence();
          wgmma_ss_72(accw, al + cc * 1024, DHI(128, 0), bl + cc * 576, DHI(256, 0));
          wgmma_ss_72(accw, al + cc * 1024 + 128, DHI(128, 0), bl + cc * 576 + 144, DHI(256, 0));
          const uint32_t ok = mbar_test(wf + cc * 8 + 8, L);
          wgmma_ss_72(accw, al + cc * 1024 + 256, DHI(128, 0), bl + cc * 576 + 288, DHI(256, 0));
          wgmma_ss_72(accw, al + cc * 1024 + 384, DHI(128, 0), bl + cc * 576 + 432, DHI(256, 0));
          wg_commit();
          wg_wait<1>();
          if (cc > 0) { if (first_lane) { mbar_arrive(ae + cc * 8 - 8); if (cc == 2) mbar_arrive(sb + BAR_EMPTY + c3 * 16); } }
          else if (first_lane && c3 > 0) { mbar_arrive(sb + BAR_AEMPTY + 40 - half * 24); mbar_arrive(sb + BAR_EMPTY + c3 * 16 - 8); }
          if (!ok && (cc < 2 || c3 < 2)) mbar_wait(wf + cc * 8 + 8, L);
        }
        wf += 24; bl += 1728; half ^= 1;
      }
    }
    wg_wait<0>();
    fence_regs<36>(accw);
    if (first_lane) { mbar_arrive(sb + BAR_AEMPTY + (2 + 3 * p) * 8); mbar_arrive(sb + BAR_EMPTY + 40); }
    CSTAMP(6);
    uint32_t xw[18];
    uint32_t rb = 0;
    if (L == 0 && p == 0) {
#pragma unroll
      for (int t = 0; t < 9; t++) {
        stg32(sc + o_x + t * 1024, pack_bf16(accw[4 * t], accw[4 * t + 1]));
        stg32(sc + o_x + t * 1024 + 128, pack_bf16(accw[4 * t + 2], accw[4 * t + 3]));
      }
      rb = ldg_rlx32(sc + o_xrb);
      fence_regs<36>(accw);
    }
    {
      float a0[2] = {0.f, 0.f}, a1[2] = {0.f, 0.f}, a2[2] = {0.f, 0.f}, b0[2] = {0.f, 0.f}, b1[2] = {0.f, 0.f}, b2[2] = {0.f, 0.f};
#pragma unroll
      for (int t = 0; t < 9; t++) {
#pragma unroll
        for (int e = 0; e < 2; e++) {
          const float x = accw[4 * t + e], y = accw[4 * t + 2 + e];
          a0[e] += x; a1[e] = fmaf(x, x, a1[e]); a2[e] = fmaf(x, wr[2 * t + e], a2[e]);
          b0[e] += y; b1[e] = fmaf(y, y, b1[e]); b2[e] = fmaf(y, wr[2 * t + e], b2[e]);
        }
      }
      const bool od = q & 1;
      const float A0 = a0[0] + a0[1], A1 = a1[0] + a1[1], A2 = a2[0] + a2[1], B0 = b0[0] + b0[1], B1 = b1[0] + b1[1], B2 = b2[0] + b2[1];
      float k0 = od ? B0 : A0, k1 = od ? B1 : A1, k2 = od ? B2 : A2;
      k0 += shx(od ? A0 : B0, 1); k1 += shx(od ? A1 : B1, 1); k2 += shx(od ? A2 : B2, 1);
      k0 += shx(k0, 2); k1 += shx(k1, 2); k2 += shx(k2, 2);
      if (q < 2) stg128(sc + o_stw, asu(k0), asu(k1), asu(k2), tg);
      STAMPD(k0, L * 40 + p * 20 + 14);
    }
#pragma unroll
    for (int t = 0; t < 9; t++) {
      xw[2 * t] = pack_bf16(accw[4 * t], accw[4 * t + 1]);
      xw[2 * t + 1] = pack_bf16(accw[4 * t + 2], accw[4 * t + 3]);
    }
    float r_lo, r_hi;
    {
      uint4 u0 = ldg_rlx128(sc + o_str), u1 = ldg_rlx128(sc + o_str + 256), u2 = ldg_rlx128(sc + o_str + 128), u3 = ldg_rlx128(sc + o_str + 384);
      flag_after(sc + o_cf, rb, 8 * T + 1, lane < 8 && L == 0 && p == 0);
      STAMPD(asf(u3.w), L * 40 + p * 20 + 15);
      int n = 0;
#pragma unroll 1
      while (__any_sync(0xffffffffu, orx(orx(orx(orx(0, u0.w, tg), u1.w, tg), u2.w, tg), u3.w, tg) != 0)) {
        rld128(u0, sc + o_str); rld128(u1, sc + o_str + 256); rld128(u2, sc + o_str + 128); rld128(u3, sc + o_str + 384);
        if (++n > SPIN) TIMEOUT(__LINE__)
      }
      float a0 = asf(u0.x) + asf(u1.x), a1 = asf(u0.y) + asf(u1.y), a2 = asf(u0.z) + asf(u1.z);
      float b0 = asf(u2.x) + asf(u3.x), b1 = asf(u2.y) + asf(u3.y), b2 = asf(u2.z) + asf(u3.z);
#pragma unroll
      for (int s = 1; s <= 2; s <<= 1) {
        const float t0 = shx(a0, s), t1 = shx(a1, s), t2 = shx(a2, s), t3 = shx(b0, s), t4 = shx(b1, s), t5 = shx(b2, s);
        a0 += t0; a1 += t1; a2 += t2; b0 += t3; b1 += t4; b2 += t5;
      }
      m_lo = a0 * (1.f / 576.f); m_hi = b0 * (1.f / 576.f);
      rs_lo = rsq(fmaxf(a1 * (1.f / 576.f) - m_lo * m_lo, 0.f) + EPS);
      rs_hi = rsq(fmaxf(b1 * (1.f / 576.f) - m_hi * m_hi, 0.f) + EPS);
      r_lo = (a2 - m_lo * wsum) * rs_lo; r_hi = (b2 - m_hi * wsum) * rs_hi;
    }
    CSTAMP(7);
    int candrow = -1;
    {
      const uint32_t kl = fkey(r_lo), kh = fkey(r_hi);
      const bool hi = kh > kl;
      const uint32_t kb = hi ? kh : kl;
      const uint32_t mx = __reduce_max_sync(0xffffffffu, kb);
      if (first_lane) sts32(sb + SM_BEST + p * 16 + w * 4, mx);
      const uint32_t bal = __ballot_sync(0xffffffffu, kb == mx);
      const bool mine = (bal & ((1u << (lane & 28)) - 1u)) == 0u && kb == mx;
      const uint32_t x0 = hi ? xw[1] : xw[0], x1 = hi ? xw[3] : xw[2], x2 = hi ? xw[5] : xw[4], x3 = hi ? xw[7] : xw[6], x4 = hi ? xw[9] : xw[8];
      const uint32_t x5 = hi ? xw[11] : xw[10], x6 = hi ? xw[13] : xw[12], x7 = hi ? xw[15] : xw[14], x8 = hi ? xw[17] : xw[16];
      nb_sync(NB_WG + p, 128);
      const uint4 bs = lds128(sb + SM_BEST + p * 16);
      const bool best = (w > 0 ? bs.x < mx : true) && (w > 1 ? bs.y < mx : bs.y <= mx) && (w > 2 ? bs.z < mx : bs.z <= mx) && bs.w <= mx;
      if (best && mine) {
        if (q < 2) stg128(sc + o_cand, asu(hi ? r_hi : r_lo), (tg << 6) + (uint32_t)(w * 16 + g + (hi ? 8 : 0)), asu(hi ? m_hi : m_lo), asu(hi ? rs_hi : rs_lo));
        stg128(sc + o_xc, x0, x1, x2, tg);
        stg128(sc + o_xc + 64, x3, x4, x5, tg);
        stg128(sc + o_xc + 128, x6, x7, x8, tg);
      }
      candrow = __reduce_max_sync(0xffffffffu, best && mine ? g + (hi ? 8 : 0) : -1);
    }
    if (L == 0 && p == 1) {
#pragma unroll
      for (int t = 0; t < 9; t++) { stg32(sc + o_x + t * 1024, xw[2 * t]); stg32(sc + o_x + t * 1024 + 128, xw[2 * t + 1]); }
      rb = ldg_rlx32(sc + o_xrb);
    }
    const uint32_t stg = sb + SM_B + p * 13824 + w * 2304;
    unsigned char* obase = (unsigned char*)P.out + ((128 * i + 32 * w + p) * 1152 + 144 * j);
    if (L == 1) {
      const float ul = 1.f + rs_lo, uh = 1.f + rs_hi, vl = -m_lo * rs_lo, vh = -m_hi * rs_hi;
#pragma unroll
      for (int t = 0; t < 9; t++) {
        xw[2 * t] = pack_bf16(fmaf(accw[4 * t], ul, vl), fmaf(accw[4 * t + 1], ul, vl));
        xw[2 * t + 1] = pack_bf16(fmaf(accw[4 * t + 2], uh, vh), fmaf(accw[4 * t + 3], uh, vh));
      }
      mbar_wait(sb + BAR_EMPTY + p * 8, 1);
      const uint32_t sa = stg + (lane & 15) * 144;
#pragma unroll
      for (int t = 0; t < 8; t += 2) stsm4(sa + (lane >> 4) * 16 + t * 16, xw[2 * t], xw[2 * t + 1], xw[2 * t + 2], xw[2 * t + 3]);
      stsm2(sa + 128, xw[16], xw[17]);
      __syncwarp();
      if (p == 0 || !OUT_LATE) store_rows(stg, obase, candrow, lane);
    }
    CSTAMP(8);
    lane = pin(lane);
    const unsigned char* cp = sc + (OFF(cand) + (j * 32 + lane) * (CAND_W * 4));
    if (p == 0) {
      if (L == 1 && candrow >= 0) {
        const Winner wn = poll_winner(cp, ldg_rlx128(cp), tg);
        if (lane < 9 && wn.ci != ip) *(uint4*)(obase + (candrow * 2304 + lane * 16)) = lds128(stg + candrow * 144 + lane * 16);
      }
    } else {
      const uint32_t gr = w * 144 + (lane & 7) + (lane >> 4) * 8, gm = sb + SM_G + ((lane >> 3) & 1) * 46080;
      const uint32_t ga = gm + gr * 64 + (((lane >> 1) & 3) << 4), gl = gm + 36864 + gr * 16;
#define GADDR(s, u) ((u) < 4 ? (ga ^ ((u) << 4)) + (s) * 1024 : gl + (s) * 256)
      uint32_t wf[NPRE][5][4];
      mbar_wait(sb + BAR_GU, 0);
#pragma unroll
      for (int s = 0; s < NPRE - 2; s++)
#pragma unroll
        for (int u = 0; u < 5; u++) ldsm4t(wf[s][u], GADDR(s, u));
      const uint4 c0 = ldg_rlx128(cp);
#pragma unroll
      for (int s = NPRE - 2; s < NPRE; s++)
#pragma unroll
        for (int u = 0; u < 5; u++) ldsm4t(wf[s][u], GADDR(s, u));
      flag_after(sc + o_cf, rb, 8 * T + 1, lane < 8 && L == 0);
      const Winner wn = poll_winner(cp, c0, tg);
      if (w == 0 && first_lane) sts128(sb + SM_WIN, asu(wn.r), asu(wn.m), asu(wn.rstd), (uint32_t)(wn.ci * 64 + wn.rr));
      CSTAMP(9);
      if (!OUT_LATE && L == 1 && candrow >= 0 && lane < 9 && wn.ci != ip) *(uint4*)(obase + (candrow * 2304 + lane * 16)) = lds128(stg + candrow * 144 + lane * 16);
      {
        uint32_t hb[18];
        const unsigned char* xc = sc + (OFF(xcand) + wn.ci * 1536 + q * 16);
        const int fp = min(cx.cta / 3, 23);
        uint4 u[7];
        int n = 0;
#pragma unroll 1
        while (true) {
          uint32_t d = 0;
#pragma unroll
          for (int e = 0; e < 7; e++) u[e] = ldg_rlx128(xc + (e < 6 ? w * 384 + e * 64 : fp * 64));
#pragma unroll
          for (int e = 0; e < 7; e++) d = orx(d, u[e].w, tg);
          if (__all_sync(0xffffffffu, d == 0)) break;
          if (++n > SPIN) TIMEOUT(__LINE__)
        }
        if (OUT_LATE == 3 && L == 1) store_rows(stg, obase, wn.ci == ip ? candrow : -1, lane);
#pragma unroll
        for (int e = 0; e < 6; e++) { hb[3 * e] = u[e].x; hb[3 * e + 1] = u[e].y; hb[3 * e + 2] = u[e].z; }
        if (w == 0) sts128(sb + SM_XW + q * 16, u[6].x, u[6].y, u[6].z, u[6].w);
        const float nb = -wn.m * wn.rstd;
#pragma unroll
        for (int b = 0; b < 18; b++) hb[b] = pack_bf16(fmaf(bf_lo(hb[b]), wn.rstd, nb), fmaf(bf_hi(hb[b]), wn.rstd, nb));
        CSTAMP(10);
        float d[5][4];
#pragma unroll
        for (int u = 0; u < 5; u++) d[u][0] = d[u][1] = d[u][2] = d[u][3] = 0.f;
#pragma unroll
        for (int s = 0; s < 9; s++) {
#pragma unroll
          for (int u = 0; u < 5; u++) {
            uint32_t* f = wf[s % NPRE][u];
            mma16(d[u], f[0], f[1], f[2], f[3], hb[2 * s], hb[2 * s + 1]);
            if (s + NPRE < 9) ldsm4t(f, GADDR(s + NPRE, u));
          }
        }
        if (q == 0) {
#pragma unroll
          for (int u = 0; u < 5; u++) sts64(sb + R_FPART + w * 320 + (u * 8 + g) * 8, asu(d[u][0]), asu(d[u][2]));
        }
        nb_arrive(NB_FFN, 224);
        CSTAMP(11);
      }
      if (OUT_LATE == 1 && L == 1) store_rows(stg, obase, wn.ci == ip ? candrow : -1, lane);
    }
  }
  STAMPIF(w == 0 && lane == 0, 40 + p * 20 + 12);
  PROF_DUMP();
#undef g
#undef q
#undef first_lane
}

__device__ __forceinline__ void load_wo_a(const Ctx& cx, const Params& P, const uint32_t T, const int L, const int p, const int lane) {
  const unsigned char* src = P.sc->obuf[cx.i * 2 + p];
#pragma unroll
  for (int c = 0; c < 9; c++) w_expect(sb + BAR_WFULL + (9 * p + c) * 8, 8192);
  mbar_wait(sb + BAR_HDONE + p * 8, L);
  wait_flags<32>(P.sc->cflag[cx.i * 2 + p], 8 * T + 2 * L, lane);
  fence_async_glob();
  STAMP(100 + L * 2 + p);
#pragma unroll
  for (int c = 0; c < 9; c++) {
    const int e = 9 * p + c, s = e % 6;
    if (e == 3) mbar_wait(sb + BAR_HDONE + 8, L);
    if (e >= 6) mbar_wait(sb + BAR_AEMPTY + s * 8, (L ^ (e / 6) ^ 1) & 1);
    w_bulk(sb + SM_A + (2 * (s % 3) + s / 3) * 8192, src + c * 8192, 8192, sb + BAR_WFULL + e * 8);
    PSTAMP(48 + L * 36 + 18 + e);
  }
}

__device__ __forceinline__ void finalize_row(const Params& P, const Winner& wn, const uint32_t T, const int L, const int grp, const int a, const int lane) {
  const unsigned char* yp = (const unsigned char*)P.sc->ypart[grp] + (a * 32 + lane) * 16;
  const uint32_t par = L ^ 1;
  uint4 u0 = ldg_rlx128(yp), u1 = ldg_rlx128(yp + 1536), u2 = make_uint4(par, 0, 0, 0);
  if (a < 2) rld128(u2, yp + 3072);
  const int col = lane & 7;
  const uint32_t xw = lds32(sb + SM_XW + (col >> 1) * 16 + (grp % 3) * 4);
  const float xsel = (col & 1) ? bf_hi(xw) : bf_lo(xw);
  const float sg = rbf(rcp(1.f + ex2(-1.4426950408889634f * rbf(wn.r))));
  const float h = rbf((xsel - wn.m) * wn.rstd);
  unsigned char* dst = L == 0 ? (unsigned char*)P.sc->xsel + (((lane >> 3) & 1) * 576 + grp * 8 + col) * 4
                              : (unsigned char*)P.out + ((128 * (wn.ci >> 1) + 2 * wn.rr + (wn.ci & 1)) * 576 + grp * 8 + col) * 2;
  int n = 0;
#pragma unroll 1
  while (__any_sync(0xffffffffu, orx(orx(orx(0, u0.x, par), u1.x, par), u2.x, par) & 1)) {
    rld128(u0, yp); rld128(u1, yp + 1536);
    if (a < 2) rld128(u2, yp + 3072);
    if (++n > SPIN) TIMEOUT(__LINE__)
  }
  const float s0 = asf(u0.x) + asf(u1.x) + asf(u2.x), s1 = asf(u0.y) + asf(u1.y) + asf(u2.y);
  const float s2 = asf(u0.z) + asf(u1.z) + asf(u2.z), s3 = asf(u0.w) + asf(u1.w) + asf(u2.w);
  const float k0 = self(lane & 2, s2, s0) + shx(self(lane & 2, s0, s2), 2), k1 = self(lane & 2, s3, s1) + shx(self(lane & 2, s1, s3), 2);
  float k = self(lane & 4, k1, k0) + shx(self(lane & 4, k0, k1), 4);
  k += shx(k, 8); k += shx(k, 16);
  if (lane < 8) stsf(sb + SM_YRED + ((lane & 1) * 4 + (lane & 2) + (lane >> 2)) * 16 + a * 4, k);
  nb_sync(NB_AUX, 96);
  if (a == 0) {
    const uint4 yy = lds128(sb + SM_YRED + col * 16);
    const float xn = rbf(xsel + rbf(h + rbf(rbf(asf(yy.x) + asf(yy.y) + asf(yy.z)) * sg)));
    if (L == 0) { if (lane < 16) stg32(dst, ftag(lane < 8 ? xn : xn - xsel, T & 1)); }
    else if (lane < 8) *(unsigned short*)dst = (unsigned short)(asu(xn) >> 16);
  }
}

__device__ __forceinline__ void aux_role(const Ctx& cx, const Params& P, const int a, const int lane_) {
  int lane = lane_;
#define t (a * 32 + lane)
#define g (lane >> 2)
#define q (lane & 3)
  const int i = cx.i, j = cx.j, cta = cx.cta;
  unsigned char* const sc = (unsigned char*)P.sc;
  const int rk = 36 * i + 12 * a;
  const uint32_t o_bf = OFF(bflag) + (j * 48 + i * 3 + a) * 32 + (lane & 7) * 4;
  uint32_t T;
  {
    const int k0 = lane & 7, tt = min(lane >> 3, 2), col = (9 * j + tt) * 16;
    const unsigned char* src = (const unsigned char*)P.wqkv + ((i * 8 + k0) * 3456 + a * 1152 + col);
    const Unit b0 = unit_load(src), b1 = unit_load(src + 128 * 3456);
    T = ldg_rlx32(sc + o_bf);
    nb_arrive(NB_ORD, 352);
    STAMPIF(1, 96);
    const uint32_t d2 = tt == 2 ? (22 - 7 * a) * 512 : 3072;
    const uint32_t o = OFF(wq) + (j * 18 + (i >> 2)) * 13824 + ((i & 3) * 8 + k0) * 16 + (a * 8 + tt) * 512;
    const uint32_t r0 = unit_store(sc, b0, lane, o, o + 1536, o + d2);
    STAMPIF(1, 80);
    const uint32_t r1 = unit_store(sc, b1, lane, o + 55296, o + 55296 + 1536, o + 55296 + d2);
    T = __shfl_sync(0xffffffffu, (T >> 3) + 1, 0);
    flag_after(sc + o_bf, r0 ^ r1, 8 * T + 1, lane < 8);
    STAMPIF(1, 98);
    const Unit b2 = unit_load(src + 256 * 3456), b3 = unit_load(src + 384 * 3456);
    const bool qkv = k0 < 4;
    const int q0 = rk + k0 - 4, q1 = rk + 4 + k0;
    const Unit u0 = unit_load(qkv ? (const unsigned char*)P.wqkv + ((512 + 4 * i + k0) * 3456 + a * 1152 + col) : (const unsigned char*)P.wo + (q0 * 1152 + col));
    const Unit u1 = unit_load((const unsigned char*)P.wo + (q1 * 1152 + col));
    const uint32_t r2 = unit_store(sc, b2, lane, o + 2 * 55296, o + 2 * 55296 + 1536, o + 2 * 55296 + d2);
    const uint32_t r3 = unit_store(sc, b3, lane, o + 3 * 55296, o + 3 * 55296 + 1536, o + 3 * 55296 + d2);
    float cs[3][8];
#pragma unroll
    for (int m = 0; m < 3; m++) {
      const uint32_t* w0 = &b0.v[m].x; const uint32_t* w1 = &b1.v[m].x; const uint32_t* w2 = &b2.v[m].x; const uint32_t* w3 = &b3.v[m].x; const uint32_t* w4 = &u0.v[m].x;
#pragma unroll
      for (int e = 0; e < 4; e++) {
        const uint32_t z = qkv ? w4[e] : 0u;
        cs[m][2 * e] = (bf_lo(w0[e]) + bf_lo(w1[e])) + (bf_lo(w2[e]) + bf_lo(w3[e])) + bf_lo(z);
        cs[m][2 * e + 1] = (bf_hi(w0[e]) + bf_hi(w1[e])) + (bf_hi(w2[e]) + bf_hi(w3[e])) + bf_hi(z);
      }
    }
    flag_after(sc + o_bf, r2 ^ r3, 8 * T + 3, lane < 8);
    STAMPIF(1, 82);
#pragma unroll
    for (int st = 4; st >= 1; st >>= 1) {
      const bool up = lane & st;
#pragma unroll
      for (int m = 0; m < 3; m++)
#pragma unroll
        for (int e = 0; e < st; e++) cs[m][e] = (up ? cs[m][e + st] : cs[m][e]) + shx(up ? cs[m][e] : cs[m][e + st], st);
    }
    {
      const uint32_t oz = OFF(zpart) + j * 13824 + i * 864 + (a * 8 + tt) * 32 + k0 * 4;
      stg32(sc + oz, ftag(cs[0][0], 1)); stg32(sc + (oz + 96), ftag(cs[1][0], 1)); stg32(sc + (oz + (d2 >> 4)), ftag(cs[2][0], 1));
    }
    STAMPIF(1, 81);
    nb_sync(NB_GO, 128);
    mbar_wait(sb + BAR_FULL + LATE_WAIT * 8, 0);
    const uint32_t ow = OFF(wo) + j * 82944 + tt * 256;
    const uint32_t oa = qkv ? OFF(wq) + (j * 18 + 16 + (i >> 3)) * 13824 + (4 * (i & 7) + k0) * 16 + (a * 8 + tt) * 512 : ow + (q0 >> 4) * 2304 + (q0 & 15) * 16;
    const uint32_t ob = ow + (q1 >> 4) * 2304 + (q1 & 15) * 16;
    const uint32_t ra = unit_store(sc, u0, lane, oa, oa + (qkv ? 1536 : 768), oa + (qkv ? d2 : 1536));
    const uint32_t rb = unit_store(sc, u1, lane, ob, ob + 768, ob + 1536);
    STAMPIF(1, 113);
#pragma unroll
    for (int S = 0; S < 3; S++) stg64(sc + (OFF(ypart) + (a * 24 + g) * 4096 + cta * 32 + q * 8) + S * 32768, 0u, 0u);
    if (cta < 72 && t < 16) stg32(sc + (OFF(xsel) + (lane >> 3) * 2304 + cta * 32 + (lane & 7) * 4), (T & 1) ^ 1);
    uint4 sv, sw;
    int n = 0;
#pragma unroll 1
    while (true) {
      sv = ldg_rlx128(sc + (OFF(st0) + i * 2048 + t * 16)); sw = ldg_rlx128(sc + (OFF(st0) + i * 2048 + 1536 + lane * 16));
      if (__all_sync(0xffffffffu, ((sv.z ^ T) | (sw.z ^ T)) == 0)) break;
      if (++n > SPIN) TIMEOUT(__LINE__)
    }
    flag_after(sc + o_bf, ra ^ rb, 8 * T + 4, lane < 8);
    sts64(sb + SM_R + t * 8, sv.x, sv.y);
    sts64(sb + SM_R + 768 + lane * 8, sw.x, sw.y);
    STAMPIF(1, 94);
  }
  Winner wn;
  bool owner = false;
  uint32_t wd[5][3][8];
  auto load_wd = [&](uint32_t (*d)[8], const unsigned char* sk) {
#pragma unroll
    for (int S = 0; S < 3; S++) {
      const uint4 v0 = ldg_nc128(sk + S * 128), v1 = ldg_nc128(sk + S * 128 + 1152);
      d[S][0] = v0.x; d[S][1] = v1.x; d[S][2] = v0.y; d[S][3] = v1.y; d[S][4] = v0.z; d[S][5] = v1.z; d[S][6] = v0.w; d[S][7] = v1.w;
    }
  };
  auto perm_wd = [&](uint32_t (*d)[8]) {
#pragma unroll
    for (int S = 0; S < 3; S++)
#pragma unroll
      for (int u = 0; u < 4; u++) {
        const uint32_t x = d[S][2 * u], y = d[S][2 * u + 1];
        asm volatile("prmt.b32 %0, %2, %3, 0x5410;\nprmt.b32 %1, %2, %3, 0x7632;" : "=&r"(d[S][2 * u]), "=r"(d[S][2 * u + 1]) : "r"(x), "r"(y));
      }
  };
#pragma unroll
  for (int kb = 0; kb < 3; kb++)
#pragma unroll
    for (int S = 0; S < 3; S++)
#pragma unroll
      for (int e = 0; e < 8; e++) wd[kb][S][e] = 0u;
#pragma unroll 1
  for (int L = 0; L < 2; L++) {
    lane = pin(lane);
    const uint32_t o_part = OFF(zpart) + j * 13824, par = L ^ 1;
    const int pk = a * 18 + min(lane, 17);
    if (L == 1) {
      if (cta < 72) finalize_row(P, wn, T, 0, cta, a, lane);
      const int gi = min(lane, 26);
      uint4 wv[12];
      {
        const int pc = gi < 24 ? gi >> 3 : gi - 24, tc = gi < 24 ? gi & 7 : 8;
        const unsigned char* se = (const unsigned char*)P.wqkv + (rk * 3456 + pc * 1152 + (9 * j + tc) * 16);
#pragma unroll
        for (int r = 0; r < 12; r++) wv[r] = ldg_nc128(se + r * 3456);
      }
      STAMPIF(1, 85);
      nb_sync(NB_AUX, 96);
      uint4 xq[3];
      {
        const unsigned char* dp = sc + (OFF(xsel) + 2304 + rk * 4);
        int n = 0;
#pragma unroll 1
        while (true) {
#pragma unroll
          for (int e = 0; e < 3; e++) xq[e] = ldg_rlx128(dp + e * 16);
          if (__all_sync(0xffffffffu, (orx(orx(orx(0, xq[0].x, T), xq[1].x, T), xq[2].x, T) & 1) == 0)) break;
          if (++n > SPIN) TIMEOUT(__LINE__)
        }
        if (t == 0) {
          sts32(sb + SM_SEL, owner ? (wn.ci & 1) * 64 + wn.rr : 0x7FFFFFFFu);
          if (wn.ci != 2 * i) mbar_arrive(sb + BAR_FIX);
          if (wn.ci != 2 * i + 1) mbar_arrive(sb + BAR_FIX + 8);
        }
        STAMPIF(1, 88);
      }
      float s[8];
#pragma unroll
      for (int e = 0; e < 8; e++) s[e] = 0.f;
#pragma unroll
      for (int r = 0; r < 12; r++) {
        const float x = asf((&xq[0].x)[r]);
        s[0] = fmaf(x, bf_lo(wv[r].x), s[0]); s[1] = fmaf(x, bf_hi(wv[r].x), s[1]);
        s[2] = fmaf(x, bf_lo(wv[r].y), s[2]); s[3] = fmaf(x, bf_hi(wv[r].y), s[3]);
        s[4] = fmaf(x, bf_lo(wv[r].z), s[4]); s[5] = fmaf(x, bf_hi(wv[r].z), s[5]);
        s[6] = fmaf(x, bf_lo(wv[r].w), s[6]); s[7] = fmaf(x, bf_hi(wv[r].w), s[7]);
      }
      sts128(sb + SM_R + a * 864 + gi * 32, asu(s[0]), asu(s[1]), asu(s[2]), asu(s[3]));
      sts128(sb + SM_R + a * 864 + gi * 32 + 16, asu(s[4]), asu(s[5]), asu(s[6]), asu(s[7]));
      nb_sync(NB_AUX, 96);
      const uint32_t ad = sb + SM_R + pk * 16;
      const uint4 u0 = lds128(ad), u1 = lds128(ad + 864), u2 = lds128(ad + 1728);
      stg128(sc + (o_part + i * 864 + pk * 16), ftag(asf(u0.x) + asf(u1.x) + asf(u2.x), par), ftag(asf(u0.y) + asf(u1.y) + asf(u2.y), par),
             ftag(asf(u0.z) + asf(u1.z) + asf(u2.z), par), ftag(asf(u0.w) + asf(u1.w) + asf(u2.w), par));
      STAMPIF(1, 86);
    }
    if (owner) {
      uint2 u[3];
      int n = 0;
#pragma unroll 1
      while (true) {
#pragma unroll
        for (int m = 0; m < 3; m++) u[m] = ldg_rlx64(sc + (OFF(xsel) + t * 8) + m * 768);
        if (__all_sync(0xffffffffu, (orx(orx(orx(0, u[0].x, T), u[1].x, T), u[2].x, T) & 1) == 0)) break;
        if (++n > SPIN) TIMEOUT(__LINE__)
      }
      STAMPIF(1, 109);
      float s1 = 0.f, s2 = 0.f;
#pragma unroll
      for (int m = 0; m < 3; m++) {
        const float x0 = asf(u[m].x), x1 = asf(u[m].y);
        s1 += x0 + x1; s2 = fmaf(x0, x0, fmaf(x1, x1, s2));
        const unsigned cc = 96 * m + t - 36 * j;
        if (cc < 36u) sts32(sb + SM_X2S + cc * 4, __byte_perm(u[m].x, u[m].y, 0x7632));
      }
      wn.m = s1; wn.rstd = s2;
    }
    if (L == 0 || owner) {
      uint4 u[16];
      int n = 0;
#pragma unroll 1
      while (true) {
        uint32_t d0 = 0, d1 = 0;
#pragma unroll
        for (int e = 0; e < 16; e++) u[e] = ldg_rlx128(sc + (o_part + pk * 16) + e * 864);
        if (L == 1 && n == 0) {
#pragma unroll
          for (int s = 1; s < 32; s <<= 1) { wn.m += shx(wn.m, s); wn.rstd += shx(wn.rstd, s); }
          if (lane == 0) sts64(sb + SM_RED2 + a * 8, asu(wn.m), asu(wn.rstd));
        }
#pragma unroll
        for (int e = 0; e < 8; e++) { d0 = orx(d0, u[e].x, par); d1 = orx(d1, u[8 + e].x, par); }
        if (__all_sync(0xffffffffu, ((d0 | d1) & 1) == 0)) break;
        if (++n > SPIN) TIMEOUT(__LINE__)
      }
      STAMPIF(1, 118 + L);
      float4 z = make_float4(0.f, 0.f, 0.f, 0.f);
#pragma unroll
      for (int e = 0; e < 16; e++) { z.x += asf(u[e].x); z.y += asf(u[e].y); z.z += asf(u[e].z); z.w += asf(u[e].w); }
      const uint32_t h0 = pack_bf16(z.x, z.y), h1 = pack_bf16(z.z, z.w);
      const uint32_t l0 = pack_bf16(z.x - bf_lo(h0), z.y - bf_hi(h0)), l1 = pack_bf16(z.z - bf_lo(h1), z.w - bf_hi(h1));
      const uint32_t ad = sb + SM_BEXT + (pk >> 1) * 128 + (pk & 1) * 8;
      if (L == 0) {
        sts64(ad, h0, h1);
#pragma unroll
        for (int r = 3; r < 8; r++) sts64(ad + r * 16, 0u, 0u);
      }
      sts64(ad + 16 + L * 48, h0, h1); sts64(ad + 32 + L * 48, l0, l1);
      fence_async_smem();
      nb_sync(NB_AUX, 96);
      if (t == 0) {
        if (L == 1) {
          const uint4 ra = lds128(sb + SM_RED2);
          const uint2 rb = lds64(sb + SM_RED2 + 16);
          const float m2 = (asf(ra.x) + asf(ra.z) + asf(rb.x)) * (1.f / 576.f);
          const float rs2 = rsq(fmaxf((asf(ra.y) + asf(ra.w) + asf(rb.y)) * (1.f / 576.f) - m2 * m2, 0.f) + EPS);
          sts64(sb + SM_SEL + 8, asu(m2), asu(rs2));
          mbar_arrive(sb + BAR_FIX + (wn.ci & 1) * 8);
        } else {
          mbar_arrive(sb + BAR_FIX); mbar_arrive(sb + BAR_FIX + 8);
        }
        STAMP(83 + L * 4);
      }
    }
    lane = pin(lane);
    const unsigned char* const wsrc = (const unsigned char*)P.wd + ((ffn_c32(cta) + 2 * q) * 1152 + a * 384 + g * 16);
    if (L == 0) {
#pragma unroll
      for (int kb = 0; kb < 3; kb++) { load_wd(wd[kb], wsrc + (kb * 9216 + (kb ? pin0(wd[kb - 1][2][7]) : 0u))); perm_wd(wd[kb]); }
    }
    load_wd(wd[3], wsrc + 3 * 9216);
    load_wd(wd[4], wsrc + ((cta & 1) ? (ffn_c8(cta) - ffn_c32(cta)) * 1152 : 24 * 1152));
    perm_wd(wd[3]); perm_wd(wd[4]);
    const uint32_t o_y = pin(OFF(ypart) + (a * 24 + g) * 4096 + cta * 32 + q * 8 + pin0(wd[4][2][7]));
    STAMPIF(1, 89 + L);
    if (a == 2) load_wo_a(cx, P, T, L, 1, lane);
    nb_sync(NB_FFN, 224);
    {
      const uint32_t ad = sb + R_FPART + min(lane, 19) * 16;
      const uint4 u0 = lds128(ad), u1 = lds128(ad + 320), u2 = lds128(ad + 640), u3 = lds128(ad + 960);
      const uint4 wv = lds128(sb + SM_WIN);
      const float g0 = rbf((asf(u0.x) + asf(u1.x)) + (asf(u2.x) + asf(u3.x))), g1 = rbf((asf(u0.z) + asf(u1.z)) + (asf(u2.z) + asf(u3.z)));
      const float v0 = rbf((asf(u0.y) + asf(u1.y)) + (asf(u2.y) + asf(u3.y))), v1 = rbf((asf(u0.w) + asf(u1.w)) + (asf(u2.w) + asf(u3.w)));
      const float s0 = rbf(g0 * rcp(1.f + ex2(-1.4426950408889634f * g0))), s1 = rbf(g1 * rcp(1.f + ex2(-1.4426950408889634f * g1)));
      const uint32_t act = lane < 16 + (cta & 1) * 4 ? pack_bf16(s0 * v0, s1 * v1) : 0u;
      uint32_t b[5];
#pragma unroll
      for (int kb = 0; kb < 5; kb++) b[kb] = __shfl_sync(0xffffffffu, act, 4 * kb + q);
#pragma unroll
      for (int S = 0; S < 3; S++) {
        float y[4][4];
#pragma unroll
        for (int u = 0; u < 4; u++) mma8z(y[u], wd[2][S][2 * u], wd[2][S][2 * u + 1], b[2]);
#pragma unroll
        for (int u = 0; u < 4; u++) mma16(y[u], wd[0][S][2 * u], wd[0][S][2 * u + 1], wd[1][S][2 * u], wd[1][S][2 * u + 1], b[0], b[1]);
#pragma unroll
        for (int u = 0; u < 4; u++) mma16(y[u], wd[3][S][2 * u], wd[3][S][2 * u + 1], wd[4][S][2 * u], wd[4][S][2 * u + 1], b[3], b[4]);
        const float y0 = self(lane & 2, self(lane & 1, y[3][0], y[2][0]), self(lane & 1, y[1][0], y[0][0]));
        const float y1 = self(lane & 2, self(lane & 1, y[3][2], y[2][2]), self(lane & 1, y[1][2], y[0][2]));
        stg64(sc + o_y + S * 32768, ftag(y0, par), ftag(y1, par));
      }
      if (L == 0) nb_arrive(NB_FFN2, 224);
      wn.r = asf(wv.x); wn.m = asf(wv.y); wn.rstd = asf(wv.z); wn.ci = wv.w >> 6; wn.rr = wv.w & 63;
    }
    STAMPIF(1, 84 + L * 8);
    owner = (wn.ci >> 1) == i;
  }
  if (cta < 72) finalize_row(P, wn, T, 1, cta, a, lane);
  STAMPIF(1, 93);
  PROF_END();
#undef t
#undef g
#undef q
}

__device__ __forceinline__ void producer_role(const Ctx& cx, const Params& P, const int lane) {
  const int i = cx.i, j = cx.j;
  if (elect_one()) asm volatile("prefetch.tensormap [%0];" ::"l"(&P.mx) : "memory");
  const uint32_t T = __shfl_sync(0xffffffffu, (ldg_rlx32(P.sc->cflag[i * 2][j * 4]) >> 3) + 1, 0);
  const unsigned char* const wq = P.sc->wq[j][0];
  nb_sync(NB_START, 288);
#pragma unroll
  for (int s = 0; s < 2 * NA0; s++) w_tma3d(sb + SM_A + s * 8192, &P.mx, (s >> 1) * 64, s & 1, i * 64, sb + BAR_FULL + (s >> 1) * 16);
#pragma unroll
  for (int h = 0; h < 6; h++) w_expect(sb + BAR_FULL + h * 8, h & 1 ? 13824 : 13824 + 16384);
  STAMP(97);
  wait_flags<48>(P.sc->bflag[j], 8 * T + 1, lane);
  fence_async_glob();
  STAMP(120);
#pragma unroll
  for (int h = 0; h < 6; h++) {
    w_bulk(sb + SM_B + h * 13824, wq + h * 13824, 13824, sb + BAR_FULL + h * 8);
    if (!(h & 1) && h >= 2 * NA0) {
      w_tma3d(sb + SM_A + h * 8192, &P.mx, h * 32, 0, i * 64, sb + BAR_FULL + h * 8);
      w_tma3d(sb + SM_A + h * 8192 + 8192, &P.mx, h * 32, 1, i * 64, sb + BAR_FULL + h * 8);
    }
  }
  PSTAMP(0);
  nb_arrive(NB_GO, 128);
  mbar_wait(sb + BAR_FULL + PF_WAIT * 8, 0);
  w_prefetch((const unsigned char*)P.wd + cx.cta * 41472, 10368);
  const unsigned char* const xb = P.sc->xbuf[i * 2];
  const unsigned char* const fp = (const unsigned char*)P.sc->bflag[j] + lane * 32;
  uint32_t f0 = 0, f1 = 0;
#pragma unroll 1
  for (int L = 0; L < 2; L++) {
    if (L == 1) {
#pragma unroll 1
      for (int p = 0; p < 2; p++) {
        mbar_wait(sb + BAR_AEMPTY + (2 + 3 * p) * 8, 0);
        wait_flags<32>(P.sc->cflag[i * 2 + p], 8 * T + 1, lane);
        fence_async_glob();
        STAMP(104 + p);
#pragma unroll
        for (int a = 0; a < 3; a++) {
          const int s = 2 * a + p;
          w_expect(sb + BAR_AFULL + s * 8, 8192);
          w_bulk(sb + SM_A + s * 8192, xb + (p * 73728 + a * 8192), 8192, sb + BAR_AFULL + s * 8);
          PSTAMP(48 + 36 + 3 * p + a);
        }
      }
    }
#pragma unroll 1
    for (int a = 3; a < 15; a++) {
      if (a == 12) {
        load_wo_a(cx, P, T, L, 0, lane);
        if (L == 1) break;
      }
      const int r = (a * 11) >> 5, s = a - 3 * r;
      const uint32_t fb = sb + BAR_FULL + s * 16, da = sb + SM_A + s * 16384, db = sb + SM_B + s * 27648;
      const unsigned char* bsrc = wq + (a < 9 ? a : a < 12 ? 72 - 6 * j + s : s) * 27648;
      const unsigned char* asrc = xb + a * 8192;
      const int kc = (a < 9 ? a : j + a - 10) * 64;
      const int amode = a == 9 || a > 11 ? 0 : L == 0 ? 1 : a < 9 ? 2 : 0;
      mbar_wait(sb + BAR_EMPTY + s * 16, (r & 1) ^ 1);
      if (L == 0) {
        if (a == 4 || a == 8) {
          const uint32_t need = 8 * T + (a == 4 ? 3 : 4);
          if (__any_sync(0xffffffffu, (int)((f0 - need) | (f1 - need)) < 0)) wait_flags<48>(P.sc->bflag[j], need, lane);
          fence_async_glob();
          STAMP(120 + (a >> 1));
        }
        if (a == 3 || a == 7) { f0 = ldg_rlx32(fp); f1 = ldg_rlx32(fp + (lane < 16 ? 1024 : 0)); }
      }
      w_bulk(db, bsrc, 13824, fb);
      w_expect(fb, amode ? 13824 + 16384 : 13824);
      mbar_wait(sb + BAR_EMPTY + s * 16 + 8, (r & 1) ^ 1);
      if (amode == 1) {
        w_tma3d(da, &P.mx, kc, 0, i * 64, fb);
        w_tma3d(da + 8192, &P.mx, kc, 1, i * 64, fb);
      } else if (amode == 2) {
        w_bulk(da, asrc, 8192, fb);
        w_bulk(da + 8192, asrc + 73728, 8192, fb);
      }
      w_bulk(db + 13824, bsrc + 13824, 13824, fb + 8);
      w_expect(fb + 8, 13824);
      PSTAMP(a < 12 ? L * 24 + a : 12 + a);
      if (L == 0) {
        if (a < 12) w_prefetch(a < 6 ? (const unsigned char*)P.wd + (cx.cta * 4 + a - 2) * 10368 : (const unsigned char*)P.wg + ((a - 6) * 128 + cx.cta) * 6912, a < 6 ? 10368 : 6912);
        if (a == 3) w_expect(sb + BAR_GU, 12 * (6144 + (cx.cta & 1) * 1536));
        if (a >= 9) load_gu(P, cx.cta, 0, a - 9, sb + BAR_GU);
        if (a >= 3 && a < 13 && ((a & 1) || a == 12)) load_gu(P, cx.cta, 1, (a - 2) >> 1, sb + BAR_GU);
      }
    }
  }
}

template <bool BY_SMID>
__global__ void __launch_bounds__(384, 1) fused_kernel(const __grid_constant__ Params P) {
  extern __shared__ __align__(1024) unsigned char smem[];
  Ctx cx;
  STAMPIF(threadIdx.x == 64, 125);
  unsigned id;
  if (BY_SMID) asm volatile("mov.u32 %0, %%smid;" : "=r"(id)); else id = blockIdx.x;
  const int work = __shfl_sync(0xffffffffu, (int)P.work[min(id, 131u)], 0);
  const int warp = __shfl_sync(0xffffffffu, (int)(threadIdx.x >> 5), 0), lane = threadIdx.x & 31;
  if (work < 0) {
    if (warp == 0) {
      const int sp = -1 - work;
      if (lane == 0) { mbar_init(sb, 1); fence_async_smem(); }
      __syncwarp();
      __nanosleep(SPARE_DELAY);
#pragma unroll 1
      for (int k = 32 + sp; k < 72; k += 4) w_prefetch((const unsigned char*)P.wqkv + k * 27648, 27648);
#pragma unroll 1
      for (int k = sp; k < 24; k += 4) w_prefetch((const unsigned char*)P.wo + k * 27648, 27648);
#pragma unroll 1
      for (int k = sp; k < X_NU; k += 4) w_prefetch((const unsigned char*)P.wu + k * 27648, 27648);
      w_expect(sb, 16);
      w_bulk(sb + 128, P.wr, 16, sb);
      mbar_wait(sb, 0);
    }
    return;
  }
  cx.cta = work; cx.i = work >> 3; cx.j = work & 7;
  STAMPIF(threadIdx.x == 32, 95);
  if (warp < 8) {
    if (warp == 0) {
      if (elect_one()) {
        if ((uint32_t)__cvta_generic_to_shared(smem) != sb) __trap();
#pragma unroll
        for (int b = 0; b < 48; b++) mbar_init(sb + SM_BAR + b * 8, b < 34 ? 1 : b < 42 ? 4 : 8);
        fence_async_smem();
      }
      __syncwarp();
    }
    consumer_role(cx, P, smem, warp >> 2, warp & 3, lane);
  } else if (warp < 11) {
    aux_role(cx, P, warp - 8, lane);
  } else {
    producer_role(cx, P, lane);
  }
}

int work_of_smid(int smid) {
  const int t = smid >> 1;
  if (t == 60 || t == 61) return -1 - ((t - 60) * 2 + (smid & 1));
  const int gpc = t < 32 ? t & 7 : t < 60 ? 1 + (t - 32) % 7 : 0;
  const int x = 2 * (t < 32 ? t >> 3 : t < 60 ? 4 + (t - 32) / 7 : t - 58) + (smid & 1);
  const int blk[8] = {6, 0, 2, 3, 4, 7, 5, 1}, b = blk[gpc];
  return ((b >> 1) * 4 + (x & 1) + (x >> 3) * 2) * 8 + (b & 1) * 4 + ((x >> 1) & 3);
}

typedef CUresult (*EncodeFn)(CUtensorMap*, CUtensorMapDataType, cuuint32_t, void*, const cuuint64_t*, const cuuint64_t*,
                             const cuuint32_t*, const cuuint32_t*, CUtensorMapInterleave, CUtensorMapSwizzle,
                             CUtensorMapL2promotion, CUtensorMapFloatOOBfill);

void make_map(EncodeFn enc, CUtensorMap* m, const void* base, int rank, const cuuint64_t* dims, const cuuint64_t* strides,
              const cuuint32_t* box, CUtensorMapSwizzle sw, CUtensorMapL2promotion promo = CU_TENSOR_MAP_L2_PROMOTION_L2_128B) {
  const cuuint32_t es[3] = {1, 1, 1};
  enc(m, CU_TENSOR_MAP_DATA_TYPE_BFLOAT16, rank, const_cast<void*>(base), dims, strides, box, es, CU_TENSOR_MAP_INTERLEAVE_NONE, sw,
      promo, CU_TENSOR_MAP_FLOAT_OOB_FILL_NONE);
}

}

extern "C" void kernel_launch(void* const* d_in, const int* in_sizes, int n_in, void* d_out, int out_size) {
  (void)in_sizes; (void)n_in; (void)out_size;
  static EncodeFn enc = nullptr;
  static int nsm = 0;
  static void* scr = nullptr;
  if (!enc) {
    void* f = nullptr;
    cudaDriverEntryPointQueryResult qr;
    cudaGetDriverEntryPoint("cuTensorMapEncodeTiled", &f, cudaEnableDefault, &qr);
    enc = (EncodeFn)f;
    cudaGetSymbolAddress(&scr, g_scratch);
    int dev = 0;
    cudaGetDevice(&dev);
    cudaDeviceGetAttribute(&nsm, cudaDevAttrMultiProcessorCount, dev);
    cudaFuncSetAttribute(fused_kernel<true>, cudaFuncAttributeMaxDynamicSharedMemorySize, SM_TOTAL);
    cudaFuncSetAttribute(fused_kernel<false>, cudaFuncAttributeMaxDynamicSharedMemorySize, SM_TOTAL);
  }
  Params P;
  P.x = (const __nv_bfloat16*)d_in[0];
  P.wqkv = (const __nv_bfloat16*)d_in[1];
  P.wo = (const __nv_bfloat16*)d_in[2];
  P.wr = (const __nv_bfloat16*)d_in[4];
  P.wg = (const __nv_bfloat16*)d_in[5];
  P.wu = (const __nv_bfloat16*)d_in[6];
  P.wd = (const __nv_bfloat16*)d_in[7];
  P.out = (__nv_bfloat16*)d_out;
  P.sc = (Scratch*)scr;
  for (int k = 0; k < 136; k++) P.work[k] = (signed char)(nsm == 132 ? (k < 132 ? work_of_smid(k) : -1) : (k < 128 ? k : k < 132 ? 127 - k : -1));
  {
    const cuuint64_t dims[3] = {576, 2, 1024}, str[2] = {1152, 2304};
    const cuuint32_t box[3] = {64, 1, 64};
    make_map(enc, &P.mx, P.x, 3, dims, str, box, CU_TENSOR_MAP_SWIZZLE_128B);
  }
  {
    const cuuint64_t dims[2] = {4608, 576}, str[1] = {9216};
    const cuuint32_t box[2] = {32, 96}, box8[2] = {8, 96};
    make_map(enc, &P.mg, d_in[5], 2, dims, str, box, CU_TENSOR_MAP_SWIZZLE_64B);
    make_map(enc, &P.mu, d_in[6], 2, dims, str, box, CU_TENSOR_MAP_SWIZZLE_64B);
    make_map(enc, &P.mg8, d_in[5], 2, dims, str, box8, CU_TENSOR_MAP_SWIZZLE_NONE);
    make_map(enc, &P.mu8, d_in[6], 2, dims, str, box8, CU_TENSOR_MAP_SWIZZLE_NONE);
  }
  if (nsm == 132) fused_kernel<true><<<132, 384, SM_TOTAL>>>(P);
  else fused_kernel<false><<<132, 384, SM_TOTAL>>>(P);
}
```

```cpp
#include <cuda_runtime.h>
#include <cuda.h>
#include <cuda_bf16.h>
#include <stdint.h>
#include <stddef.h>

namespace {

constexpr int NPRE = 5;
#define X_NU 192
#define CAND_W 8
#define HALO_V 0
#define X_DELAY 200
#define X_STEP 100
#define HOLD_C 13
#define NA0 3
#define B2_AT 0
#define LATE_WAIT 3
#define OUT_LATE 0
#define U_AT 0xFFFF75
#define G_AT 0xEDCBA9
#define PG_0 6
#define WD_PF 3
#define U_WIN 11
#define G_WIN 11
#define G_GAP 300
#define U_GAP 400
#define PF_WAIT 0
#define POLL_GAP 100
#define SPARE_DELAY 400
constexpr float EPS = 1e-5f;
constexpr int SPIN = 1 << 22;
#define TIMEOUT(line) __trap();

struct __align__(128) Scratch {
  uint32_t bflag[8][48][8];
  uint32_t cflag[32][32][8];
  uint32_t halo[32][8][672];
  uint32_t stats[32][4][8][64];
  uint32_t cand[8][32][CAND_W];
  uint32_t xcand[32][8][48];
  uint32_t ypart[72][128][8];
  uint32_t zpart[8][16][216];
  uint32_t st0[2048][4];
  uint32_t xsel[2][576];
  unsigned char wq[8][9][27648];
  unsigned char wo[8][3][27648];
  unsigned char obuf[32][73728];
  unsigned char xbuf[32][73728];
};
__device__ Scratch g_scratch;
#define OFF(f) ((uint32_t)offsetof(Scratch, f))
#define STAMPD(v, k) do {} while (0)
#define STAMPIF(c, k) do {} while (0)
#define STAMP(k) do {} while (0)

constexpr uint32_t sb = 1024;
constexpr uint32_t SM_A = 0;
constexpr uint32_t SM_B = 49152;
constexpr uint32_t SM_G = 132096;
constexpr uint32_t SM_BEXT = 224256;

constexpr uint32_t SM_WIN = 227712;
constexpr uint32_t SM_XW = 228320;
constexpr uint32_t SM_YRED = 228448;
constexpr uint32_t SM_X2S = 228576;
constexpr uint32_t SM_RED2 = 228736;
constexpr uint32_t SM_WR = 228864;
constexpr uint32_t SM_R = 229168;
constexpr uint32_t SM_BEST = 231760;
constexpr uint32_t SM_SEL = 231824;
constexpr uint32_t SM_BAR = 231840;
constexpr uint32_t SM_TOTAL = 232448;
constexpr uint32_t R_FPART = SM_R;
constexpr uint32_t BAR_FULL = SM_BAR  , BAR_AFULL = SM_BAR + 48  , BAR_WFULL = SM_BAR + 96  , BAR_GU = SM_BAR + 248,
                   BAR_FIX = SM_BAR + 256  , BAR_AEMPTY = SM_BAR + 272  , BAR_HDONE = SM_BAR + 320  ,
                   BAR_EMPTY = SM_BAR + 336  ;
enum { NB_WG = 1  , NB_STAG = 3, NB_AUX = 4, NB_FFN2 = 5, NB_FFN = 8, NB_START = 9, NB_GO = 6, NB_ORD = 7 };

struct Params {
  const __nv_bfloat16 *wqkv, *x, *wr, *wo;
  Scratch* sc;
  const __nv_bfloat16 *wd, *wg, *wu;
  __nv_bfloat16* out;
  signed char work[136];
  CUtensorMap mx, mg, mu, mg8, mu8;
};

__device__ __forceinline__ void mbar_init(uint32_t bar, int cnt) { asm volatile("mbarrier.init.shared::cta.b64 [%0], %1;" ::"r"(bar), "r"(cnt) : "memory"); }
__device__ __forceinline__ void mbar_arrive(uint32_t bar) { asm volatile("mbarrier.arrive.shared::cta.b64 _, [%0];" ::"r"(bar) : "memory"); }
__device__ __forceinline__ void mbar_wait(uint32_t bar, uint32_t par) {
  asm volatile("{\n.reg .pred p;\nLOOP:\nmbarrier.try_wait.parity.shared::cta.b64 p, [%0], %1;\n@!p bra.uni LOOP;\n}\n" ::"r"(bar), "r"(par) : "memory");
}
__device__ __forceinline__ uint32_t mbar_test(uint32_t bar, uint32_t par) {
  uint32_t ok;
  asm volatile("{\n.reg .pred p;\nmbarrier.test_wait.parity.shared::cta.b64 p, [%1], %2;\nselp.u32 %0,1,0,p;\n}" : "=r"(ok) : "r"(bar), "r"(par) : "memory");
  return ok;
}
__device__ __forceinline__ bool elect_one() {
  uint32_t ok;
  asm volatile("{\n.reg .pred p;\nelect.sync _|p, 0xffffffff;\nselp.u32 %0, 1, 0, p;\n}" : "=r"(ok));
  return ok;
}
__device__ __forceinline__ float ex2(float x) { float r; asm("ex2.approx.ftz.f32 %0, %1;" : "=f"(r) : "f"(x)); return r; }
__device__ __forceinline__ float rsq(float x) { float r; asm("rsqrt.approx.ftz.f32 %0, %1;" : "=f"(r) : "f"(x)); return r; }
__device__ __forceinline__ float rcp(float x) { float r; asm("rcp.approx.ftz.f32 %0, %1;" : "=f"(r) : "f"(x)); return r; }
__device__ __forceinline__ void w_expect(uint32_t bar, uint32_t bytes) {
  asm volatile("{\n.reg .pred p;\nelect.sync _|p, 0xffffffff;\n@p mbarrier.arrive.expect_tx.shared::cta.b64 _, [%0], %1;\n}" ::"r"(bar), "r"(bytes) : "memory");
}
__device__ __forceinline__ void w_bulk(uint32_t dst, const void* src, uint32_t bytes, uint32_t bar) {
  asm volatile("{\n.reg .pred p;\nelect.sync _|p, 0xffffffff;\n@p cp.async.bulk.shared::cluster.global.mbarrier::complete_tx::bytes [%0], [%1], %2, [%3];\n}" ::"r"(dst), "l"(src), "r"(bytes), "r"(bar) : "memory");
}
__device__ __forceinline__ void w_tma2d(uint32_t dst, const CUtensorMap* m, int c0, int c1, uint32_t bar) {
  asm volatile("{\n.reg .pred p;\nelect.sync _|p, 0xffffffff;\n@p cp.async.bulk.tensor.2d.shared::cluster.global.mbarrier::complete_tx::bytes [%0], [%1, {%3, %4}], [%2];\n}" ::"r"(dst), "l"(m), "r"(bar), "r"(c0), "r"(c1) : "memory");
}
__device__ __forceinline__ void w_tma3d(uint32_t dst, const CUtensorMap* m, int c0, int c1, int c2, uint32_t bar) {
  asm volatile("{\n.reg .pred p;\nelect.sync _|p, 0xffffffff;\n@p cp.async.bulk.tensor.3d.shared::cluster.global.mbarrier::complete_tx::bytes [%0], [%1, {%3, %4, %5}], [%2];\n}" ::"r"(dst), "l"(m), "r"(bar), "r"(c0), "r"(c1), "r"(c2) : "memory");
}
__device__ __forceinline__ void w_prefetch(const void* src, uint32_t bytes) {
  asm volatile("{\n.reg .pred p;\nelect.sync _|p, 0xffffffff;\n@p cp.async.bulk.prefetch.L2.global [%0], %1;\n}" ::"l"(src), "r"(bytes) : "memory");
}
__device__ __forceinline__ void nb_sync(int id, int n) { asm volatile("bar.sync %0, %1;" ::"r"(id), "r"(n) : "memory"); }
__device__ __forceinline__ void nb_arrive(int id, int n) { asm volatile("bar.arrive %0, %1;" ::"r"(id), "r"(n) : "memory"); }
__device__ __forceinline__ void fence_async_smem() { asm volatile("fence.proxy.async.shared::cta;" ::: "memory"); }
__device__ __forceinline__ void fence_async_glob() { asm volatile("fence.proxy.async.global;" ::: "memory"); }
__device__ __forceinline__ void flag_after(void* p, uint32_t readback, uint32_t T, bool writer) {
  asm volatile("{\n.reg .pred p;\n.reg .u32 v;\nsetp.ne.u32 p, %3, 0;\nor.b32 v, %1, %2;\nmin.u32 v, v, %2;\n@p st.relaxed.gpu.global.u32 [%0], v;\n}"
               ::"l"(p), "r"(readback), "r"(T), "r"((uint32_t)writer) : "memory");
}
__device__ __forceinline__ uint4 ldg_rlx128(const void* p) { uint4 v; asm volatile("ld.relaxed.gpu.global.v4.b32 {%0,%1,%2,%3}, [%4];" : "=r"(v.x), "=r"(v.y), "=r"(v.z), "=r"(v.w) : "l"(p) : "memory"); return v; }
__device__ __forceinline__ uint2 ldg_rlx64(const void* p) { uint2 v; asm volatile("ld.relaxed.gpu.global.v2.b32 {%0,%1}, [%2];" : "=r"(v.x), "=r"(v.y) : "l"(p) : "memory"); return v; }
__device__ __forceinline__ void rld128(uint4& v, const void* p) { asm volatile("ld.relaxed.gpu.global.v4.b32 {%0,%1,%2,%3}, [%4];" : "+r"(v.x), "+r"(v.y), "+r"(v.z), "+r"(v.w) : "l"(p) : "memory"); }
__device__ __forceinline__ uint32_t ldg_rlx32(const void* p) { uint32_t v; asm volatile("ld.relaxed.gpu.global.b32 %0, [%1];" : "=r"(v) : "l"(p) : "memory"); return v; }
__device__ __forceinline__ uint4 ldg_nc128(const void* p) { uint4 v; asm volatile("ld.global.nc.v4.b32 {%0,%1,%2,%3}, [%4];" : "=r"(v.x), "=r"(v.y), "=r"(v.z), "=r"(v.w) : "l"(p)); return v; }
__device__ __forceinline__ uint32_t ldg_nc32(const void* p) { uint32_t v; asm volatile("ld.global.nc.L1::no_allocate.b32 %0, [%1];" : "=r"(v) : "l"(p)); return v; }
__device__ __forceinline__ void stg128(void* p, uint32_t a, uint32_t b, uint32_t c, uint32_t d) { asm volatile("st.relaxed.gpu.global.v4.b32 [%0], {%1,%2,%3,%4};" ::"l"(p), "r"(a), "r"(b), "r"(c), "r"(d) : "memory"); }
__device__ __forceinline__ void stg64(void* p, uint32_t a, uint32_t b) { asm volatile("st.relaxed.gpu.global.v2.b32 [%0], {%1,%2};" ::"l"(p), "r"(a), "r"(b) : "memory"); }
__device__ __forceinline__ void stg32(void* p, uint32_t a) { asm volatile("st.relaxed.gpu.global.b32 [%0], %1;" ::"l"(p), "r"(a) : "memory"); }
__device__ __forceinline__ void sts128(uint32_t a, uint32_t x, uint32_t y, uint32_t z, uint32_t w) { asm volatile("st.shared.v4.b32 [%0], {%1,%2,%3,%4};" ::"r"(a), "r"(x), "r"(y), "r"(z), "r"(w) : "memory"); }
__device__ __forceinline__ void sts64(uint32_t a, uint32_t x, uint32_t y) { asm volatile("st.shared.v2.b32 [%0], {%1,%2};" ::"r"(a), "r"(x), "r"(y) : "memory"); }
__device__ __forceinline__ void sts32(uint32_t a, uint32_t x) { asm volatile("st.shared.b32 [%0], %1;" ::"r"(a), "r"(x) : "memory"); }
__device__ __forceinline__ void stsf(uint32_t a, float x) { sts32(a, __float_as_uint(x)); }
__device__ __forceinline__ uint4 lds128(uint32_t a) { uint4 v; asm volatile("ld.shared.v4.b32 {%0,%1,%2,%3}, [%4];" : "=r"(v.x), "=r"(v.y), "=r"(v.z), "=r"(v.w) : "r"(a) : "memory"); return v; }
__device__ __forceinline__ uint2 lds64(uint32_t a) { uint2 v; asm volatile("ld.shared.v2.b32 {%0,%1}, [%2];" : "=r"(v.x), "=r"(v.y) : "r"(a) : "memory"); return v; }
__device__ __forceinline__ uint32_t lds32(uint32_t a) { uint32_t v; asm volatile("ld.shared.b32 %0, [%1];" : "=r"(v) : "r"(a) : "memory"); return v; }
__device__ __forceinline__ uint32_t pack_bf16(float lo, float hi) { uint32_t r; asm("cvt.rn.bf16x2.f32 %0, %1, %2;" : "=r"(r) : "f"(hi), "f"(lo)); return r; }
__device__ __forceinline__ float bf_lo(uint32_t w) { return __uint_as_float(w << 16); }
__device__ __forceinline__ float bf_hi(uint32_t w) { return __uint_as_float(w & 0xFFFF0000u); }
__device__ __forceinline__ float rbf(float x) { return bf_lo(pack_bf16(x, 0.f)); }
__device__ __forceinline__ float asf(uint32_t u) { return __uint_as_float(u); }
__device__ __forceinline__ uint32_t asu(float f) { return __float_as_uint(f); }
__device__ __forceinline__ float shx(float v, int m) { return __shfl_xor_sync(0xffffffffu, v, m); }
__device__ __forceinline__ uint32_t movm(uint32_t a) { uint32_t o; asm volatile("movmatrix.sync.aligned.m8n8.trans.b16 %0, %1;" : "=r"(o) : "r"(a)); return o; }
__device__ __forceinline__ void ldsm2(uint32_t& a, uint32_t& b, uint32_t addr) { asm volatile("ldmatrix.sync.aligned.m8n8.x2.shared.b16 {%0,%1}, [%2];" : "=r"(a), "=r"(b) : "r"(addr) : "memory"); }
__device__ __forceinline__ void ldsm4t(uint32_t* r, uint32_t addr) { asm volatile("ldmatrix.sync.aligned.m8n8.x4.trans.shared.b16 {%0,%1,%2,%3}, [%4];" : "=r"(r[0]), "=r"(r[1]), "=r"(r[2]), "=r"(r[3]) : "r"(addr) : "memory"); }
__device__ __forceinline__ void stsm4(uint32_t addr, uint32_t a, uint32_t b, uint32_t c, uint32_t d) { asm volatile("stmatrix.sync.aligned.m8n8.x4.shared.b16 [%0], {%1,%2,%3,%4};" ::"r"(addr), "r"(a), "r"(b), "r"(c), "r"(d) : "memory"); }
__device__ __forceinline__ void stsm2(uint32_t addr, uint32_t a, uint32_t b) { asm volatile("stmatrix.sync.aligned.m8n8.x2.shared.b16 [%0], {%1,%2};" ::"r"(addr), "r"(a), "r"(b) : "memory"); }
__device__ __forceinline__ void mma16(float* d, uint32_t a0, uint32_t a1, uint32_t a2, uint32_t a3, uint32_t b0, uint32_t b1) {
  asm volatile("mma.sync.aligned.m16n8k16.row.col.f32.bf16.bf16.f32 {%0,%1,%2,%3},{%4,%5,%6,%7},{%8,%9},{%0,%1,%2,%3};"
               : "+f"(d[0]), "+f"(d[1]), "+f"(d[2]), "+f"(d[3]) : "r"(a0), "r"(a1), "r"(a2), "r"(a3), "r"(b0), "r"(b1));
}
__device__ __forceinline__ void mma16z(float* d, uint32_t a0, uint32_t a1, uint32_t a2, uint32_t a3, uint32_t b0, uint32_t b1) {
  asm volatile("mma.sync.aligned.m16n8k16.row.col.f32.bf16.bf16.f32 {%0,%1,%2,%3},{%4,%5,%6,%7},{%8,%9},{%10,%10,%10,%10};"
               : "=f"(d[0]), "=f"(d[1]), "=f"(d[2]), "=f"(d[3]) : "r"(a0), "r"(a1), "r"(a2), "r"(a3), "r"(b0), "r"(b1), "f"(0.f));
}
__device__ __forceinline__ void mma8(float* d, uint32_t a0, uint32_t a1, uint32_t b0) {
  asm volatile("mma.sync.aligned.m16n8k8.row.col.f32.bf16.bf16.f32 {%0,%1,%2,%3},{%4,%5},{%6},{%0,%1,%2,%3};"
               : "+f"(d[0]), "+f"(d[1]), "+f"(d[2]), "+f"(d[3]) : "r"(a0), "r"(a1), "r"(b0));
}
__device__ __forceinline__ uint32_t pin(uint32_t v) { uint32_t r; asm volatile("shfl.sync.bfly.b32 %0, %1, 0, 31, 0xffffffff;" : "=r"(r) : "r"(v)); return r; }
__device__ __forceinline__ uint32_t pin0(uint32_t v) { uint32_t r; asm volatile("{\n.reg .u32 t;\nor.b32 t, %1, 1;\nbfind.shiftamt.u32 %0, t;\nshr.u32 %0, %0, 5;\n}" : "=r"(r) : "r"(v)); return r; }
__device__ __forceinline__ void mma8z(float* d, uint32_t a0, uint32_t a1, uint32_t b0) {
  asm volatile("mma.sync.aligned.m16n8k8.row.col.f32.bf16.bf16.f32 {%0,%1,%2,%3},{%4,%5},{%6},{%7,%7,%7,%7};"
               : "=f"(d[0]), "=f"(d[1]), "=f"(d[2]), "=f"(d[3]) : "r"(a0), "r"(a1), "r"(b0), "f"(0.f));
}
__device__ __forceinline__ void wg_fence() { asm volatile("wgmma.fence.sync.aligned;" ::: "memory"); }
__device__ __forceinline__ void wg_commit() { asm volatile("wgmma.commit_group.sync.aligned;" ::: "memory"); }
template <int N> __device__ __forceinline__ void wg_wait() { asm volatile("wgmma.wait_group.sync.aligned %0;" ::"n"(N) : "memory"); }
template <int N> __device__ __forceinline__ void fence_regs(float* d) {
#pragma unroll
  for (int k = 0; k < N; k++) asm volatile("" : "+f"(d[k])::"memory");
}
__host__ __device__ constexpr uint32_t DLO(uint32_t addr, uint32_t lbo) { return (addr >> 4) | ((lbo >> 4) << 16); }
__host__ __device__ constexpr uint32_t DHI(uint32_t sbo, uint32_t swz) { return (sbo >> 4) | (swz << 30); }
template <int N>
__device__ __forceinline__ void wait_flags(const void* base, const uint32_t V, const int lane) {
  const unsigned char* p = (const unsigned char*)base + lane * 32;
  const unsigned char* p2 = p + (lane < N - 32 ? 1024 : 0);
  uint32_t a0 = ldg_rlx32(p), a1 = N > 32 ? ldg_rlx32(p2) : V;
  __nanosleep(POLL_GAP);
  int n = 0;
#pragma unroll 1
  while (true) {
    const uint32_t b0 = ldg_rlx32(p), b1 = N > 32 ? ldg_rlx32(p2) : V;
    if (__all_sync(0xffffffffu, (int)((a0 - V) | (a1 - V)) >= 0)) break;
    a0 = ldg_rlx32(p); a1 = N > 32 ? ldg_rlx32(p2) : V;
    if (__all_sync(0xffffffffu, (int)((b0 - V) | (b1 - V)) >= 0)) break;
    if (++n > SPIN) TIMEOUT(__LINE__)
  }
}
__device__ __forceinline__ uint32_t ftag(float v, uint32_t par) { return (asu(v) & ~1u) | par; }
__device__ __forceinline__ uint32_t selu(uint32_t c, uint32_t a, uint32_t b) { uint32_t r; asm("{\n.reg .pred p;\nsetp.ne.u32 p, %1, 0;\nselp.b32 %0, %2, %3, p;\n}" : "=r"(r) : "r"(c), "r"(a), "r"(b)); return r; }
__device__ __forceinline__ float self(uint32_t c, float a, float b) { return asf(selu(c, asu(a), asu(b))); }
__device__ __forceinline__ uint32_t orx(uint32_t acc, uint32_t a, uint32_t ref) { uint32_t r; asm("lop3.b32 %0, %1, %2, %3, 0xF6;" : "=r"(r) : "r"(acc), "r"(a), "r"(ref)); return r; }
__device__ __forceinline__ uint32_t fkey(float r) {
  uint32_t u = asu(r);
  u = (u & 0x80000000u) ? ~u : (u | 0x80000000u);
  return (r == r) ? u : 0u;
}
__host__ __device__ constexpr int GI(int part, int t) { return t < 8 ? part * 8 + t : 24 + part; }

__device__ __forceinline__ void wgmma_ss_216(float* d, uint32_t al, uint32_t ah, uint32_t bl, uint32_t bh) {
  asm volatile("{\n.reg .b64 da, db;\nmov.b64 da, {%108, %109};\nmov.b64 db, {%110, %111};\n"
      "wgmma.mma_async.sync.aligned.m64n216k16.f32.bf16.bf16 {"
      "%0,%1,%2,%3,%4,%5,%6,%7,%8,%9,%10,%11,%12,%13,%14,%15,%16,%17,%18,%19,%20,%21,%22,%23,%24,%25,%26,"
      "%27,%28,%29,%30,%31,%32,%33,%34,%35,%36,%37,%38,%39,%40,%41,%42,%43,%44,%45,%46,%47,%48,%49,%50,%51,%52,%53,"
      "%54,%55,%56,%57,%58,%59,%60,%61,%62,%63,%64,%65,%66,%67,%68,%69,%70,%71,%72,%73,%74,%75,%76,%77,%78,%79,%80,"
      "%81,%82,%83,%84,%85,%86,%87,%88,%89,%90,%91,%92,%93,%94,%95,%96,%97,%98,%99,%100,%101,%102,%103,%104,%105,%106,%107"
      "}, da, db, 1, 1, 1, 0, 1;\n}\n"
      : "+f"(d[0]), "+f"(d[1]), "+f"(d[2]), "+f"(d[3]), "+f"(d[4]), "+f"(d[5]), "+f"(d[6]), "+f"(d[7]), "+f"(d[8]),
        "+f"(d[9]), "+f"(d[10]), "+f"(d[11]), "+f"(d[12]), "+f"(d[13]), "+f"(d[14]), "+f"(d[15]), "+f"(d[16]), "+f"(d[17]),
        "+f"(d[18]), "+f"(d[19]), "+f"(d[20]), "+f"(d[21]), "+f"(d[22]), "+f"(d[23]), "+f"(d[24]), "+f"(d[25]), "+f"(d[26]),
        "+f"(d[27]), "+f"(d[28]), "+f"(d[29]), "+f"(d[30]), "+f"(d[31]), "+f"(d[32]), "+f"(d[33]), "+f"(d[34]), "+f"(d[35]),
        "+f"(d[36]), "+f"(d[37]), "+f"(d[38]), "+f"(d[39]), "+f"(d[40]), "+f"(d[41]), "+f"(d[42]), "+f"(d[43]), "+f"(d[44]),
        "+f"(d[45]), "+f"(d[46]), "+f"(d[47]), "+f"(d[48]), "+f"(d[49]), "+f"(d[50]), "+f"(d[51]), "+f"(d[52]), "+f"(d[53]),
        "+f"(d[54]), "+f"(d[55]), "+f"(d[56]), "+f"(d[57]), "+f"(d[58]), "+f"(d[59]), "+f"(d[60]), "+f"(d[61]), "+f"(d[62]),
        "+f"(d[63]), "+f"(d[64]), "+f"(d[65]), "+f"(d[66]), "+f"(d[67]), "+f"(d[68]), "+f"(d[69]), "+f"(d[70]), "+f"(d[71]),
        "+f"(d[72]), "+f"(d[73]), "+f"(d[74]), "+f"(d[75]), "+f"(d[76]), "+f"(d[77]), "+f"(d[78]), "+f"(d[79]), "+f"(d[80]),
        "+f"(d[81]), "+f"(d[82]), "+f"(d[83]), "+f"(d[84]), "+f"(d[85]), "+f"(d[86]), "+f"(d[87]), "+f"(d[88]), "+f"(d[89]),
        "+f"(d[90]), "+f"(d[91]), "+f"(d[92]), "+f"(d[93]), "+f"(d[94]), "+f"(d[95]), "+f"(d[96]), "+f"(d[97]), "+f"(d[98]),
        "+f"(d[99]), "+f"(d[100]), "+f"(d[101]), "+f"(d[102]), "+f"(d[103]), "+f"(d[104]), "+f"(d[105]), "+f"(d[106]), "+f"(d[107])
      : "r"(al), "r"(ah), "r"(bl), "r"(bh));
}
__device__ __forceinline__ void wgmma_ss_72(float* d, uint32_t al, uint32_t ah, uint32_t bl, uint32_t bh) {
  asm volatile("{\n.reg .b64 da, db;\nmov.b64 da, {%36, %37};\nmov.b64 db, {%38, %39};\n"
      "wgmma.mma_async.sync.aligned.m64n72k16.f32.bf16.bf16 {"
      "%0,%1,%2,%3,%4,%5,%6,%7,%8,%9,%10,%11,%12,%13,%14,%15,%16,%17,%18,%19,%20,%21,%22,%23,%24,%25,%26,"
      "%27,%28,%29,%30,%31,%32,%33,%34,%35"
      "}, da, db, 1, 1, 1, 0, 1;\n}\n"
      : "+f"(d[0]), "+f"(d[1]), "+f"(d[2]), "+f"(d[3]), "+f"(d[4]), "+f"(d[5]), "+f"(d[6]), "+f"(d[7]), "+f"(d[8]),
        "+f"(d[9]), "+f"(d[10]), "+f"(d[11]), "+f"(d[12]), "+f"(d[13]), "+f"(d[14]), "+f"(d[15]), "+f"(d[16]), "+f"(d[17]),
        "+f"(d[18]), "+f"(d[19]), "+f"(d[20]), "+f"(d[21]), "+f"(d[22]), "+f"(d[23]), "+f"(d[24]), "+f"(d[25]), "+f"(d[26]),
        "+f"(d[27]), "+f"(d[28]), "+f"(d[29]), "+f"(d[30]), "+f"(d[31]), "+f"(d[32]), "+f"(d[33]), "+f"(d[34]), "+f"(d[35])
      : "r"(al), "r"(ah), "r"(bl), "r"(bh));
}
template <uint32_t BH>
__device__ __forceinline__ void wgmma_rs_216(float* d, uint32_t a0, uint32_t a1, uint32_t a2, uint32_t a3, uint32_t bl) {
  asm volatile("{\n.reg .b64 db;\nmov.b64 db, {%112, %113};\n"
      "wgmma.mma_async.sync.aligned.m64n216k16.f32.bf16.bf16 {"
      "%0,%1,%2,%3,%4,%5,%6,%7,%8,%9,%10,%11,%12,%13,%14,%15,%16,%17,%18,%19,%20,%21,%22,%23,%24,%25,%26,"
      "%27,%28,%29,%30,%31,%32,%33,%34,%35,%36,%37,%38,%39,%40,%41,%42,%43,%44,%45,%46,%47,%48,%49,%50,%51,%52,%53,"
      "%54,%55,%56,%57,%58,%59,%60,%61,%62,%63,%64,%65,%66,%67,%68,%69,%70,%71,%72,%73,%74,%75,%76,%77,%78,%79,%80,"
      "%81,%82,%83,%84,%85,%86,%87,%88,%89,%90,%91,%92,%93,%94,%95,%96,%97,%98,%99,%100,%101,%102,%103,%104,%105,%106,%107"
      "}, {%108,%109,%110,%111}, db, 1, 1, 1, 1;\n}\n"
      : "+f"(d[0]), "+f"(d[1]), "+f"(d[2]), "+f"(d[3]), "+f"(d[4]), "+f"(d[5]), "+f"(d[6]), "+f"(d[7]), "+f"(d[8]),
        "+f"(d[9]), "+f"(d[10]), "+f"(d[11]), "+f"(d[12]), "+f"(d[13]), "+f"(d[14]), "+f"(d[15]), "+f"(d[16]), "+f"(d[17]),
        "+f"(d[18]), "+f"(d[19]), "+f"(d[20]), "+f"(d[21]), "+f"(d[22]), "+f"(d[23]), "+f"(d[24]), "+f"(d[25]), "+f"(d[26]),
        "+f"(d[27]), "+f"(d[28]), "+f"(d[29]), "+f"(d[30]), "+f"(d[31]), "+f"(d[32]), "+f"(d[33]), "+f"(d[34]), "+f"(d[35]),
        "+f"(d[36]), "+f"(d[37]), "+f"(d[38]), "+f"(d[39]), "+f"(d[40]), "+f"(d[41]), "+f"(d[42]), "+f"(d[43]), "+f"(d[44]),
        "+f"(d[45]), "+f"(d[46]), "+f"(d[47]), "+f"(d[48]), "+f"(d[49]), "+f"(d[50]), "+f"(d[51]), "+f"(d[52]), "+f"(d[53]),
        "+f"(d[54]), "+f"(d[55]), "+f"(d[56]), "+f"(d[57]), "+f"(d[58]), "+f"(d[59]), "+f"(d[60]), "+f"(d[61]), "+f"(d[62]),
        "+f"(d[63]), "+f"(d[64]), "+f"(d[65]), "+f"(d[66]), "+f"(d[67]), "+f"(d[68]), "+f"(d[69]), "+f"(d[70]), "+f"(d[71]),
        "+f"(d[72]), "+f"(d[73]), "+f"(d[74]), "+f"(d[75]), "+f"(d[76]), "+f"(d[77]), "+f"(d[78]), "+f"(d[79]), "+f"(d[80]),
        "+f"(d[81]), "+f"(d[82]), "+f"(d[83]), "+f"(d[84]), "+f"(d[85]), "+f"(d[86]), "+f"(d[87]), "+f"(d[88]), "+f"(d[89]),
        "+f"(d[90]), "+f"(d[91]), "+f"(d[92]), "+f"(d[93]), "+f"(d[94]), "+f"(d[95]), "+f"(d[96]), "+f"(d[97]), "+f"(d[98]),
        "+f"(d[99]), "+f"(d[100]), "+f"(d[101]), "+f"(d[102]), "+f"(d[103]), "+f"(d[104]), "+f"(d[105]), "+f"(d[106]), "+f"(d[107])
      : "r"(a0), "r"(a1), "r"(a2), "r"(a3), "r"(bl), "n"(BH));
}

struct Ctx {
  int i, j, cta;
};
#define TSTAMP(k) do {} while (0)
#define PSTAMP(k) do {} while (0)
#define PROF_DUMP() do {} while (0)
#define PROF_END() do {} while (0)
#define GSTAMP(k) do {} while (0)
#define CSTAMP(k) STAMPIF(1, L * 40 + p * 20 + (k))

__device__ __forceinline__ int ffn_c32(int cta) { return 32 * cta; }
__device__ __forceinline__ int ffn_c8(int cta) { return 4096 + 8 * (cta >> 1); }
__device__ __forceinline__ void load_gu(const Params& P, const int cta_, const int mat, const int b, const uint32_t bar) {
  const int cta = cta_;
  w_tma2d(sb + SM_G + mat * 46080 + b * 6144, &P.mg + mat, ffn_c32(cta), b * 96, bar);
  if (cta & 1) w_tma2d(sb + SM_G + mat * 46080 + 36864 + b * 1536, &P.mg8 + mat, ffn_c8(cta), b * 96, bar);
}

struct Winner { float r, m, rstd; int ci, rr; };

__device__ __forceinline__ Winner poll_winner(const void* p, uint4 v, const uint32_t tg) {
  int n = 0;
#pragma unroll 1
  while (!__all_sync(0xffffffffu, ((v.y ^ (tg << 6)) >> 6) == 0)) {
    rld128(v, p);
    if (++n > SPIN) TIMEOUT(__LINE__)
  }
  uint32_t key = fkey(asf(v.x));
  uint32_t mx = __reduce_max_sync(0xffffffffu, key);
  int src = __ffs(__ballot_sync(0xffffffffu, key == mx)) - 1;
  Winner w;
  w.ci = src;
  w.r = asf(__shfl_sync(0xffffffffu, v.x, src));
  w.rr = (int)__shfl_sync(0xffffffffu, v.y, src) & 63;
  w.m = asf(__shfl_sync(0xffffffffu, v.z, src));
  w.rstd = asf(__shfl_sync(0xffffffffu, v.w, src));
  return w;
}

__device__ __forceinline__ float2 row_stats(const Params& P, const int r, const int lane) {
  const unsigned char* src = (const unsigned char*)P.x + (((r & ~127) + 2 * (r & 63) + ((r >> 6) & 1)) * 1152 + (lane & 15) * 16);
  uint4 v[4];
#pragma unroll
  for (int m = 0; m < 4; m++) v[m] = ldg_nc128(src + m * 256);
  uint2 v4;
  asm volatile("ld.global.nc.v2.b32 {%0,%1}, [%2];" : "=r"(v4.x), "=r"(v4.y) : "l"(src + (1024 - (lane & 15) * 8)));
  nb_arrive(NB_START, 288 + pin0(v4.x));
  const float sft = __shfl_sync(0xffffffffu, bf_lo(v[0].x), lane & 16);
  float s1 = 0.f, s2 = 0.f, s3 = 0.f;
#pragma unroll
  for (int e = 0; e < 18; e++) {
    const uint32_t u = e < 16 ? (&v[0].x)[e] : (&v4.x)[e - 16];
    const float d0 = bf_lo(u) - sft, d1 = bf_hi(u) - sft;
    s1 += d0 + d1; s2 = fmaf(d0, d0, s2); s3 = fmaf(d1, d1, s3);
  }
  s2 += s3;
#pragma unroll
  for (int o = 1; o < 16; o <<= 1) { s1 += shx(s1, o); s2 += shx(s2, o); }
  s1 *= (1.f / 576.f);
  return make_float2(s1 + sft, rsq(fmaxf(s2 * (1.f / 576.f) - s1 * s1, 0.f) + EPS));
}

struct Unit { uint4 v[3]; };
__device__ __forceinline__ Unit unit_load(const unsigned char* src) {
  Unit u;
#pragma unroll
  for (int m = 0; m < 3; m++) u.v[m] = ldg_nc128(src + m * 48);
  return u;
}
__device__ __forceinline__ uint32_t unit_store(unsigned char* sc, const Unit& u, const int lane, const uint32_t o0, const uint32_t o1, const uint32_t o2) {
  stg128(sc + o0, u.v[0].x, u.v[0].y, u.v[0].z, u.v[0].w);
  stg128(sc + o1, u.v[1].x, u.v[1].y, u.v[1].z, u.v[1].w);
  stg128(sc + o2, u.v[2].x, u.v[2].y, u.v[2].z, u.v[2].w);
  return ldg_rlx32(sc + ((lane & 3) == 0 ? o0 : (lane & 3) == 1 ? o1 : o2));
}

__device__ __forceinline__ void store_rows(const uint32_t stg, unsigned char* obase, const int skip, const int lane) {
#pragma unroll
  for (int m = 0; m < 5; m++) {
    const int e = lane + 32 * m, r = (e * 57) >> 9;
    const uint4 v = lds128(stg + min(e, 143) * 16);
    if (e < 144 && r != skip) *(uint4*)(obase + (r * (2304 - 144) + e * 16)) = v;
  }
}

__device__ __forceinline__ void consumer_role(const Ctx& cx, const Params& P, const unsigned char* smem, const int p, const int w, const int lane_) {
  int lane = lane_;
#define g (lane >> 2)
#define q (lane & 3)
#define first_lane (lane == 0)
  const int i = cx.i, j = cx.j, ip = i * 2 + p;
  unsigned char* const sc = (unsigned char*)P.sc;
  float m_lo = 0.f, m_hi = 0.f, rs_lo = 0.f, rs_hi = 0.f;
  uint32_t T = ldg_rlx32(P.sc->cflag[ip][j * 4 + w]);
  nb_sync(NB_ORD, 352);
  if (X_DELAY) { const int c0 = clock(); while ((int)(clock() - c0) < X_DELAY + (p * 4 + w) * X_STEP) {} }
  {
    const int t = min(w * 32 + lane, 95);
    uint32_t u0 = 0, u1 = 0, u2 = 0, u = 0;
    if (p == 0) {
      u0 = ldg_nc32((const uint32_t*)P.wr + t); u1 = ldg_nc32((const uint32_t*)P.wr + 96 + t); u2 = ldg_nc32((const uint32_t*)P.wr + 192 + t);
      u = ldg_nc32((const uint32_t*)P.wr + 36 * j + min(t, 35));
    }
    const int r = cx.cta * 16 + (p * 4 + w) * 2 + (lane >> 4);
    const float2 st = row_stats(P, r, lane);
    T = __shfl_sync(0xffffffffu, (T >> 3) + 1, 0);
    if ((lane & 15) == 0) stg128(sc + (OFF(st0) + r * 16), asu(st.x), asu(st.y), T, 0u);
    STAMPIF(1, 111);
    if (p == 0) {
      float s = (bf_lo(u0) + bf_hi(u0)) + (bf_lo(u1) + bf_hi(u1)) + (bf_lo(u2) + bf_hi(u2));
#pragma unroll
      for (int o = 1; o < 32; o <<= 1) s += shx(s, o);
      stsf(sb + SM_WR + 288 + w * 4, s);
      sts64(sb + SM_WR + min(t, 35) * 8, u << 16, u & 0xFFFF0000u);
    }
  }
#pragma unroll 1
  for (int L = 0; L < 2; L++) {
    lane = pin(lane);
    const uint32_t tg = 2 * T + L;
    float c_lo = 0.f, c_hi = 0.f;
    bool sel_lo = false, sel_hi = false;
    float acc[108];
#pragma unroll
    for (int k = 0; k < 108; k++) acc[k] = 0.f;
    fence_regs<108>(acc);
    {
      const uint32_t ah = L == 0 ? DHI(1024, 1) : DHI(128, 0);
      const uint32_t astep = L == 0 ? 2 : 128;
      const uint32_t a0 = (L == 0 ? DLO(sb + SM_A, 16) : DLO(sb + SM_A, 1024)) + p * 512;
      constexpr uint32_t bh = DHI(512, 0);
      if (L == 1) {
        const float ul = 1.f + rs_lo, uh = 1.f + rs_hi;
        const float vl = fmaxf(rcp(rs_lo * rs_lo) - EPS, 0.f), vh = fmaxf(rcp(rs_hi * rs_hi) - EPS, 0.f);
        c_lo = ul * rsq(vl * ul * ul + EPS);
        c_hi = uh * rsq(vh * uh * uh + EPS);
      }
      if (L == 1) mbar_wait(sb + BAR_AFULL + p * 8, 0);
      mbar_wait(sb + BAR_FULL, 0);
      if (L == 1 && p == 1) nb_sync(NB_FFN2, 224);
      CSTAMP(0); GSTAMP(120 + 2 * L);
      uint32_t e0 = 0, e1 = 0;
      bool prepped = false, gone = false;
      auto prep_ext = [&]() {
        const int row = p * 64 + w * 16 + g;
        if (L == 0) {
          const uint2 u0 = lds64(sb + SM_R + row * 8), u1 = lds64(sb + SM_R + row * 8 + 64);
          m_lo = asf(u0.x); c_lo = asf(u0.y); m_hi = asf(u1.x); c_hi = asf(u1.y);
        } else {
          const uint4 sv = lds128(sb + SM_SEL);
          sel_lo = (int)sv.x == row; sel_hi = (int)sv.x == row + 8;
          if (sel_lo) { m_lo = asf(sv.z); c_lo = asf(sv.w); }
          if (sel_hi) { m_hi = asf(sv.z); c_hi = asf(sv.w); }
        }
        const float hl = rbf(-m_lo), hh = rbf(-m_hi);
        const uint32_t em = selu(lane & 1, 0x0000FFFFu, 0xFFFFFFFFu);
        e0 = selu(lane & 2, selu(sel_lo && !(lane & 1), 0x3F803F80u, 0u), pack_bf16(hl, -m_lo - hl) & em);
        e1 = selu(lane & 2, selu(sel_hi && !(lane & 1), 0x3F803F80u, 0u), pack_bf16(hh, -m_hi - hh) & em);
      };
      bool pend = false;
#pragma unroll 1
      for (int r = 0; r < 3; r++) {
#pragma unroll
        for (int h = 0; h < 6; h++) {
          const uint32_t al = a0 + (h >> 1) * 1024 + (h & 1) * 2 * astep, bl = DLO(sb + SM_B, 128) + h * 864;
          const uint32_t nb = sb + BAR_FULL + ((h + 1) % 6) * 8, np = (r + (h == 5)) & 1;
          TSTAMP((6 * r + h) * 2);
          wg_fence();
          wgmma_ss_216(acc, al, ah, bl, bh);
          wgmma_ss_216(acc, al + astep, ah, bl + 16, bh);
          wg_commit();
          if (h == 5 && r == 2) break;
          const uint32_t ok = mbar_test(nb, np);
          if ((h == 1 || h == 3) && r == 0 && L == 1) mbar_wait(sb + BAR_AFULL + (h + 1 + p) * 8, 0);
          if (h == 0 && r == 1 && L == 0) {
          if (lane < 16) stg128(sc + (OFF(stats) + (ip * 4 + w) * 2048 + j * 256 + lane * 16), 0u, 0u, 0u, 0u);
          if (w == 3 && i < 15 && lane < 28) {
#pragma unroll
            for (int e = 0; e < 6; e++) stg128(sc + (OFF(halo) + ((ip + 2) * 8 + j) * 2688 + lane * 16) + e * 448, 0u, 0u, 0u, 0u);
          }
          if (w == 0 && lane < 2) stg128(sc + (OFF(cand) + (j * 32 + ip) * (CAND_W * 4) + lane * 16), 0u, 0u, 0u, 0u);
          }
          wg_wait<1>();
          if (first_lane && pend) mbar_arrive(sb + BAR_EMPTY + ((h + 5) % 6) * 8);
          pend = true;
          const bool hold = h == HOLD_C % 6 && r == HOLD_C / 6 && p == 1;
          if (hold || (!ok && !mbar_test(nb, np))) {
            wg_wait<0>();
            if (first_lane) mbar_arrive(sb + BAR_EMPTY + h * 8);
            pend = false;
            TSTAMP((6 * r + h) * 2 + 1);
            mbar_wait(nb, np);
            if (hold) {
              if (mbar_test(sb + BAR_FIX + 8, L)) { prep_ext(); prepped = true; }
              nb_sync(NB_STAG, 256);
            }
          }
        }
      }
      if (!prepped) {
        if (p == 0 && !gone && !mbar_test(sb + BAR_FIX, L)) { nb_arrive(NB_STAG, 256); gone = true; }
        mbar_wait(sb + BAR_FIX + p * 8, L);
        prep_ext();
      }
      wg_fence();
      wgmma_rs_216<DHI(128, 0)>(acc, e0, e1, 0u, 0u, DLO(sb + SM_BEXT, 0));
      wg_commit();
      if (p == 0 && !gone) nb_arrive(NB_STAG, 256);
      wg_wait<2>();
      if (first_lane && pend) mbar_arrive(sb + BAR_EMPTY + 32);
    }
    lane = pin(lane);
    const uint32_t fragoff = ip * 73728 + (9 * j) * 1024 + w * 256 + lane * 4;
    const uint32_t rboff = (min(lane, 17) >> 1) * 1024 + (lane < 18 ? lane & 1 : 0) * 128;
    const uint32_t hl16 = (lane < 4 ? lane : lane - 4) * 16;
    const uint32_t o_halo = pin(OFF(halo) + ((ip + (w == 3 ? 2 : 0)) * 8 + j) * 2688 + hl16);
    const uint32_t o_o = pin(OFF(obuf) + fragoff);
    nb_sync(NB_WG + p, 128);
    if ((o_halo | o_o) == 0xFFFFFFFFu) __trap();
    wg_wait<0>();
    fence_regs<108>(acc);
    if (first_lane) mbar_arrive(sb + BAR_EMPTY + 40);
    CSTAMP(1); GSTAMP(121 + 2 * L);
    {
      uint32_t Kh[9], Vh[9], Kl[9], Vl[9], Kx[9], Vx[9], Ql[9], Qh[9];
#pragma unroll
      for (int t = 0; t < 9; t++) {
        Kh[t] = pack_bf16(acc[4 * GI(1, t) + 2] * c_hi, acc[4 * GI(1, t) + 3] * c_hi);
        Vh[t] = pack_bf16(acc[4 * GI(2, t) + 2] * c_hi, acc[4 * GI(2, t) + 3] * c_hi);
        Ql[t] = pack_bf16(acc[4 * GI(0, t)], acc[4 * GI(0, t) + 1]);
        Qh[t] = pack_bf16(acc[4 * GI(0, t) + 2], acc[4 * GI(0, t) + 3]);
      }
      const uint32_t hbuf = sb + SM_A + p * 8192 + w * 2688 + hl16;
      if (w < 3) {
        if (lane >= 4) {
#pragma unroll
          for (int e = 0; e < 4; e++) sts128(hbuf + e * 448, Kh[2 * e], Kh[2 * e + 1], Vh[e], tg);
          sts128(hbuf + 4 * 448, Kh[8], Vh[4], Vh[5], tg);
          sts128(hbuf + 5 * 448, Vh[6], Vh[7], Vh[8], tg);
        }
      } else if (i < 15 && lane >= 4) {
#pragma unroll
        for (int e = 0; e < 4; e++) stg128(sc + o_halo + e * 448, Kh[2 * e], Kh[2 * e + 1], Vh[e], tg);
        stg128(sc + o_halo + 4 * 448, Kh[8], Vh[4], Vh[5], tg);
        stg128(sc + o_halo + 5 * 448, Vh[6], Vh[7], Vh[8], tg);
      }
      nb_sync(NB_WG + p, 128);
#pragma unroll
      for (int t = 0; t < 9; t++) {
        Kl[t] = pack_bf16(acc[4 * GI(1, t)] * c_lo, acc[4 * GI(1, t) + 1] * c_lo);
      }
#pragma unroll
      for (int t = 0; t < HALO_V; t++) Vl[t] = pack_bf16(acc[4 * GI(2, t)] * c_lo, acc[4 * GI(2, t) + 1] * c_lo);
      uint32_t dep = (Kl[0] ^ Kl[1] ^ Kl[2]) | (Kl[3] ^ Kl[4] ^ Kl[5]) | (Kl[6] ^ Kl[7] ^ Kl[8]);
#pragma unroll
      for (int t = 0; t < HALO_V; t += 3) dep |= Vl[t] ^ Vl[t + 1] ^ Vl[t + 2];
      const unsigned char* hp = (w > 0 ? smem + (hbuf - 2688 - sb) : sc + o_halo) + pin0(dep);
      uint4 hv[6];
#pragma unroll
      for (int e = 0; e < 6; e++)
        asm volatile("ld.relaxed.gpu.v4.b32 {%0,%1,%2,%3}, [%4];" : "=r"(hv[e].x), "=r"(hv[e].y), "=r"(hv[e].z), "=r"(hv[e].w) : "l"(hp + e * 448) : "memory");
      CSTAMP(2);
#pragma unroll
      for (int t = 0; t < 9; t++) {
        if (t >= HALO_V) Vl[t] = pack_bf16(acc[4 * GI(2, t)] * c_lo, acc[4 * GI(2, t) + 1] * c_lo);
        Vl[t] = movm(Vl[t]);
        Vh[t] = movm(Vh[t]);
      }
      uint32_t qa[4][2], qb[4][2];
      float s1[4][4], s2[4][4];
#pragma unroll
      for (int h = 0; h < 4; h++) {
        qa[h][0] = q >= h ? Ql[2 * h] : 0u; qa[h][1] = q >= h ? Qh[2 * h] : 0u;
        qb[h][0] = q <= h ? Ql[2 * h + 2] : 0u; qb[h][1] = q <= h ? Qh[2 * h + 2] : 0u;
      }
      const bool first = (i == 0 && w == 0);
      if (w == 0 && i > 0) {
        int n = 0;
#pragma unroll 1
        while (__any_sync(0xffffffffu, (orx(orx(orx(0, hv[0].w, tg), hv[1].w, tg), hv[2].w, tg) | orx(orx(orx(0, hv[3].w, tg), hv[4].w, tg), hv[5].w, tg)) != 0)) {
#pragma unroll
          for (int e = 0; e < 6; e++) rld128(hv[e], sc + o_halo + e * 448);
          if (++n > SPIN) TIMEOUT(__LINE__)
        }
      }
#pragma unroll
      for (int e = 0; e < 4; e++) { Kx[2 * e] = hv[e].x; Kx[2 * e + 1] = hv[e].y; Vx[e] = hv[e].z; }
      Kx[8] = hv[4].x; Vx[4] = hv[4].y; Vx[5] = hv[4].z; Vx[6] = hv[5].x; Vx[7] = hv[5].y; Vx[8] = hv[5].z;
      CSTAMP(3);
#pragma unroll
      for (int t = 0; t < 9; t++) Vx[t] = movm(Vx[t]);
#pragma unroll
      for (int h = 0; h < 4; h++) { mma8z(s1[h], qb[h][0], qb[h][1], Kl[2 * h + 2]); mma8z(s2[h], qb[h][0], qb[h][1], Kh[2 * h + 2]); }
#pragma unroll
      for (int h = 0; h < 4; h++) {
        mma16(s1[h], qa[h][0], qa[h][1], Ql[2 * h + 1], Qh[2 * h + 1], Kl[2 * h], Kl[2 * h + 1]);
        mma16(s2[h], qa[h][0], qa[h][1], Ql[2 * h + 1], Qh[2 * h + 1], Kh[2 * h], Kh[2 * h + 1]);
      }
      float s0[4][4];
#pragma unroll
      for (int h = 0; h < 4; h++) mma8z(s0[h], qb[h][0], qb[h][1], Kx[2 * h + 2]);
#pragma unroll
      for (int h = 0; h < 4; h++) mma16(s0[h], qa[h][0], qa[h][1], Ql[2 * h + 1], Qh[2 * h + 1], Kx[2 * h], Kx[2 * h + 1]);
      const bool pv0 = 2 * q > g, pv1 = 2 * q + 1 > g;
      const uint32_t PM = (pv0 ? 0x0000FFFFu : 0u) | (pv1 ? 0xFFFF0000u : 0u);
      const float kS = 0.23570226039551584f * 1.4426950408889634f;
      const float sc_lo = c_lo * kS, sc_hi = c_hi * kS;
      float sl[4][2], sh[4][2], ml[4], mh[4];
#pragma unroll
      for (int h = 0; h < 4; h++) {
        sh[h][0] = pv0 ? s1[h][2] : s2[h][2];
        sh[h][1] = pv1 ? s1[h][3] : s2[h][3];
        mh[h] = fmaxf(sh[h][0], sh[h][1]);
        sl[h][0] = pv0 ? (first ? -INFINITY : s0[h][0]) : s1[h][0];
        sl[h][1] = pv1 ? (first ? -INFINITY : s0[h][1]) : s1[h][1];
        ml[h] = fmaxf(sl[h][0], sl[h][1]);
      }
#pragma unroll
      for (int s = 1; s <= 2; s <<= 1) {
        float tl[4], th[4];
#pragma unroll
        for (int h = 0; h < 4; h++) { th[h] = shx(mh[h], s); tl[h] = shx(ml[h], s); }
#pragma unroll
        for (int h = 0; h < 4; h++) { mh[h] = fmaxf(mh[h], th[h]); ml[h] = fmaxf(ml[h], tl[h]); }
      }
      float o[4][3][4], den[4][4];
      uint32_t px[4];
#pragma unroll
      for (int h = 0; h < 4; h++) {
        const float bl = -ml[h] * sc_lo, bh = -mh[h] * sc_hi;
        const uint32_t pl = pack_bf16(ex2(fmaf(sl[h][0], sc_lo, bl)), ex2(fmaf(sl[h][1], sc_lo, bl)));
        const uint32_t ph = pack_bf16(ex2(fmaf(sh[h][0], sc_hi, bh)), ex2(fmaf(sh[h][1], sc_hi, bh)));
        mma8z(den[h], pl, ph, 0x3F803F80u);
        px[h] = pl & PM;
#pragma unroll
        for (int u = 0; u < 3; u++) mma16z(o[h][u], pl & ~PM, ph & PM, 0u, ph & ~PM, Vl[2 * h + u], Vh[2 * h + u]);
      }
#pragma unroll
      for (int h = 0; h < 4; h++)
#pragma unroll
        for (int u = 0; u < 3; u++) mma8(o[h][u], px[h], 0u, Vx[2 * h + u]);
      float il[4], ih[4];
#pragma unroll
      for (int h = 0; h < 4; h++) { il[h] = rcp(den[h][0]); ih[h] = rcp(den[h][2]); }
#pragma unroll
      for (int t = 0; t < 9; t++) {
        const int h = t == 8 ? 3 : t >> 1, u = t == 8 ? 2 : t & 1;
        float v0 = o[h][u][0], v1 = o[h][u][1], v2 = o[h][u][2], v3 = o[h][u][3], kl = il[h], kh = ih[h];
        if (u == 0 && h > 0 && q < h) {
          v0 = o[h - 1][2][0]; v1 = o[h - 1][2][1]; v2 = o[h - 1][2][2]; v3 = o[h - 1][2][3]; kl = il[h - 1]; kh = ih[h - 1];
        }
        stg32(sc + o_o + t * 1024, pack_bf16(v0 * kl, v1 * kl));
        stg32(sc + o_o + t * 1024 + 128, pack_bf16(v2 * kh, v3 * kh));
      }
    }
    CSTAMP(4);
    const uint32_t rbo = ldg_rlx32(sc + (o_o + rboff));
    lane = pin(lane);
    const uint32_t o_x = o_o + (OFF(xbuf) - OFF(obuf)), o_xrb = o_x + rboff;
    const uint32_t o_cf = OFF(cflag) + (ip * 32 + j * 4 + w) * 32 + lane * 4;
    if (L == 1 && first_lane) mbar_arrive(sb + BAR_HDONE + p * 8);
    flag_after(sc + o_cf, rbo, 8 * T + 2 * L, lane < 8);
    STAMPD(asf(rbo), L * 40 + p * 20 + 13);
    uint32_t resid[18];
    mbar_wait(sb + BAR_FULL + 16, 1); mbar_wait(sb + BAR_FULL + 32, 1);
    if (L == 0) {
      const uint32_t ra = sb + SM_A + (2 + p) * 8192 + (w * 16 + (lane & 15)) * 128;
#pragma unroll
      for (int t = 0; t < 9; t++) ldsm2(resid[2 * t], resid[2 * t + 1], ra + ((j + t) >> 3) * 16384 + ((((j + t) ^ lane) & 7) << 4));
      if (first_lane) mbar_arrive(sb + BAR_HDONE + p * 8 + pin0(resid[17]));
    } else {
#pragma unroll
      for (int t = 0; t < 9; t++) { resid[2 * t] = ldg_rlx32(sc + o_x + t * 1024); resid[2 * t + 1] = ldg_rlx32(sc + o_x + t * 1024 + 128); }
    }
    const uint32_t o_st = OFF(stats) + (ip * 4 + w) * 2048;
    const uint32_t o_stw = pin(o_st + j * 256 + (g + 8 * (q & 1)) * 16), o_str = pin(o_st + q * 512 + g * 16);
    const uint32_t o_cand = pin(OFF(cand) + (j * 32 + ip) * (CAND_W * 4) + q * 16);
    const uint32_t o_xc = pin(OFF(xcand) + (ip * 8 + j) * 192 + q * 16);
    float accw[36];
    float wr[18];
#pragma unroll
    for (int t = 0; t < 9; t++) { const uint2 u = lds64(sb + SM_WR + t * 32 + q * 8); wr[2 * t] = asf(u.x); wr[2 * t + 1] = asf(u.y); }
    const uint4 ws4 = lds128(sb + SM_WR + 288);
    const float wsum = asf(pin(asu(asf(ws4.x) + asf(ws4.y) + asf(ws4.z))));
    {
      float ul = 1.f, uh = 1.f, vl = 0.f, vh = 0.f;
      if (L == 1) {
        ul += rs_lo; uh += rs_hi; vl = -m_lo * rs_lo; vh = -m_hi * rs_hi;
        if (sel_lo || sel_hi) {
#pragma unroll
          for (int t = 0; t < 9; t++) {
            const uint32_t z = lds32(sb + SM_X2S + t * 16 + q * 4);
            if (sel_hi) resid[2 * t + 1] = z; else resid[2 * t] = z;
          }
          if (sel_hi) { uh = 1.f; vh = 0.f; } else { ul = 1.f; vl = 0.f; }
        }
        __syncwarp();
      }
#pragma unroll
      for (int t = 0; t < 9; t++) {
        accw[4 * t] = fmaf(bf_lo(resid[2 * t]), ul, vl); accw[4 * t + 1] = fmaf(bf_hi(resid[2 * t]), ul, vl);
        accw[4 * t + 2] = fmaf(bf_lo(resid[2 * t + 1]), uh, vh); accw[4 * t + 3] = fmaf(bf_hi(resid[2 * t + 1]), uh, vh);
      }
    }
    fence_regs<36>(accw);
    mbar_wait(sb + BAR_FULL, 1); mbar_wait(sb + BAR_FULL + 8, 1); mbar_wait(sb + BAR_FULL + 24, 1); mbar_wait(sb + BAR_FULL + 40, 1);
    {
      uint32_t wf = sb + BAR_WFULL + p * 72;
      uint32_t bl = DLO(sb + SM_B, 128);
      uint32_t half = p;
      mbar_wait(wf, L);
      CSTAMP(5);
#pragma unroll 1
      for (int c3 = 0; c3 < 3; c3++) {
        const uint32_t al = DLO(sb + SM_A, 1024) + half * 512;
        const uint32_t ae = sb + BAR_AEMPTY + half * 24;
#pragma unroll
        for (int cc = 0; cc < 3; cc++) {
          TSTAMP(36 + (c3 * 3 + cc) * 2);
          wg_fence();
          wgmma_ss_72(accw, al + cc * 1024, DHI(128, 0), bl + cc * 576, DHI(256, 0));
          wgmma_ss_72(accw, al + cc * 1024 + 128, DHI(128, 0), bl + cc * 576 + 144, DHI(256, 0));
          const uint32_t ok = mbar_test(wf + cc * 8 + 8, L);
          wgmma_ss_72(accw, al + cc * 1024 + 256, DHI(128, 0), bl + cc * 576 + 288, DHI(256, 0));
          wgmma_ss_72(accw, al + cc * 1024 + 384, DHI(128, 0), bl + cc * 576 + 432, DHI(256, 0));
          wg_commit();
          wg_wait<1>();
          if (cc > 0) { if (first_lane) { mbar_arrive(ae + cc * 8 - 8); if (cc == 2) mbar_arrive(sb + BAR_EMPTY + c3 * 16); } }
          else if (first_lane && c3 > 0) { mbar_arrive(sb + BAR_AEMPTY + 40 - half * 24); mbar_arrive(sb + BAR_EMPTY + c3 * 16 - 8); }
          if (!ok && (cc < 2 || c3 < 2)) mbar_wait(wf + cc * 8 + 8, L);
        }
        wf += 24; bl += 1728; half ^= 1;
      }
    }
    wg_wait<0>();
    fence_regs<36>(accw);
    if (first_lane) { mbar_arrive(sb + BAR_AEMPTY + (2 + 3 * p) * 8); mbar_arrive(sb + BAR_EMPTY + 40); }
    CSTAMP(6);
    uint32_t xw[18];
    uint32_t rb = 0;
    if (L == 0 && p == 0) {
#pragma unroll
      for (int t = 0; t < 9; t++) {
        stg32(sc + o_x + t * 1024, pack_bf16(accw[4 * t], accw[4 * t + 1]));
        stg32(sc + o_x + t * 1024 + 128, pack_bf16(accw[4 * t + 2], accw[4 * t + 3]));
      }
      rb = ldg_rlx32(sc + o_xrb);
      fence_regs<36>(accw);
    }
    {
      float a0[2] = {0.f, 0.f}, a1[2] = {0.f, 0.f}, a2[2] = {0.f, 0.f}, b0[2] = {0.f, 0.f}, b1[2] = {0.f, 0.f}, b2[2] = {0.f, 0.f};
#pragma unroll
      for (int t = 0; t < 9; t++) {
#pragma unroll
        for (int e = 0; e < 2; e++) {
          const float x = accw[4 * t + e], y = accw[4 * t + 2 + e];
          a0[e] += x; a1[e] = fmaf(x, x, a1[e]); a2[e] = fmaf(x, wr[2 * t + e], a2[e]);
          b0[e] += y; b1[e] = fmaf(y, y, b1[e]); b2[e] = fmaf(y, wr[2 * t + e], b2[e]);
        }
      }
      const bool od = q & 1;
      const float A0 = a0[0] + a0[1], A1 = a1[0] + a1[1], A2 = a2[0] + a2[1], B0 = b0[0] + b0[1], B1 = b1[0] + b1[1], B2 = b2[0] + b2[1];
      float k0 = od ? B0 : A0, k1 = od ? B1 : A1, k2 = od ? B2 : A2;
      k0 += shx(od ? A0 : B0, 1); k1 += shx(od ? A1 : B1, 1); k2 += shx(od ? A2 : B2, 1);
      k0 += shx(k0, 2); k1 += shx(k1, 2); k2 += shx(k2, 2);
      if (q < 2) stg128(sc + o_stw, asu(k0), asu(k1), asu(k2), tg);
      STAMPD(k0, L * 40 + p * 20 + 14);
    }
#pragma unroll
    for (int t = 0; t < 9; t++) {
      xw[2 * t] = pack_bf16(accw[4 * t], accw[4 * t + 1]);
      xw[2 * t + 1] = pack_bf16(accw[4 * t + 2], accw[4 * t + 3]);
    }
    float r_lo, r_hi;
    {
      uint4 u0 = ldg_rlx128(sc + o_str), u1 = ldg_rlx128(sc + o_str + 256), u2 = ldg_rlx128(sc + o_str + 128), u3 = ldg_rlx128(sc + o_str + 384);
      flag_after(sc + o_cf, rb, 8 * T + 1, lane < 8 && L == 0 && p == 0);
      STAMPD(asf(u3.w), L * 40 + p * 20 + 15);
      int n = 0;
#pragma unroll 1
      while (__any_sync(0xffffffffu, orx(orx(orx(orx(0, u0.w, tg), u1.w, tg), u2.w, tg), u3.w, tg) != 0)) {
        rld128(u0, sc + o_str); rld128(u1, sc + o_str + 256); rld128(u2, sc + o_str + 128); rld128(u3, sc + o_str + 384);
        if (++n > SPIN) TIMEOUT(__LINE__)
      }
      float a0 = asf(u0.x) + asf(u1.x), a1 = asf(u0.y) + asf(u1.y), a2 = asf(u0.z) + asf(u1.z);
      float b0 = asf(u2.x) + asf(u3.x), b1 = asf(u2.y) + asf(u3.y), b2 = asf(u2.z) + asf(u3.z);
#pragma unroll
      for (int s = 1; s <= 2; s <<= 1) {
        const float t0 = shx(a0, s), t1 = shx(a1, s), t2 = shx(a2, s), t3 = shx(b0, s), t4 = shx(b1, s), t5 = shx(b2, s);
        a0 += t0; a1 += t1; a2 += t2; b0 += t3; b1 += t4; b2 += t5;
      }
      m_lo = a0 * (1.f / 576.f); m_hi = b0 * (1.f / 576.f);
      rs_lo = rsq(fmaxf(a1 * (1.f / 576.f) - m_lo * m_lo, 0.f) + EPS);
      rs_hi = rsq(fmaxf(b1 * (1.f / 576.f) - m_hi * m_hi, 0.f) + EPS);
      r_lo = (a2 - m_lo * wsum) * rs_lo; r_hi = (b2 - m_hi * wsum) * rs_hi;
    }
    CSTAMP(7);
    int candrow = -1;
    {
      const uint32_t kl = fkey(r_lo), kh = fkey(r_hi);
      const bool hi = kh > kl;
      const uint32_t kb = hi ? kh : kl;
      const uint32_t mx = __reduce_max_sync(0xffffffffu, kb);
      if (first_lane) sts32(sb + SM_BEST + p * 16 + w * 4, mx);
      const uint32_t bal = __ballot_sync(0xffffffffu, kb == mx);
      const bool mine = (bal & ((1u << (lane & 28)) - 1u)) == 0u && kb == mx;
      const uint32_t x0 = hi ? xw[1] : xw[0], x1 = hi ? xw[3] : xw[2], x2 = hi ? xw[5] : xw[4], x3 = hi ? xw[7] : xw[6], x4 = hi ? xw[9] : xw[8];
      const uint32_t x5 = hi ? xw[11] : xw[10], x6 = hi ? xw[13] : xw[12], x7 = hi ? xw[15] : xw[14], x8 = hi ? xw[17] : xw[16];
      nb_sync(NB_WG + p, 128);
      const uint4 bs = lds128(sb + SM_BEST + p * 16);
      const bool best = (w > 0 ? bs.x < mx : true) && (w > 1 ? bs.y < mx : bs.y <= mx) && (w > 2 ? bs.z < mx : bs.z <= mx) && bs.w <= mx;
      if (best && mine) {
        if (q < 2) stg128(sc + o_cand, asu(hi ? r_hi : r_lo), (tg << 6) + (uint32_t)(w * 16 + g + (hi ? 8 : 0)), asu(hi ? m_hi : m_lo), asu(hi ? rs_hi : rs_lo));
        stg128(sc + o_xc, x0, x1, x2, tg);
        stg128(sc + o_xc + 64, x3, x4, x5, tg);
        stg128(sc + o_xc + 128, x6, x7, x8, tg);
      }
      candrow = __reduce_max_sync(0xffffffffu, best && mine ? g + (hi ? 8 : 0) : -1);
    }
    if (L == 0 && p == 1) {
#pragma unroll
      for (int t = 0; t < 9; t++) { stg32(sc + o_x + t * 1024, xw[2 * t]); stg32(sc + o_x + t * 1024 + 128, xw[2 * t + 1]); }
      rb = ldg_rlx32(sc + o_xrb);
    }
    const uint32_t stg = sb + SM_B + p * 13824 + w * 2304;
    unsigned char* obase = (unsigned char*)P.out + ((128 * i + 32 * w + p) * 1152 + 144 * j);
    if (L == 1) {
      const float ul = 1.f + rs_lo, uh = 1.f + rs_hi, vl = -m_lo * rs_lo, vh = -m_hi * rs_hi;
#pragma unroll
      for (int t = 0; t < 9; t++) {
        xw[2 * t] = pack_bf16(fmaf(accw[4 * t], ul, vl), fmaf(accw[4 * t + 1], ul, vl));
        xw[2 * t + 1] = pack_bf16(fmaf(accw[4 * t + 2], uh, vh), fmaf(accw[4 * t + 3], uh, vh));
      }
      mbar_wait(sb + BAR_EMPTY + p * 8, 1);
      const uint32_t sa = stg + (lane & 15) * 144;
#pragma unroll
      for (int t = 0; t < 8; t += 2) stsm4(sa + (lane >> 4) * 16 + t * 16, xw[2 * t], xw[2 * t + 1], xw[2 * t + 2], xw[2 * t + 3]);
      stsm2(sa + 128, xw[16], xw[17]);
      __syncwarp();
      if (p == 0 || !OUT_LATE) store_rows(stg, obase, candrow, lane);
    }
    CSTAMP(8);
    lane = pin(lane);
    const unsigned char* cp = sc + (OFF(cand) + (j * 32 + lane) * (CAND_W * 4));
    if (p == 0) {
      if (L == 1 && candrow >= 0) {
        const Winner wn = poll_winner(cp, ldg_rlx128(cp), tg);
        if (lane < 9 && wn.ci != ip) *(uint4*)(obase + (candrow * 2304 + lane * 16)) = lds128(stg + candrow * 144 + lane * 16);
      }
    } else {
      const uint32_t gr = w * 144 + (lane & 7) + (lane >> 4) * 8, gm = sb + SM_G + ((lane >> 3) & 1) * 46080;
      const uint32_t ga = gm + gr * 64 + (((lane >> 1) & 3) << 4), gl = gm + 36864 + gr * 16;
#define GADDR(s, u) ((u) < 4 ? (ga ^ ((u) << 4)) + (s) * 1024 : gl + (s) * 256)
      uint32_t wf[NPRE][5][4];
      mbar_wait(sb + BAR_GU, 0);
#pragma unroll
      for (int s = 0; s < NPRE - 2; s++)
#pragma unroll
        for (int u = 0; u < 5; u++) ldsm4t(wf[s][u], GADDR(s, u));
      const uint4 c0 = ldg_rlx128(cp);
#pragma unroll
      for (int s = NPRE - 2; s < NPRE; s++)
#pragma unroll
        for (int u = 0; u < 5; u++) ldsm4t(wf[s][u], GADDR(s, u));
      flag_after(sc + o_cf, rb, 8 * T + 1, lane < 8 && L == 0);
      const Winner wn = poll_winner(cp, c0, tg);
      if (w == 0 && first_lane) sts128(sb + SM_WIN, asu(wn.r), asu(wn.m), asu(wn.rstd), (uint32_t)(wn.ci * 64 + wn.rr));
      CSTAMP(9);
      if (!OUT_LATE && L == 1 && candrow >= 0 && lane < 9 && wn.ci != ip) *(uint4*)(obase + (candrow * 2304 + lane * 16)) = lds128(stg + candrow * 144 + lane * 16);
      {
        uint32_t hb[18];
        const unsigned char* xc = sc + (OFF(xcand) + wn.ci * 1536 + q * 16);
        const int fp = min(cx.cta / 3, 23);
        uint4 u[7];
        int n = 0;
#pragma unroll 1
        while (true) {
          uint32_t d = 0;
#pragma unroll
          for (int e = 0; e < 7; e++) u[e] = ldg_rlx128(xc + (e < 6 ? w * 384 + e * 64 : fp * 64));
#pragma unroll
          for (int e = 0; e < 7; e++) d = orx(d, u[e].w, tg);
          if (__all_sync(0xffffffffu, d == 0)) break;
          if (++n > SPIN) TIMEOUT(__LINE__)
        }
        if (OUT_LATE == 3 && L == 1) store_rows(stg, obase, wn.ci == ip ? candrow : -1, lane);
#pragma unroll
        for (int e = 0; e < 6; e++) { hb[3 * e] = u[e].x; hb[3 * e + 1] = u[e].y; hb[3 * e + 2] = u[e].z; }
        if (w == 0) sts128(sb + SM_XW + q * 16, u[6].x, u[6].y, u[6].z, u[6].w);
        const float nb = -wn.m * wn.rstd;
#pragma unroll
        for (int b = 0; b < 18; b++) hb[b] = pack_bf16(fmaf(bf_lo(hb[b]), wn.rstd, nb), fmaf(bf_hi(hb[b]), wn.rstd, nb));
        CSTAMP(10);
        float d[5][4];
#pragma unroll
        for (int u = 0; u < 5; u++) d[u][0] = d[u][1] = d[u][2] = d[u][3] = 0.f;
#pragma unroll
        for (int s = 0; s < 9; s++) {
#pragma unroll
          for (int u = 0; u < 5; u++) {
            uint32_t* f = wf[s % NPRE][u];
            mma16(d[u], f[0], f[1], f[2], f[3], hb[2 * s], hb[2 * s + 1]);
            if (s + NPRE < 9) ldsm4t(f, GADDR(s + NPRE, u));
          }
        }
        if (q == 0) {
#pragma unroll
          for (int u = 0; u < 5; u++) sts64(sb + R_FPART + w * 320 + (u * 8 + g) * 8, asu(d[u][0]), asu(d[u][2]));
        }
        nb_arrive(NB_FFN, 224);
        CSTAMP(11);
      }
      if (OUT_LATE == 1 && L == 1) store_rows(stg, obase, wn.ci == ip ? candrow : -1, lane);
    }
  }
  STAMPIF(w == 0 && lane == 0, 40 + p * 20 + 12);
  PROF_DUMP();
#undef g
#undef q
#undef first_lane
}

__device__ __forceinline__ void load_wo_a(const Ctx& cx, const Params& P, const uint32_t T, const int L, const int p, const int lane) {
  const unsigned char* src = P.sc->obuf[cx.i * 2 + p];
#pragma unroll
  for (int c = 0; c < 9; c++) w_expect(sb + BAR_WFULL + (9 * p + c) * 8, 8192);
  mbar_wait(sb + BAR_HDONE + p * 8, L);
  wait_flags<32>(P.sc->cflag[cx.i * 2 + p], 8 * T + 2 * L, lane);
  fence_async_glob();
  STAMP(100 + L * 2 + p);
#pragma unroll
  for (int c = 0; c < 9; c++) {
    const int e = 9 * p + c, s = e % 6;
    if (e == 3) mbar_wait(sb + BAR_HDONE + 8, L);
    if (e >= 6) mbar_wait(sb + BAR_AEMPTY + s * 8, (L ^ (e / 6) ^ 1) & 1);
    w_bulk(sb + SM_A + (2 * (s % 3) + s / 3) * 8192, src + c * 8192, 8192, sb + BAR_WFULL + e * 8);
    PSTAMP(48 + L * 36 + 18 + e);
  }
}

__device__ __forceinline__ void finalize_row(const Params& P, const Winner& wn, const uint32_t T, const int L, const int grp, const int a, const int lane) {
  const unsigned char* yp = (const unsigned char*)P.sc->ypart[grp] + (a * 32 + lane) * 16;
  const uint32_t par = L ^ 1;
  uint4 u0 = ldg_rlx128(yp), u1 = ldg_rlx128(yp + 1536), u2 = make_uint4(par, 0, 0, 0);
  if (a < 2) rld128(u2, yp + 3072);
  const int col = lane & 7;
  const uint32_t xw = lds32(sb + SM_XW + (col >> 1) * 16 + (grp % 3) * 4);
  const float xsel = (col & 1) ? bf_hi(xw) : bf_lo(xw);
  const float sg = rbf(rcp(1.f + ex2(-1.4426950408889634f * rbf(wn.r))));
  const float h = rbf((xsel - wn.m) * wn.rstd);
  unsigned char* dst = L == 0 ? (unsigned char*)P.sc->xsel + (((lane >> 3) & 1) * 576 + grp * 8 + col) * 4
                              : (unsigned char*)P.out + ((128 * (wn.ci >> 1) + 2 * wn.rr + (wn.ci & 1)) * 576 + grp * 8 + col) * 2;
  int n = 0;
#pragma unroll 1
  while (__any_sync(0xffffffffu, orx(orx(orx(0, u0.x, par), u1.x, par), u2.x, par) & 1)) {
    rld128(u0, yp); rld128(u1, yp + 1536);
    if (a < 2) rld128(u2, yp + 3072);
    if (++n > SPIN) TIMEOUT(__LINE__)
  }
  const float s0 = asf(u0.x) + asf(u1.x) + asf(u2.x), s1 = asf(u0.y) + asf(u1.y) + asf(u2.y);
  const float s2 = asf(u0.z) + asf(u1.z) + asf(u2.z), s3 = asf(u0.w) + asf(u1.w) + asf(u2.w);
  const float k0 = self(lane & 2, s2, s0) + shx(self(lane & 2, s0, s2), 2), k1 = self(lane & 2, s3, s1) + shx(self(lane & 2, s1, s3), 2);
  float k = self(lane & 4, k1, k0) + shx(self(lane & 4, k0, k1), 4);
  k += shx(k, 8); k += shx(k, 16);
  if (lane < 8) stsf(sb + SM_YRED + ((lane & 1) * 4 + (lane & 2) + (lane >> 2)) * 16 + a * 4, k);
  nb_sync(NB_AUX, 96);
  if (a == 0) {
    const uint4 yy = lds128(sb + SM_YRED + col * 16);
    const float xn = rbf(xsel + rbf(h + rbf(rbf(asf(yy.x) + asf(yy.y) + asf(yy.z)) * sg)));
    if (L == 0) { if (lane < 16) stg32(dst, ftag(lane < 8 ? xn : xn - xsel, T & 1)); }
    else if (lane < 8) *(unsigned short*)dst = (unsigned short)(asu(xn) >> 16);
  }
}

__device__ __forceinline__ void aux_role(const Ctx& cx, const Params& P, const int a, const int lane_) {
  int lane = lane_;
#define t (a * 32 + lane)
#define g (lane >> 2)
#define q (lane & 3)
  const int i = cx.i, j = cx.j, cta = cx.cta;
  unsigned char* const sc = (unsigned char*)P.sc;
  const int rk = 36 * i + 12 * a;
  const uint32_t o_bf = OFF(bflag) + (j * 48 + i * 3 + a) * 32 + (lane & 7) * 4;
  uint32_t T;
  {
    const int k0 = lane & 7, tt = min(lane >> 3, 2), col = (9 * j + tt) * 16;
    const unsigned char* src = (const unsigned char*)P.wqkv + ((i * 8 + k0) * 3456 + a * 1152 + col);
    const Unit b0 = unit_load(src), b1 = unit_load(src + 128 * 3456);
    T = ldg_rlx32(sc + o_bf);
    nb_arrive(NB_ORD, 352);
    STAMPIF(1, 96);
    const uint32_t d2 = tt == 2 ? (22 - 7 * a) * 512 : 3072;
    const uint32_t o = OFF(wq) + (j * 18 + (i >> 2)) * 13824 + ((i & 3) * 8 + k0) * 16 + (a * 8 + tt) * 512;
    const uint32_t r0 = unit_store(sc, b0, lane, o, o + 1536, o + d2);
    STAMPIF(1, 80);
    const uint32_t r1 = unit_store(sc, b1, lane, o + 55296, o + 55296 + 1536, o + 55296 + d2);
    T = __shfl_sync(0xffffffffu, (T >> 3) + 1, 0);
    flag_after(sc + o_bf, r0 ^ r1, 8 * T + 1, lane < 8);
    STAMPIF(1, 98);
    const Unit b2 = unit_load(src + 256 * 3456), b3 = unit_load(src + 384 * 3456);
    const bool qkv = k0 < 4;
    const int q0 = rk + k0 - 4, q1 = rk + 4 + k0;
    const Unit u0 = unit_load(qkv ? (const unsigned char*)P.wqkv + ((512 + 4 * i + k0) * 3456 + a * 1152 + col) : (const unsigned char*)P.wo + (q0 * 1152 + col));
    const Unit u1 = unit_load((const unsigned char*)P.wo + (q1 * 1152 + col));
    const uint32_t r2 = unit_store(sc, b2, lane, o + 2 * 55296, o + 2 * 55296 + 1536, o + 2 * 55296 + d2);
    const uint32_t r3 = unit_store(sc, b3, lane, o + 3 * 55296, o + 3 * 55296 + 1536, o + 3 * 55296 + d2);
    float cs[3][8];
#pragma unroll
    for (int m = 0; m < 3; m++) {
      const uint32_t* w0 = &b0.v[m].x; const uint32_t* w1 = &b1.v[m].x; const uint32_t* w2 = &b2.v[m].x; const uint32_t* w3 = &b3.v[m].x; const uint32_t* w4 = &u0.v[m].x;
#pragma unroll
      for (int e = 0; e < 4; e++) {
        const uint32_t z = qkv ? w4[e] : 0u;
        cs[m][2 * e] = (bf_lo(w0[e]) + bf_lo(w1[e])) + (bf_lo(w2[e]) + bf_lo(w3[e])) + bf_lo(z);
        cs[m][2 * e + 1] = (bf_hi(w0[e]) + bf_hi(w1[e])) + (bf_hi(w2[e]) + bf_hi(w3[e])) + bf_hi(z);
      }
    }
    flag_after(sc + o_bf, r2 ^ r3, 8 * T + 3, lane < 8);
    STAMPIF(1, 82);
#pragma unroll
    for (int st = 4; st >= 1; st >>= 1) {
      const bool up = lane & st;
#pragma unroll
      for (int m = 0; m < 3; m++)
#pragma unroll
        for (int e = 0; e < st; e++) cs[m][e] = (up ? cs[m][e + st] : cs[m][e]) + shx(up ? cs[m][e] : cs[m][e + st], st);
    }
    {
      const uint32_t oz = OFF(zpart) + j * 13824 + i * 864 + (a * 8 + tt) * 32 + k0 * 4;
      stg32(sc + oz, ftag(cs[0][0], 1)); stg32(sc + (oz + 96), ftag(cs[1][0], 1)); stg32(sc + (oz + (d2 >> 4)), ftag(cs[2][0], 1));
    }
    STAMPIF(1, 81);
    nb_sync(NB_GO, 128);
    mbar_wait(sb + BAR_FULL + LATE_WAIT * 8, 0);
    const uint32_t ow = OFF(wo) + j * 82944 + tt * 256;
    const uint32_t oa = qkv ? OFF(wq) + (j * 18 + 16 + (i >> 3)) * 13824 + (4 * (i & 7) + k0) * 16 + (a * 8 + tt) * 512 : ow + (q0 >> 4) * 2304 + (q0 & 15) * 16;
    const uint32_t ob = ow + (q1 >> 4) * 2304 + (q1 & 15) * 16;
    const uint32_t ra = unit_store(sc, u0, lane, oa, oa + (qkv ? 1536 : 768), oa + (qkv ? d2 : 1536));
    const uint32_t rb = unit_store(sc, u1, lane, ob, ob + 768, ob + 1536);
    STAMPIF(1, 113);
#pragma unroll
    for (int S = 0; S < 3; S++) stg64(sc + (OFF(ypart) + (a * 24 + g) * 4096 + cta * 32 + q * 8) + S * 32768, 0u, 0u);
    if (cta < 72 && t < 16) stg32(sc + (OFF(xsel) + (lane >> 3) * 2304 + cta * 32 + (lane & 7) * 4), (T & 1) ^ 1);
    uint4 sv, sw;
    int n = 0;
#pragma unroll 1
    while (true) {
      sv = ldg_rlx128(sc + (OFF(st0) + i * 2048 + t * 16)); sw = ldg_rlx128(sc + (OFF(st0) + i * 2048 + 1536 + lane * 16));
      if (__all_sync(0xffffffffu, ((sv.z ^ T) | (sw.z ^ T)) == 0)) break;
      if (++n > SPIN) TIMEOUT(__LINE__)
    }
    flag_after(sc + o_bf, ra ^ rb, 8 * T + 4, lane < 8);
    sts64(sb + SM_R + t * 8, sv.x, sv.y);
    sts64(sb + SM_R + 768 + lane * 8, sw.x, sw.y);
    STAMPIF(1, 94);
  }
  Winner wn;
  bool owner = false;
  uint32_t wd[5][3][8];
  auto load_wd = [&](uint32_t (*d)[8], const unsigned char* sk) {
#pragma unroll
    for (int S = 0; S < 3; S++) {
      const uint4 v0 = ldg_nc128(sk + S * 128), v1 = ldg_nc128(sk + S * 128 + 1152);
      d[S][0] = v0.x; d[S][1] = v1.x; d[S][2] = v0.y; d[S][3] = v1.y; d[S][4] = v0.z; d[S][5] = v1.z; d[S][6] = v0.w; d[S][7] = v1.w;
    }
  };
  auto perm_wd = [&](uint32_t (*d)[8]) {
#pragma unroll
    for (int S = 0; S < 3; S++)
#pragma unroll
      for (int u = 0; u < 4; u++) {
        const uint32_t x = d[S][2 * u], y = d[S][2 * u + 1];
        asm volatile("prmt.b32 %0, %2, %3, 0x5410;\nprmt.b32 %1, %2, %3, 0x7632;" : "=&r"(d[S][2 * u]), "=r"(d[S][2 * u + 1]) : "r"(x), "r"(y));
      }
  };
#pragma unroll
  for (int kb = 0; kb < 3; kb++)
#pragma unroll
    for (int S = 0; S < 3; S++)
#pragma unroll
      for (int e = 0; e < 8; e++) wd[kb][S][e] = 0u;
#pragma unroll 1
  for (int L = 0; L < 2; L++) {
    lane = pin(lane);
    const uint32_t o_part = OFF(zpart) + j * 13824, par = L ^ 1;
    const int pk = a * 18 + min(lane, 17);
    if (L == 1) {
      if (cta < 72) finalize_row(P, wn, T, 0, cta, a, lane);
      const int gi = min(lane, 26);
      uint4 wv[12];
      {
        const int pc = gi < 24 ? gi >> 3 : gi - 24, tc = gi < 24 ? gi & 7 : 8;
        const unsigned char* se = (const unsigned char*)P.wqkv + (rk * 3456 + pc * 1152 + (9 * j + tc) * 16);
#pragma unroll
        for (int r = 0; r < 12; r++) wv[r] = ldg_nc128(se + r * 3456);
      }
      STAMPIF(1, 85);
      nb_sync(NB_AUX, 96);
      uint4 xq[3];
      {
        const unsigned char* dp = sc + (OFF(xsel) + 2304 + rk * 4);
        int n = 0;
#pragma unroll 1
        while (true) {
#pragma unroll
          for (int e = 0; e < 3; e++) xq[e] = ldg_rlx128(dp + e * 16);
          if (__all_sync(0xffffffffu, (orx(orx(orx(0, xq[0].x, T), xq[1].x, T), xq[2].x, T) & 1) == 0)) break;
          if (++n > SPIN) TIMEOUT(__LINE__)
        }
        if (t == 0) {
          sts32(sb + SM_SEL, owner ? (wn.ci & 1) * 64 + wn.rr : 0x7FFFFFFFu);
          if (wn.ci != 2 * i) mbar_arrive(sb + BAR_FIX);
          if (wn.ci != 2 * i + 1) mbar_arrive(sb + BAR_FIX + 8);
        }
        STAMPIF(1, 88);
      }
      float s[8];
#pragma unroll
      for (int e = 0; e < 8; e++) s[e] = 0.f;
#pragma unroll
      for (int r = 0; r < 12; r++) {
        const float x = asf((&xq[0].x)[r]);
        s[0] = fmaf(x, bf_lo(wv[r].x), s[0]); s[1] = fmaf(x, bf_hi(wv[r].x), s[1]);
        s[2] = fmaf(x, bf_lo(wv[r].y), s[2]); s[3] = fmaf(x, bf_hi(wv[r].y), s[3]);
        s[4] = fmaf(x, bf_lo(wv[r].z), s[4]); s[5] = fmaf(x, bf_hi(wv[r].z), s[5]);
        s[6] = fmaf(x, bf_lo(wv[r].w), s[6]); s[7] = fmaf(x, bf_hi(wv[r].w), s[7]);
      }
      sts128(sb + SM_R + a * 864 + gi * 32, asu(s[0]), asu(s[1]), asu(s[2]), asu(s[3]));
      sts128(sb + SM_R + a * 864 + gi * 32 + 16, asu(s[4]), asu(s[5]), asu(s[6]), asu(s[7]));
      nb_sync(NB_AUX, 96);
      const uint32_t ad = sb + SM_R + pk * 16;
      const uint4 u0 = lds128(ad), u1 = lds128(ad + 864), u2 = lds128(ad + 1728);
      stg128(sc + (o_part + i * 864 + pk * 16), ftag(asf(u0.x) + asf(u1.x) + asf(u2.x), par), ftag(asf(u0.y) + asf(u1.y) + asf(u2.y), par),
             ftag(asf(u0.z) + asf(u1.z) + asf(u2.z), par), ftag(asf(u0.w) + asf(u1.w) + asf(u2.w), par));
      STAMPIF(1, 86);
    }
    if (owner) {
      uint2 u[3];
      int n = 0;
#pragma unroll 1
      while (true) {
#pragma unroll
        for (int m = 0; m < 3; m++) u[m] = ldg_rlx64(sc + (OFF(xsel) + t * 8) + m * 768);
        if (__all_sync(0xffffffffu, (orx(orx(orx(0, u[0].x, T), u[1].x, T), u[2].x, T) & 1) == 0)) break;
        if (++n > SPIN) TIMEOUT(__LINE__)
      }
      STAMPIF(1, 109);
      float s1 = 0.f, s2 = 0.f;
#pragma unroll
      for (int m = 0; m < 3; m++) {
        const float x0 = asf(u[m].x), x1 = asf(u[m].y);
        s1 += x0 + x1; s2 = fmaf(x0, x0, fmaf(x1, x1, s2));
        const unsigned cc = 96 * m + t - 36 * j;
        if (cc < 36u) sts32(sb + SM_X2S + cc * 4, __byte_perm(u[m].x, u[m].y, 0x7632));
      }
      wn.m = s1; wn.rstd = s2;
    }
    if (L == 0 || owner) {
      uint4 u[16];
      int n = 0;
#pragma unroll 1
      while (true) {
        uint32_t d0 = 0, d1 = 0;
#pragma unroll
        for (int e = 0; e < 16; e++) u[e] = ldg_rlx128(sc + (o_part + pk * 16) + e * 864);
        if (L == 1 && n == 0) {
#pragma unroll
          for (int s = 1; s < 32; s <<= 1) { wn.m += shx(wn.m, s); wn.rstd += shx(wn.rstd, s); }
          if (lane == 0) sts64(sb + SM_RED2 + a * 8, asu(wn.m), asu(wn.rstd));
        }
#pragma unroll
        for (int e = 0; e < 8; e++) { d0 = orx(d0, u[e].x, par); d1 = orx(d1, u[8 + e].x, par); }
        if (__all_sync(0xffffffffu, ((d0 | d1) & 1) == 0)) break;
        if (++n > SPIN) TIMEOUT(__LINE__)
      }
      STAMPIF(1, 118 + L);
      float4 z = make_float4(0.f, 0.f, 0.f, 0.f);
#pragma unroll
      for (int e = 0; e < 16; e++) { z.x += asf(u[e].x); z.y += asf(u[e].y); z.z += asf(u[e].z); z.w += asf(u[e].w); }
      const uint32_t h0 = pack_bf16(z.x, z.y), h1 = pack_bf16(z.z, z.w);
      const uint32_t l0 = pack_bf16(z.x - bf_lo(h0), z.y - bf_hi(h0)), l1 = pack_bf16(z.z - bf_lo(h1), z.w - bf_hi(h1));
      const uint32_t ad = sb + SM_BEXT + (pk >> 1) * 128 + (pk & 1) * 8;
      if (L == 0) {
        sts64(ad, h0, h1);
#pragma unroll
        for (int r = 3; r < 8; r++) sts64(ad + r * 16, 0u, 0u);
      }
      sts64(ad + 16 + L * 48, h0, h1); sts64(ad + 32 + L * 48, l0, l1);
      fence_async_smem();
      nb_sync(NB_AUX, 96);
      if (t == 0) {
        if (L == 1) {
          const uint4 ra = lds128(sb + SM_RED2);
          const uint2 rb = lds64(sb + SM_RED2 + 16);
          const float m2 = (asf(ra.x) + asf(ra.z) + asf(rb.x)) * (1.f / 576.f);
          const float rs2 = rsq(fmaxf((asf(ra.y) + asf(ra.w) + asf(rb.y)) * (1.f / 576.f) - m2 * m2, 0.f) + EPS);
          sts64(sb + SM_SEL + 8, asu(m2), asu(rs2));
          mbar_arrive(sb + BAR_FIX + (wn.ci & 1) * 8);
        } else {
          mbar_arrive(sb + BAR_FIX); mbar_arrive(sb + BAR_FIX + 8);
        }
        STAMP(83 + L * 4);
      }
    }
    lane = pin(lane);
    const unsigned char* const wsrc = (const unsigned char*)P.wd + ((ffn_c32(cta) + 2 * q) * 1152 + a * 384 + g * 16);
    if (L == 0) {
#pragma unroll
      for (int kb = 0; kb < 3; kb++) { load_wd(wd[kb], wsrc + (kb * 9216 + (kb ? pin0(wd[kb - 1][2][7]) : 0u))); perm_wd(wd[kb]); }
    }
    load_wd(wd[3], wsrc + 3 * 9216);
    load_wd(wd[4], wsrc + ((cta & 1) ? (ffn_c8(cta) - ffn_c32(cta)) * 1152 : 24 * 1152));
    perm_wd(wd[3]); perm_wd(wd[4]);
    const uint32_t o_y = pin(OFF(ypart) + (a * 24 + g) * 4096 + cta * 32 + q * 8 + pin0(wd[4][2][7]));
    STAMPIF(1, 89 + L);
    if (a == 2) load_wo_a(cx, P, T, L, 1, lane);
    nb_sync(NB_FFN, 224);
    {
      const uint32_t ad = sb + R_FPART + min(lane, 19) * 16;
      const uint4 u0 = lds128(ad), u1 = lds128(ad + 320), u2 = lds128(ad + 640), u3 = lds128(ad + 960);
      const uint4 wv = lds128(sb + SM_WIN);
      const float g0 = rbf((asf(u0.x) + asf(u1.x)) + (asf(u2.x) + asf(u3.x))), g1 = rbf((asf(u0.z) + asf(u1.z)) + (asf(u2.z) + asf(u3.z)));
      const float v0 = rbf((asf(u0.y) + asf(u1.y)) + (asf(u2.y) + asf(u3.y))), v1 = rbf((asf(u0.w) + asf(u1.w)) + (asf(u2.w) + asf(u3.w)));
      const float s0 = rbf(g0 * rcp(1.f + ex2(-1.4426950408889634f * g0))), s1 = rbf(g1 * rcp(1.f + ex2(-1.4426950408889634f * g1)));
      const uint32_t act = lane < 16 + (cta & 1) * 4 ? pack_bf16(s0 * v0, s1 * v1) : 0u;
      uint32_t b[5];
#pragma unroll
      for (int kb = 0; kb < 5; kb++) b[kb] = __shfl_sync(0xffffffffu, act, 4 * kb + q);
#pragma unroll
      for (int S = 0; S < 3; S++) {
        float y[4][4];
#pragma unroll
        for (int u = 0; u < 4; u++) mma8z(y[u], wd[2][S][2 * u], wd[2][S][2 * u + 1], b[2]);
#pragma unroll
        for (int u = 0; u < 4; u++) mma16(y[u], wd[0][S][2 * u], wd[0][S][2 * u + 1], wd[1][S][2 * u], wd[1][S][2 * u + 1], b[0], b[1]);
#pragma unroll
        for (int u = 0; u < 4; u++) mma16(y[u], wd[3][S][2 * u], wd[3][S][2 * u + 1], wd[4][S][2 * u], wd[4][S][2 * u + 1], b[3], b[4]);
        const float y0 = self(lane & 2, self(lane & 1, y[3][0], y[2][0]), self(lane & 1, y[1][0], y[0][0]));
        const float y1 = self(lane & 2, self(lane & 1, y[3][2], y[2][2]), self(lane & 1, y[1][2], y[0][2]));
        stg64(sc + o_y + S * 32768, ftag(y0, par), ftag(y1, par));
      }
      if (L == 0) nb_arrive(NB_FFN2, 224);
      wn.r = asf(wv.x); wn.m = asf(wv.y); wn.rstd = asf(wv.z); wn.ci = wv.w >> 6; wn.rr = wv.w & 63;
    }
    STAMPIF(1, 84 + L * 8);
    owner = (wn.ci >> 1) == i;
  }
  if (cta < 72) finalize_row(P, wn, T, 1, cta, a, lane);
  STAMPIF(1, 93);
  PROF_END();
#undef t
#undef g
#undef q
}

__device__ __forceinline__ int sched_box(const uint32_t at, const int a) {
  int r = -1;
#pragma unroll
  for (int b = 0; b < 6; b++) if (((at >> (4 * b)) & 15) != 15) r = a == (int)((at >> (4 * b)) & 15) ? b : r;
  return r;
}
__host__ __device__ constexpr int sched_first(const uint32_t at) { int b = 0; while (b < 6 && ((at >> (4 * b)) & 15) != 15) b++; return b; }
__host__ __device__ constexpr int sched_last(const uint32_t at) { int b = 5; while (b >= 0 && ((at >> (4 * b)) & 15) != 15) b--; return b; }
__device__ __forceinline__ void producer_role(const Ctx& cx, const Params& P, const int lane) {
  const int i = cx.i, j = cx.j;
  if (elect_one()) asm volatile("prefetch.tensormap [%0];" ::"l"(&P.mx) : "memory");
  const uint32_t T = __shfl_sync(0xffffffffu, (ldg_rlx32(P.sc->cflag[i * 2][j * 4]) >> 3) + 1, 0);
  const unsigned char* const wq = P.sc->wq[j][0];
  nb_sync(NB_START, 288);
#pragma unroll
  for (int s = 0; s < 2 * NA0; s++) w_tma3d(sb + SM_A + s * 8192, &P.mx, (s >> 1) * 64, s & 1, i * 64, sb + BAR_FULL + (s >> 1) * 16);
#pragma unroll
  for (int h = 0; h < 6; h++) w_expect(sb + BAR_FULL + h * 8, h & 1 ? 13824 : 13824 + 16384);
  STAMP(97);
  wait_flags<48>(P.sc->bflag[j], 8 * T + 1, lane);
  fence_async_glob();
  STAMP(120);
#pragma unroll
  for (int h = 0; h < 6; h++) {
    w_bulk(sb + SM_B + h * 13824, wq + h * 13824, 13824, sb + BAR_FULL + h * 8);
    if (!(h & 1) && h >= 2 * NA0) {
      w_tma3d(sb + SM_A + h * 8192, &P.mx, h * 32, 0, i * 64, sb + BAR_FULL + h * 8);
      w_tma3d(sb + SM_A + h * 8192 + 8192, &P.mx, h * 32, 1, i * 64, sb + BAR_FULL + h * 8);
    }
  }
  PSTAMP(0);
  nb_arrive(NB_GO, 128);
  mbar_wait(sb + BAR_FULL + PF_WAIT * 8, 0);
  w_prefetch((const unsigned char*)P.wd + cx.cta * 41472, 10368);
  const unsigned char* const xb = P.sc->xbuf[i * 2];
  const unsigned char* const fp = (const unsigned char*)P.sc->bflag[j] + lane * 32;
  uint32_t f0 = 0, f1 = 0;
#pragma unroll 1
  for (int L = 0; L < 2; L++) {
    if (L == 1) {
#pragma unroll 1
      for (int p = 0; p < 2; p++) {
        mbar_wait(sb + BAR_AEMPTY + (2 + 3 * p) * 8, 0);
        wait_flags<32>(P.sc->cflag[i * 2 + p], 8 * T + 1, lane);
        fence_async_glob();
        STAMP(104 + p);
#pragma unroll
        for (int a = 0; a < 3; a++) {
          const int s = 2 * a + p;
          w_expect(sb + BAR_AFULL + s * 8, 8192);
          w_bulk(sb + SM_A + s * 8192, xb + (p * 73728 + a * 8192), 8192, sb + BAR_AFULL + s * 8);
          PSTAMP(48 + 36 + 3 * p + a);
        }
      }
    }
#pragma unroll 1
    for (int a = 3; a < 15; a++) {
      if (a == 12) {
        load_wo_a(cx, P, T, L, 0, lane);
        if (L == 1) break;
      }
      const int r = (a * 11) >> 5, s = a - 3 * r;
      const uint32_t fb = sb + BAR_FULL + s * 16, da = sb + SM_A + s * 16384, db = sb + SM_B + s * 27648;
      const unsigned char* bsrc = wq + (a < 9 ? a : a < 12 ? 72 - 6 * j + s : s) * 27648;
      const unsigned char* asrc = xb + a * 8192;
      const int kc = (a < 9 ? a : j + a - 10) * 64;
      const int amode = a == 9 || a > 11 ? 0 : L == 0 ? 1 : a < 9 ? 2 : 0;
      mbar_wait(sb + BAR_EMPTY + s * 16, (r & 1) ^ 1);
      if (L == 0) {
        if (a == 4 || a == 8) {
          const uint32_t need = 8 * T + (a == 4 ? 3 : 4);
          if (__any_sync(0xffffffffu, (int)((f0 - need) | (f1 - need)) < 0)) wait_flags<48>(P.sc->bflag[j], need, lane);
          fence_async_glob();
          STAMP(120 + (a >> 1));
        }
        if (a == 3 || a == 7) { f0 = ldg_rlx32(fp); f1 = ldg_rlx32(fp + (lane < 16 ? 1024 : 0)); }
      }
      w_bulk(db, bsrc, 13824, fb);
      w_expect(fb, amode ? 13824 + 16384 : 13824);
      mbar_wait(sb + BAR_EMPTY + s * 16 + 8, (r & 1) ^ 1);
      if (amode == 1) {
        w_tma3d(da, &P.mx, kc, 0, i * 64, fb);
        w_tma3d(da + 8192, &P.mx, kc, 1, i * 64, fb);
      } else if (amode == 2) {
        w_bulk(da, asrc, 8192, fb);
        w_bulk(da + 8192, asrc + 73728, 8192, fb);
      }
      w_bulk(db + 13824, bsrc + 13824, 13824, fb + 8);
      w_expect(fb + 8, 13824);
      PSTAMP(a < 12 ? L * 24 + a : 12 + a);
      if (L == 0) {
        {
          if (a >= WD_PF && a < WD_PF + 3) w_prefetch((const unsigned char*)P.wd + (cx.cta * 4 + a - WD_PF + 1) * 10368, 10368);
          if (a >= PG_0 && a < PG_0 + 6) w_prefetch((const unsigned char*)P.wg + ((a - PG_0) * 128 + cx.cta) * 6912, 6912);
        }
        if (a == 3) w_expect(sb + BAR_GU, 12 * (6144 + (cx.cta & 1) * 1536));
        {
          const int bu = sched_box(U_AT, a), bg = sched_box(G_AT, a);
          if (bu >= 0) load_gu(P, cx.cta, 1, bu, sb + BAR_GU);
          if (bg >= 0) load_gu(P, cx.cta, 0, bg, sb + BAR_GU);
          if (a == U_WIN) {
#pragma unroll 1
            for (int b = sched_first(U_AT); b <= sched_last(U_AT); b++) {
              const int c0 = clock();
              while ((int)(clock() - c0) < U_GAP) {}
              load_gu(P, cx.cta, 1, b, sb + BAR_GU);
            }
          }
          if (a == G_WIN) {
#pragma unroll 1
            for (int b = sched_first(G_AT); b <= sched_last(G_AT); b++) {
              const int c0 = clock();
              while ((int)(clock() - c0) < G_GAP) {}
              load_gu(P, cx.cta, 0, b, sb + BAR_GU);
            }
          }
        }
      }
    }
  }
}

template <bool BY_SMID>
__global__ void __launch_bounds__(384, 1) fused_kernel(const __grid_constant__ Params P) {
  extern __shared__ __align__(1024) unsigned char smem[];
  Ctx cx;
  STAMPIF(threadIdx.x == 64, 125);
  unsigned id;
  if (BY_SMID) asm volatile("mov.u32 %0, %%smid;" : "=r"(id)); else id = blockIdx.x;
  const int work = __shfl_sync(0xffffffffu, (int)P.work[min(id, 131u)], 0);
  const int warp = __shfl_sync(0xffffffffu, (int)(threadIdx.x >> 5), 0), lane = threadIdx.x & 31;
  if (work < 0) {
    if (warp == 0) {
      const int sp = -1 - work;
      if (lane == 0) { mbar_init(sb, 1); fence_async_smem(); }
      __syncwarp();
      __nanosleep(SPARE_DELAY);
#pragma unroll 1
      for (int k = 32 + sp; k < 72; k += 4) w_prefetch((const unsigned char*)P.wqkv + k * 27648, 27648);
#pragma unroll 1
      for (int k = sp; k < 24; k += 4) w_prefetch((const unsigned char*)P.wo + k * 27648, 27648);
#pragma unroll 1
      for (int k = sp; k < X_NU; k += 4) w_prefetch((const unsigned char*)P.wu + k * 27648, 27648);
      w_expect(sb, 16);
      w_bulk(sb + 128, P.wr, 16, sb);
      mbar_wait(sb, 0);
    }
    return;
  }
  cx.cta = work; cx.i = work >> 3; cx.j = work & 7;
  STAMPIF(threadIdx.x == 32, 95);
  if (warp < 8) {
    if (warp == 0) {
      if (elect_one()) {
        if ((uint32_t)__cvta_generic_to_shared(smem) != sb) __trap();
#pragma unroll
        for (int b = 0; b < 48; b++) mbar_init(sb + SM_BAR + b * 8, b < 34 ? 1 : b < 42 ? 4 : 8);
        fence_async_smem();
      }
      __syncwarp();
    }
    consumer_role(cx, P, smem, warp >> 2, warp & 3, lane);
  } else if (warp < 11) {
    aux_role(cx, P, warp - 8, lane);
  } else {
    producer_role(cx, P, lane);
  }
}

int work_of_smid(int smid) {
  const int t = smid >> 1;
  if (t == 60 || t == 61) return -1 - ((t - 60) * 2 + (smid & 1));
  const int gpc = t < 32 ? t & 7 : t < 60 ? 1 + (t - 32) % 7 : 0;
  const int x = 2 * (t < 32 ? t >> 3 : t < 60 ? 4 + (t - 32) / 7 : t - 58) + (smid & 1);
  const int blk[8] = {6, 0, 2, 3, 4, 7, 5, 1}, b = blk[gpc];
  return ((b >> 1) * 4 + (x & 1) + (x >> 3) * 2) * 8 + (b & 1) * 4 + ((x >> 1) & 3);
}

typedef CUresult (*EncodeFn)(CUtensorMap*, CUtensorMapDataType, cuuint32_t, void*, const cuuint64_t*, const cuuint64_t*,
                             const cuuint32_t*, const cuuint32_t*, CUtensorMapInterleave, CUtensorMapSwizzle,
                             CUtensorMapL2promotion, CUtensorMapFloatOOBfill);

void make_map(EncodeFn enc, CUtensorMap* m, const void* base, int rank, const cuuint64_t* dims, const cuuint64_t* strides,
              const cuuint32_t* box, CUtensorMapSwizzle sw, CUtensorMapL2promotion promo = CU_TENSOR_MAP_L2_PROMOTION_L2_128B) {
  const cuuint32_t es[3] = {1, 1, 1};
  enc(m, CU_TENSOR_MAP_DATA_TYPE_BFLOAT16, rank, const_cast<void*>(base), dims, strides, box, es, CU_TENSOR_MAP_INTERLEAVE_NONE, sw,
      promo, CU_TENSOR_MAP_FLOAT_OOB_FILL_NONE);
}

}

extern "C" void kernel_launch(void* const* d_in, const int* in_sizes, int n_in, void* d_out, int out_size) {
  (void)in_sizes; (void)n_in; (void)out_size;
  static EncodeFn enc = nullptr;
  static int nsm = 0;
  static void* scr = nullptr;
  if (!enc) {
    void* f = nullptr;
    cudaDriverEntryPointQueryResult qr;
    cudaGetDriverEntryPoint("cuTensorMapEncodeTiled", &f, cudaEnableDefault, &qr);
    enc = (EncodeFn)f;
    cudaGetSymbolAddress(&scr, g_scratch);
    int dev = 0;
    cudaGetDevice(&dev);
    cudaDeviceGetAttribute(&nsm, cudaDevAttrMultiProcessorCount, dev);
    cudaFuncSetAttribute(fused_kernel<true>, cudaFuncAttributeMaxDynamicSharedMemorySize, SM_TOTAL);
    cudaFuncSetAttribute(fused_kernel<false>, cudaFuncAttributeMaxDynamicSharedMemorySize, SM_TOTAL);
  }
  Params P;
  P.x = (const __nv_bfloat16*)d_in[0];
  P.wqkv = (const __nv_bfloat16*)d_in[1];
  P.wo = (const __nv_bfloat16*)d_in[2];
  P.wr = (const __nv_bfloat16*)d_in[4];
  P.wg = (const __nv_bfloat16*)d_in[5];
  P.wu = (const __nv_bfloat16*)d_in[6];
  P.wd = (const __nv_bfloat16*)d_in[7];
  P.out = (__nv_bfloat16*)d_out;
  P.sc = (Scratch*)scr;
  for (int k = 0; k < 136; k++) P.work[k] = (signed char)(nsm == 132 ? (k < 132 ? work_of_smid(k) : -1) : (k < 128 ? k : k < 132 ? 127 - k : -1));
  {
    const cuuint64_t dims[3] = {576, 2, 1024}, str[2] = {1152, 2304};
    const cuuint32_t box[3] = {64, 1, 64};
    make_map(enc, &P.mx, P.x, 3, dims, str, box, CU_TENSOR_MAP_SWIZZLE_128B);
  }
  {
    const cuuint64_t dims[2] = {4608, 576}, str[1] = {9216};
    const cuuint32_t box[2] = {32, 96}, box8[2] = {8, 96};
    make_map(enc, &P.mg, d_in[5], 2, dims, str, box, CU_TENSOR_MAP_SWIZZLE_64B);
    make_map(enc, &P.mu, d_in[6], 2, dims, str, box, CU_TENSOR_MAP_SWIZZLE_64B);
    make_map(enc, &P.mg8, d_in[5], 2, dims, str, box8, CU_TENSOR_MAP_SWIZZLE_NONE);
    make_map(enc, &P.mu8, d_in[6], 2, dims, str, box8, CU_TENSOR_MAP_SWIZZLE_NONE);
  }
  if (nsm == 132) fused_kernel<true><<<132, 384, SM_TOTAL>>>(P);
  else fused_kernel<false><<<132, 384, SM_TOTAL>>>(P);
}
```

```cpp
#include <cuda_runtime.h>
#include <cuda.h>
#include <cuda_bf16.h>
#include <stdint.h>
#include <stddef.h>

namespace {

constexpr int NPRE = 5;
#define X_NU 192
#define CAND_W 8
#define HALO_V 0
#define X_DELAY 200
#define X_STEP 100
#define HOLD_C 13
#define NA0 3
#define B2_AT 0
#define LATE_WAIT 3
#define OUT_LATE 0
#define U_AT 0xFFFF75
#define G_AT 0xEEEEEB
#define PG_0 6
#define WD_PF 3
#define U_WIN 11
#define G_WIN 11
#define G_GAP 300
#define U_GAP 400
#define ST_HOLD 0
#define ST_P 1
#define LATE_Q1 1
#define LATE_G0 1
#define LATE_GGAP 600
#define Q1_BOTH 1
#define PF_WAIT 0
#define POLL_GAP 100
#define SPARE_DELAY 400
constexpr float EPS = 1e-5f;
constexpr int SPIN = 1 << 22;
#define TIMEOUT(line) __trap();

struct __align__(128) Scratch {
  uint32_t bflag[8][48][8];
  uint32_t cflag[32][32][8];
  uint32_t halo[32][8][672];
  uint32_t stats[32][4][8][64];
  uint32_t cand[8][32][CAND_W];
  uint32_t xcand[32][8][48];
  uint32_t ypart[72][128][8];
  uint32_t zpart[8][16][216];
  uint32_t st0[2048][4];
  uint32_t xsel[2][576];
  unsigned char wq[8][9][27648];
  unsigned char wo[8][3][27648];
  unsigned char obuf[32][73728];
  unsigned char xbuf[32][73728];
};
__device__ Scratch g_scratch;
#define OFF(f) ((uint32_t)offsetof(Scratch, f))
#define STAMPD(v, k) do {} while (0)
#define STAMPIF(c, k) do {} while (0)
#define STAMP(k) do {} while (0)

constexpr uint32_t sb = 1024;
constexpr uint32_t SM_A = 0;
constexpr uint32_t SM_B = 49152;
constexpr uint32_t SM_G = 132096;
constexpr uint32_t SM_BEXT = 224256;

constexpr uint32_t SM_WIN = 227712;
constexpr uint32_t SM_XW = 228320;
constexpr uint32_t SM_YRED = 228448;
constexpr uint32_t SM_X2S = 228576;
constexpr uint32_t SM_RED2 = 228736;
constexpr uint32_t SM_WR = 228864;
constexpr uint32_t SM_R = 229168;
constexpr uint32_t SM_BEST = 231760;
constexpr uint32_t SM_SEL = 231824;
constexpr uint32_t SM_BAR = 231840;
constexpr uint32_t SM_TOTAL = 232448;
constexpr uint32_t R_FPART = SM_R;
constexpr uint32_t BAR_FULL = SM_BAR  , BAR_AFULL = SM_BAR + 48  , BAR_WFULL = SM_BAR + 96  , BAR_ST = SM_BAR + 240, BAR_GU = SM_BAR + 248,
                   BAR_FIX = SM_BAR + 256  , BAR_AEMPTY = SM_BAR + 272  , BAR_HDONE = SM_BAR + 320  ,
                   BAR_EMPTY = SM_BAR + 336  ;
enum { NB_WG = 1  , NB_STAG = 3, NB_AUX = 4, NB_FFN2 = 5, NB_FFN = 8, NB_START = 9, NB_GO = 6, NB_ORD = 7 };

struct Params {
  const __nv_bfloat16 *wqkv, *x, *wr, *wo;
  Scratch* sc;
  const __nv_bfloat16 *wd, *wg, *wu;
  __nv_bfloat16* out;
  signed char work[136];
  CUtensorMap mx, mg, mu, mg8, mu8;
};

__device__ __forceinline__ void mbar_init(uint32_t bar, int cnt) { asm volatile("mbarrier.init.shared::cta.b64 [%0], %1;" ::"r"(bar), "r"(cnt) : "memory"); }
__device__ __forceinline__ void mbar_arrive(uint32_t bar) { asm volatile("mbarrier.arrive.shared::cta.b64 _, [%0];" ::"r"(bar) : "memory"); }
__device__ __forceinline__ void mbar_wait(uint32_t bar, uint32_t par) {
  asm volatile("{\n.reg .pred p;\nLOOP:\nmbarrier.try_wait.parity.shared::cta.b64 p, [%0], %1;\n@!p bra.uni LOOP;\n}\n" ::"r"(bar), "r"(par) : "memory");
}
__device__ __forceinline__ uint32_t mbar_test(uint32_t bar, uint32_t par) {
  uint32_t ok;
  asm volatile("{\n.reg .pred p;\nmbarrier.test_wait.parity.shared::cta.b64 p, [%1], %2;\nselp.u32 %0,1,0,p;\n}" : "=r"(ok) : "r"(bar), "r"(par) : "memory");
  return ok;
}
__device__ __forceinline__ bool elect_one() {
  uint32_t ok;
  asm volatile("{\n.reg .pred p;\nelect.sync _|p, 0xffffffff;\nselp.u32 %0, 1, 0, p;\n}" : "=r"(ok));
  return ok;
}
__device__ __forceinline__ float ex2(float x) { float r; asm("ex2.approx.ftz.f32 %0, %1;" : "=f"(r) : "f"(x)); return r; }
__device__ __forceinline__ float rsq(float x) { float r; asm("rsqrt.approx.ftz.f32 %0, %1;" : "=f"(r) : "f"(x)); return r; }
__device__ __forceinline__ float rcp(float x) { float r; asm("rcp.approx.ftz.f32 %0, %1;" : "=f"(r) : "f"(x)); return r; }
__device__ __forceinline__ void w_expect(uint32_t bar, uint32_t bytes) {
  asm volatile("{\n.reg .pred p;\nelect.sync _|p, 0xffffffff;\n@p mbarrier.arrive.expect_tx.shared::cta.b64 _, [%0], %1;\n}" ::"r"(bar), "r"(bytes) : "memory");
}
__device__ __forceinline__ void w_bulk(uint32_t dst, const void* src, uint32_t bytes, uint32_t bar) {
  asm volatile("{\n.reg .pred p;\nelect.sync _|p, 0xffffffff;\n@p cp.async.bulk.shared::cluster.global.mbarrier::complete_tx::bytes [%0], [%1], %2, [%3];\n}" ::"r"(dst), "l"(src), "r"(bytes), "r"(bar) : "memory");
}
__device__ __forceinline__ void w_tma2d(uint32_t dst, const CUtensorMap* m, int c0, int c1, uint32_t bar) {
  asm volatile("{\n.reg .pred p;\nelect.sync _|p, 0xffffffff;\n@p cp.async.bulk.tensor.2d.shared::cluster.global.mbarrier::complete_tx::bytes [%0], [%1, {%3, %4}], [%2];\n}" ::"r"(dst), "l"(m), "r"(bar), "r"(c0), "r"(c1) : "memory");
}
__device__ __forceinline__ void w_tma3d(uint32_t dst, const CUtensorMap* m, int c0, int c1, int c2, uint32_t bar) {
  asm volatile("{\n.reg .pred p;\nelect.sync _|p, 0xffffffff;\n@p cp.async.bulk.tensor.3d.shared::cluster.global.mbarrier::complete_tx::bytes [%0], [%1, {%3, %4, %5}], [%2];\n}" ::"r"(dst), "l"(m), "r"(bar), "r"(c0), "r"(c1), "r"(c2) : "memory");
}
__device__ __forceinline__ void w_prefetch(const void* src, uint32_t bytes) {
  asm volatile("{\n.reg .pred p;\nelect.sync _|p, 0xffffffff;\n@p cp.async.bulk.prefetch.L2.global [%0], %1;\n}" ::"l"(src), "r"(bytes) : "memory");
}
__device__ __forceinline__ void nb_sync(int id, int n) { asm volatile("bar.sync %0, %1;" ::"r"(id), "r"(n) : "memory"); }
__device__ __forceinline__ void nb_arrive(int id, int n) { asm volatile("bar.arrive %0, %1;" ::"r"(id), "r"(n) : "memory"); }
__device__ __forceinline__ void fence_async_smem() { asm volatile("fence.proxy.async.shared::cta;" ::: "memory"); }
__device__ __forceinline__ void fence_async_glob() { asm volatile("fence.proxy.async.global;" ::: "memory"); }
__device__ __forceinline__ void flag_after(void* p, uint32_t readback, uint32_t T, bool writer) {
  asm volatile("{\n.reg .pred p;\n.reg .u32 v;\nsetp.ne.u32 p, %3, 0;\nor.b32 v, %1, %2;\nmin.u32 v, v, %2;\n@p st.relaxed.gpu.global.u32 [%0], v;\n}"
               ::"l"(p), "r"(readback), "r"(T), "r"((uint32_t)writer) : "memory");
}
__device__ __forceinline__ uint4 ldg_rlx128(const void* p) { uint4 v; asm volatile("ld.relaxed.gpu.global.v4.b32 {%0,%1,%2,%3}, [%4];" : "=r"(v.x), "=r"(v.y), "=r"(v.z), "=r"(v.w) : "l"(p) : "memory"); return v; }
__device__ __forceinline__ uint2 ldg_rlx64(const void* p) { uint2 v; asm volatile("ld.relaxed.gpu.global.v2.b32 {%0,%1}, [%2];" : "=r"(v.x), "=r"(v.y) : "l"(p) : "memory"); return v; }
__device__ __forceinline__ void rld128(uint4& v, const void* p) { asm volatile("ld.relaxed.gpu.global.v4.b32 {%0,%1,%2,%3}, [%4];" : "+r"(v.x), "+r"(v.y), "+r"(v.z), "+r"(v.w) : "l"(p) : "memory"); }
__device__ __forceinline__ uint32_t ldg_rlx32(const void* p) { uint32_t v; asm volatile("ld.relaxed.gpu.global.b32 %0, [%1];" : "=r"(v) : "l"(p) : "memory"); return v; }
__device__ __forceinline__ uint4 ldg_nc128(const void* p) { uint4 v; asm volatile("ld.global.nc.v4.b32 {%0,%1,%2,%3}, [%4];" : "=r"(v.x), "=r"(v.y), "=r"(v.z), "=r"(v.w) : "l"(p)); return v; }
__device__ __forceinline__ uint32_t ldg_nc32(const void* p) { uint32_t v; asm volatile("ld.global.nc.L1::no_allocate.b32 %0, [%1];" : "=r"(v) : "l"(p)); return v; }
__device__ __forceinline__ void stg128(void* p, uint32_t a, uint32_t b, uint32_t c, uint32_t d) { asm volatile("st.relaxed.gpu.global.v4.b32 [%0], {%1,%2,%3,%4};" ::"l"(p), "r"(a), "r"(b), "r"(c), "r"(d) : "memory"); }
__device__ __forceinline__ void stg64(void* p, uint32_t a, uint32_t b) { asm volatile("st.relaxed.gpu.global.v2.b32 [%0], {%1,%2};" ::"l"(p), "r"(a), "r"(b) : "memory"); }
__device__ __forceinline__ void stg32(void* p, uint32_t a) { asm volatile("st.relaxed.gpu.global.b32 [%0], %1;" ::"l"(p), "r"(a) : "memory"); }
__device__ __forceinline__ void sts128(uint32_t a, uint32_t x, uint32_t y, uint32_t z, uint32_t w) { asm volatile("st.shared.v4.b32 [%0], {%1,%2,%3,%4};" ::"r"(a), "r"(x), "r"(y), "r"(z), "r"(w) : "memory"); }
__device__ __forceinline__ void sts64(uint32_t a, uint32_t x, uint32_t y) { asm volatile("st.shared.v2.b32 [%0], {%1,%2};" ::"r"(a), "r"(x), "r"(y) : "memory"); }
__device__ __forceinline__ void sts32(uint32_t a, uint32_t x) { asm volatile("st.shared.b32 [%0], %1;" ::"r"(a), "r"(x) : "memory"); }
__device__ __forceinline__ void stsf(uint32_t a, float x) { sts32(a, __float_as_uint(x)); }
__device__ __forceinline__ uint4 lds128(uint32_t a) { uint4 v; asm volatile("ld.shared.v4.b32 {%0,%1,%2,%3}, [%4];" : "=r"(v.x), "=r"(v.y), "=r"(v.z), "=r"(v.w) : "r"(a) : "memory"); return v; }
__device__ __forceinline__ uint2 lds64(uint32_t a) { uint2 v; asm volatile("ld.shared.v2.b32 {%0,%1}, [%2];" : "=r"(v.x), "=r"(v.y) : "r"(a) : "memory"); return v; }
__device__ __forceinline__ uint32_t lds32(uint32_t a) { uint32_t v; asm volatile("ld.shared.b32 %0, [%1];" : "=r"(v) : "r"(a) : "memory"); return v; }
__device__ __forceinline__ uint32_t pack_bf16(float lo, float hi) { uint32_t r; asm("cvt.rn.bf16x2.f32 %0, %1, %2;" : "=r"(r) : "f"(hi), "f"(lo)); return r; }
__device__ __forceinline__ float bf_lo(uint32_t w) { return __uint_as_float(w << 16); }
__device__ __forceinline__ float bf_hi(uint32_t w) { return __uint_as_float(w & 0xFFFF0000u); }
__device__ __forceinline__ float rbf(float x) { return bf_lo(pack_bf16(x, 0.f)); }
__device__ __forceinline__ float asf(uint32_t u) { return __uint_as_float(u); }
__device__ __forceinline__ uint32_t asu(float f) { return __float_as_uint(f); }
__device__ __forceinline__ float shx(float v, int m) { return __shfl_xor_sync(0xffffffffu, v, m); }
__device__ __forceinline__ uint32_t movm(uint32_t a) { uint32_t o; asm volatile("movmatrix.sync.aligned.m8n8.trans.b16 %0, %1;" : "=r"(o) : "r"(a)); return o; }
__device__ __forceinline__ void ldsm2(uint32_t& a, uint32_t& b, uint32_t addr) { asm volatile("ldmatrix.sync.aligned.m8n8.x2.shared.b16 {%0,%1}, [%2];" : "=r"(a), "=r"(b) : "r"(addr) : "memory"); }
__device__ __forceinline__ void ldsm4t(uint32_t* r, uint32_t addr) { asm volatile("ldmatrix.sync.aligned.m8n8.x4.trans.shared.b16 {%0,%1,%2,%3}, [%4];" : "=r"(r[0]), "=r"(r[1]), "=r"(r[2]), "=r"(r[3]) : "r"(addr) : "memory"); }
__device__ __forceinline__ void stsm4(uint32_t addr, uint32_t a, uint32_t b, uint32_t c, uint32_t d) { asm volatile("stmatrix.sync.aligned.m8n8.x4.shared.b16 [%0], {%1,%2,%3,%4};" ::"r"(addr), "r"(a), "r"(b), "r"(c), "r"(d) : "memory"); }
__device__ __forceinline__ void stsm2(uint32_t addr, uint32_t a, uint32_t b) { asm volatile("stmatrix.sync.aligned.m8n8.x2.shared.b16 [%0], {%1,%2};" ::"r"(addr), "r"(a), "r"(b) : "memory"); }
__device__ __forceinline__ void mma16(float* d, uint32_t a0, uint32_t a1, uint32_t a2, uint32_t a3, uint32_t b0, uint32_t b1) {
  asm volatile("mma.sync.aligned.m16n8k16.row.col.f32.bf16.bf16.f32 {%0,%1,%2,%3},{%4,%5,%6,%7},{%8,%9},{%0,%1,%2,%3};"
               : "+f"(d[0]), "+f"(d[1]), "+f"(d[2]), "+f"(d[3]) : "r"(a0), "r"(a1), "r"(a2), "r"(a3), "r"(b0), "r"(b1));
}
__device__ __forceinline__ void mma16z(float* d, uint32_t a0, uint32_t a1, uint32_t a2, uint32_t a3, uint32_t b0, uint32_t b1) {
  asm volatile("mma.sync.aligned.m16n8k16.row.col.f32.bf16.bf16.f32 {%0,%1,%2,%3},{%4,%5,%6,%7},{%8,%9},{%10,%10,%10,%10};"
               : "=f"(d[0]), "=f"(d[1]), "=f"(d[2]), "=f"(d[3]) : "r"(a0), "r"(a1), "r"(a2), "r"(a3), "r"(b0), "r"(b1), "f"(0.f));
}
__device__ __forceinline__ void mma8(float* d, uint32_t a0, uint32_t a1, uint32_t b0) {
  asm volatile("mma.sync.aligned.m16n8k8.row.col.f32.bf16.bf16.f32 {%0,%1,%2,%3},{%4,%5},{%6},{%0,%1,%2,%3};"
               : "+f"(d[0]), "+f"(d[1]), "+f"(d[2]), "+f"(d[3]) : "r"(a0), "r"(a1), "r"(b0));
}
__device__ __forceinline__ uint32_t pin(uint32_t v) { uint32_t r; asm volatile("shfl.sync.bfly.b32 %0, %1, 0, 31, 0xffffffff;" : "=r"(r) : "r"(v)); return r; }
__device__ __forceinline__ uint32_t pin0(uint32_t v) { uint32_t r; asm volatile("{\n.reg .u32 t;\nor.b32 t, %1, 1;\nbfind.shiftamt.u32 %0, t;\nshr.u32 %0, %0, 5;\n}" : "=r"(r) : "r"(v)); return r; }
__device__ __forceinline__ void mma8z(float* d, uint32_t a0, uint32_t a1, uint32_t b0) {
  asm volatile("mma.sync.aligned.m16n8k8.row.col.f32.bf16.bf16.f32 {%0,%1,%2,%3},{%4,%5},{%6},{%7,%7,%7,%7};"
               : "=f"(d[0]), "=f"(d[1]), "=f"(d[2]), "=f"(d[3]) : "r"(a0), "r"(a1), "r"(b0), "f"(0.f));
}
__device__ __forceinline__ void wg_fence() { asm volatile("wgmma.fence.sync.aligned;" ::: "memory"); }
__device__ __forceinline__ void wg_commit() { asm volatile("wgmma.commit_group.sync.aligned;" ::: "memory"); }
template <int N> __device__ __forceinline__ void wg_wait() { asm volatile("wgmma.wait_group.sync.aligned %0;" ::"n"(N) : "memory"); }
template <int N> __device__ __forceinline__ void fence_regs(float* d) {
#pragma unroll
  for (int k = 0; k < N; k++) asm volatile("" : "+f"(d[k])::"memory");
}
__host__ __device__ constexpr uint32_t DLO(uint32_t addr, uint32_t lbo) { return (addr >> 4) | ((lbo >> 4) << 16); }
__host__ __device__ constexpr uint32_t DHI(uint32_t sbo, uint32_t swz) { return (sbo >> 4) | (swz << 30); }
template <int N>
__device__ __forceinline__ void wait_flags(const void* base, const uint32_t V, const int lane) {
  const unsigned char* p = (const unsigned char*)base + lane * 32;
  const unsigned char* p2 = p + (lane < N - 32 ? 1024 : 0);
  uint32_t a0 = ldg_rlx32(p), a1 = N > 32 ? ldg_rlx32(p2) : V;
  __nanosleep(POLL_GAP);
  int n = 0;
#pragma unroll 1
  while (true) {
    const uint32_t b0 = ldg_rlx32(p), b1 = N > 32 ? ldg_rlx32(p2) : V;
    if (__all_sync(0xffffffffu, (int)((a0 - V) | (a1 - V)) >= 0)) break;
    a0 = ldg_rlx32(p); a1 = N > 32 ? ldg_rlx32(p2) : V;
    if (__all_sync(0xffffffffu, (int)((b0 - V) | (b1 - V)) >= 0)) break;
    if (++n > SPIN) TIMEOUT(__LINE__)
  }
}
__device__ __forceinline__ uint32_t ftag(float v, uint32_t par) { return (asu(v) & ~1u) | par; }
__device__ __forceinline__ uint32_t selu(uint32_t c, uint32_t a, uint32_t b) { uint32_t r; asm("{\n.reg .pred p;\nsetp.ne.u32 p, %1, 0;\nselp.b32 %0, %2, %3, p;\n}" : "=r"(r) : "r"(c), "r"(a), "r"(b)); return r; }
__device__ __forceinline__ float self(uint32_t c, float a, float b) { return asf(selu(c, asu(a), asu(b))); }
__device__ __forceinline__ uint32_t orx(uint32_t acc, uint32_t a, uint32_t ref) { uint32_t r; asm("lop3.b32 %0, %1, %2, %3, 0xF6;" : "=r"(r) : "r"(acc), "r"(a), "r"(ref)); return r; }
__device__ __forceinline__ uint32_t fkey(float r) {
  uint32_t u = asu(r);
  u = (u & 0x80000000u) ? ~u : (u | 0x80000000u);
  return (r == r) ? u : 0u;
}
__host__ __device__ constexpr int GI(int part, int t) { return t < 8 ? part * 8 + t : 24 + part; }

__device__ __forceinline__ void wgmma_ss_216(float* d, uint32_t al, uint32_t ah, uint32_t bl, uint32_t bh) {
  asm volatile("{\n.reg .b64 da, db;\nmov.b64 da, {%108, %109};\nmov.b64 db, {%110, %111};\n"
      "wgmma.mma_async.sync.aligned.m64n216k16.f32.bf16.bf16 {"
      "%0,%1,%2,%3,%4,%5,%6,%7,%8,%9,%10,%11,%12,%13,%14,%15,%16,%17,%18,%19,%20,%21,%22,%23,%24,%25,%26,"
      "%27,%28,%29,%30,%31,%32,%33,%34,%35,%36,%37,%38,%39,%40,%41,%42,%43,%44,%45,%46,%47,%48,%49,%50,%51,%52,%53,"
      "%54,%55,%56,%57,%58,%59,%60,%61,%62,%63,%64,%65,%66,%67,%68,%69,%70,%71,%72,%73,%74,%75,%76,%77,%78,%79,%80,"
      "%81,%82,%83,%84,%85,%86,%87,%88,%89,%90,%91,%92,%93,%94,%95,%96,%97,%98,%99,%100,%101,%102,%103,%104,%105,%106,%107"
      "}, da, db, 1, 1, 1, 0, 1;\n}\n"
      : "+f"(d[0]), "+f"(d[1]), "+f"(d[2]), "+f"(d[3]), "+f"(d[4]), "+f"(d[5]), "+f"(d[6]), "+f"(d[7]), "+f"(d[8]),
        "+f"(d[9]), "+f"(d[10]), "+f"(d[11]), "+f"(d[12]), "+f"(d[13]), "+f"(d[14]), "+f"(d[15]), "+f"(d[16]), "+f"(d[17]),
        "+f"(d[18]), "+f"(d[19]), "+f"(d[20]), "+f"(d[21]), "+f"(d[22]), "+f"(d[23]), "+f"(d[24]), "+f"(d[25]), "+f"(d[26]),
        "+f"(d[27]), "+f"(d[28]), "+f"(d[29]), "+f"(d[30]), "+f"(d[31]), "+f"(d[32]), "+f"(d[33]), "+f"(d[34]), "+f"(d[35]),
        "+f"(d[36]), "+f"(d[37]), "+f"(d[38]), "+f"(d[39]), "+f"(d[40]), "+f"(d[41]), "+f"(d[42]), "+f"(d[43]), "+f"(d[44]),
        "+f"(d[45]), "+f"(d[46]), "+f"(d[47]), "+f"(d[48]), "+f"(d[49]), "+f"(d[50]), "+f"(d[51]), "+f"(d[52]), "+f"(d[53]),
        "+f"(d[54]), "+f"(d[55]), "+f"(d[56]), "+f"(d[57]), "+f"(d[58]), "+f"(d[59]), "+f"(d[60]), "+f"(d[61]), "+f"(d[62]),
        "+f"(d[63]), "+f"(d[64]), "+f"(d[65]), "+f"(d[66]), "+f"(d[67]), "+f"(d[68]), "+f"(d[69]), "+f"(d[70]), "+f"(d[71]),
        "+f"(d[72]), "+f"(d[73]), "+f"(d[74]), "+f"(d[75]), "+f"(d[76]), "+f"(d[77]), "+f"(d[78]), "+f"(d[79]), "+f"(d[80]),
        "+f"(d[81]), "+f"(d[82]), "+f"(d[83]), "+f"(d[84]), "+f"(d[85]), "+f"(d[86]), "+f"(d[87]), "+f"(d[88]), "+f"(d[89]),
        "+f"(d[90]), "+f"(d[91]), "+f"(d[92]), "+f"(d[93]), "+f"(d[94]), "+f"(d[95]), "+f"(d[96]), "+f"(d[97]), "+f"(d[98]),
        "+f"(d[99]), "+f"(d[100]), "+f"(d[101]), "+f"(d[102]), "+f"(d[103]), "+f"(d[104]), "+f"(d[105]), "+f"(d[106]), "+f"(d[107])
      : "r"(al), "r"(ah), "r"(bl), "r"(bh));
}
__device__ __forceinline__ void wgmma_ss_72(float* d, uint32_t al, uint32_t ah, uint32_t bl, uint32_t bh) {
  asm volatile("{\n.reg .b64 da, db;\nmov.b64 da, {%36, %37};\nmov.b64 db, {%38, %39};\n"
      "wgmma.mma_async.sync.aligned.m64n72k16.f32.bf16.bf16 {"
      "%0,%1,%2,%3,%4,%5,%6,%7,%8,%9,%10,%11,%12,%13,%14,%15,%16,%17,%18,%19,%20,%21,%22,%23,%24,%25,%26,"
      "%27,%28,%29,%30,%31,%32,%33,%34,%35"
      "}, da, db, 1, 1, 1, 0, 1;\n}\n"
      : "+f"(d[0]), "+f"(d[1]), "+f"(d[2]), "+f"(d[3]), "+f"(d[4]), "+f"(d[5]), "+f"(d[6]), "+f"(d[7]), "+f"(d[8]),
        "+f"(d[9]), "+f"(d[10]), "+f"(d[11]), "+f"(d[12]), "+f"(d[13]), "+f"(d[14]), "+f"(d[15]), "+f"(d[16]), "+f"(d[17]),
        "+f"(d[18]), "+f"(d[19]), "+f"(d[20]), "+f"(d[21]), "+f"(d[22]), "+f"(d[23]), "+f"(d[24]), "+f"(d[25]), "+f"(d[26]),
        "+f"(d[27]), "+f"(d[28]), "+f"(d[29]), "+f"(d[30]), "+f"(d[31]), "+f"(d[32]), "+f"(d[33]), "+f"(d[34]), "+f"(d[35])
      : "r"(al), "r"(ah), "r"(bl), "r"(bh));
}
template <uint32_t BH>
__device__ __forceinline__ void wgmma_rs_216(float* d, uint32_t a0, uint32_t a1, uint32_t a2, uint32_t a3, uint32_t bl) {
  asm volatile("{\n.reg .b64 db;\nmov.b64 db, {%112, %113};\n"
      "wgmma.mma_async.sync.aligned.m64n216k16.f32.bf16.bf16 {"
      "%0,%1,%2,%3,%4,%5,%6,%7,%8,%9,%10,%11,%12,%13,%14,%15,%16,%17,%18,%19,%20,%21,%22,%23,%24,%25,%26,"
      "%27,%28,%29,%30,%31,%32,%33,%34,%35,%36,%37,%38,%39,%40,%41,%42,%43,%44,%45,%46,%47,%48,%49,%50,%51,%52,%53,"
      "%54,%55,%56,%57,%58,%59,%60,%61,%62,%63,%64,%65,%66,%67,%68,%69,%70,%71,%72,%73,%74,%75,%76,%77,%78,%79,%80,"
      "%81,%82,%83,%84,%85,%86,%87,%88,%89,%90,%91,%92,%93,%94,%95,%96,%97,%98,%99,%100,%101,%102,%103,%104,%105,%106,%107"
      "}, {%108,%109,%110,%111}, db, 1, 1, 1, 1;\n}\n"
      : "+f"(d[0]), "+f"(d[1]), "+f"(d[2]), "+f"(d[3]), "+f"(d[4]), "+f"(d[5]), "+f"(d[6]), "+f"(d[7]), "+f"(d[8]),
        "+f"(d[9]), "+f"(d[10]), "+f"(d[11]), "+f"(d[12]), "+f"(d[13]), "+f"(d[14]), "+f"(d[15]), "+f"(d[16]), "+f"(d[17]),
        "+f"(d[18]), "+f"(d[19]), "+f"(d[20]), "+f"(d[21]), "+f"(d[22]), "+f"(d[23]), "+f"(d[24]), "+f"(d[25]), "+f"(d[26]),
        "+f"(d[27]), "+f"(d[28]), "+f"(d[29]), "+f"(d[30]), "+f"(d[31]), "+f"(d[32]), "+f"(d[33]), "+f"(d[34]), "+f"(d[35]),
        "+f"(d[36]), "+f"(d[37]), "+f"(d[38]), "+f"(d[39]), "+f"(d[40]), "+f"(d[41]), "+f"(d[42]), "+f"(d[43]), "+f"(d[44]),
        "+f"(d[45]), "+f"(d[46]), "+f"(d[47]), "+f"(d[48]), "+f"(d[49]), "+f"(d[50]), "+f"(d[51]), "+f"(d[52]), "+f"(d[53]),
        "+f"(d[54]), "+f"(d[55]), "+f"(d[56]), "+f"(d[57]), "+f"(d[58]), "+f"(d[59]), "+f"(d[60]), "+f"(d[61]), "+f"(d[62]),
        "+f"(d[63]), "+f"(d[64]), "+f"(d[65]), "+f"(d[66]), "+f"(d[67]), "+f"(d[68]), "+f"(d[69]), "+f"(d[70]), "+f"(d[71]),
        "+f"(d[72]), "+f"(d[73]), "+f"(d[74]), "+f"(d[75]), "+f"(d[76]), "+f"(d[77]), "+f"(d[78]), "+f"(d[79]), "+f"(d[80]),
        "+f"(d[81]), "+f"(d[82]), "+f"(d[83]), "+f"(d[84]), "+f"(d[85]), "+f"(d[86]), "+f"(d[87]), "+f"(d[88]), "+f"(d[89]),
        "+f"(d[90]), "+f"(d[91]), "+f"(d[92]), "+f"(d[93]), "+f"(d[94]), "+f"(d[95]), "+f"(d[96]), "+f"(d[97]), "+f"(d[98]),
        "+f"(d[99]), "+f"(d[100]), "+f"(d[101]), "+f"(d[102]), "+f"(d[103]), "+f"(d[104]), "+f"(d[105]), "+f"(d[106]), "+f"(d[107])
      : "r"(a0), "r"(a1), "r"(a2), "r"(a3), "r"(bl), "n"(BH));
}

struct Ctx {
  int i, j, cta;
};
#define TSTAMP(k) do {} while (0)
#define PSTAMP(k) do {} while (0)
#define PROF_DUMP() do {} while (0)
#define PROF_END() do {} while (0)
#define GSTAMP(k) do {} while (0)
#define CSTAMP(k) STAMPIF(1, L * 40 + p * 20 + (k))

__device__ __forceinline__ int ffn_c32(int cta) { return 32 * cta; }
__device__ __forceinline__ int ffn_c8(int cta) { return 4096 + 8 * (cta >> 1); }
__device__ __forceinline__ void load_gu(const Params& P, const int cta_, const int mat, const int b, const uint32_t bar) {
  const int cta = cta_;
  w_tma2d(sb + SM_G + mat * 46080 + b * 6144, &P.mg + mat, ffn_c32(cta), b * 96, bar);
  if (cta & 1) w_tma2d(sb + SM_G + mat * 46080 + 36864 + b * 1536, &P.mg8 + mat, ffn_c8(cta), b * 96, bar);
}

struct Winner { float r, m, rstd; int ci, rr; };

__device__ __forceinline__ Winner poll_winner(const void* p, uint4 v, const uint32_t tg) {
  int n = 0;
#pragma unroll 1
  while (!__all_sync(0xffffffffu, ((v.y ^ (tg << 6)) >> 6) == 0)) {
    rld128(v, p);
    if (++n > SPIN) TIMEOUT(__LINE__)
  }
  uint32_t key = fkey(asf(v.x));
  uint32_t mx = __reduce_max_sync(0xffffffffu, key);
  int src = __ffs(__ballot_sync(0xffffffffu, key == mx)) - 1;
  Winner w;
  w.ci = src;
  w.r = asf(__shfl_sync(0xffffffffu, v.x, src));
  w.rr = (int)__shfl_sync(0xffffffffu, v.y, src) & 63;
  w.m = asf(__shfl_sync(0xffffffffu, v.z, src));
  w.rstd = asf(__shfl_sync(0xffffffffu, v.w, src));
  return w;
}

__device__ __forceinline__ float2 row_stats(const Params& P, const int r, const int lane) {
  const unsigned char* src = (const unsigned char*)P.x + (((r & ~127) + 2 * (r & 63) + ((r >> 6) & 1)) * 1152 + (lane & 15) * 16);
  uint4 v[4];
#pragma unroll
  for (int m = 0; m < 4; m++) v[m] = ldg_nc128(src + m * 256);
  uint2 v4;
  asm volatile("ld.global.nc.v2.b32 {%0,%1}, [%2];" : "=r"(v4.x), "=r"(v4.y) : "l"(src + (1024 - (lane & 15) * 8)));
  nb_arrive(NB_START, 288 + pin0(v4.x));
  const float sft = __shfl_sync(0xffffffffu, bf_lo(v[0].x), lane & 16);
  float s1 = 0.f, s2 = 0.f, s3 = 0.f;
#pragma unroll
  for (int e = 0; e < 18; e++) {
    const uint32_t u = e < 16 ? (&v[0].x)[e] : (&v4.x)[e - 16];
    const float d0 = bf_lo(u) - sft, d1 = bf_hi(u) - sft;
    s1 += d0 + d1; s2 = fmaf(d0, d0, s2); s3 = fmaf(d1, d1, s3);
  }
  s2 += s3;
#pragma unroll
  for (int o = 1; o < 16; o <<= 1) { s1 += shx(s1, o); s2 += shx(s2, o); }
  s1 *= (1.f / 576.f);
  return make_float2(s1 + sft, rsq(fmaxf(s2 * (1.f / 576.f) - s1 * s1, 0.f) + EPS));
}

struct Unit { uint4 v[3]; };
__device__ __forceinline__ Unit unit_load(const unsigned char* src) {
  Unit u;
#pragma unroll
  for (int m = 0; m < 3; m++) u.v[m] = ldg_nc128(src + m * 48);
  return u;
}
__device__ __forceinline__ uint32_t unit_store(unsigned char* sc, const Unit& u, const int lane, const uint32_t o0, const uint32_t o1, const uint32_t o2) {
  stg128(sc + o0, u.v[0].x, u.v[0].y, u.v[0].z, u.v[0].w);
  stg128(sc + o1, u.v[1].x, u.v[1].y, u.v[1].z, u.v[1].w);
  stg128(sc + o2, u.v[2].x, u.v[2].y, u.v[2].z, u.v[2].w);
  return ldg_rlx32(sc + ((lane & 3) == 0 ? o0 : (lane & 3) == 1 ? o1 : o2));
}

__device__ __forceinline__ void store_rows(const uint32_t stg, unsigned char* obase, const int skip, const int lane) {
#pragma unroll
  for (int m = 0; m < 5; m++) {
    const int e = lane + 32 * m, r = (e * 57) >> 9;
    const uint4 v = lds128(stg + min(e, 143) * 16);
    if (e < 144 && r != skip) *(uint4*)(obase + (r * (2304 - 144) + e * 16)) = v;
  }
}

__device__ __forceinline__ void consumer_role(const Ctx& cx, const Params& P, const unsigned char* smem, const int p, const int w, const int lane_) {
  int lane = lane_;
#define g (lane >> 2)
#define q (lane & 3)
#define first_lane (lane == 0)
  const int i = cx.i, j = cx.j, ip = i * 2 + p;
  unsigned char* const sc = (unsigned char*)P.sc;
  float m_lo = 0.f, m_hi = 0.f, rs_lo = 0.f, rs_hi = 0.f;
  uint32_t T = ldg_rlx32(P.sc->cflag[ip][j * 4 + w]);
  nb_sync(NB_ORD, 352);
  if (X_DELAY) { const int c0 = clock(); while ((int)(clock() - c0) < X_DELAY + (p * 4 + w) * X_STEP) {} }
  {
    const int t = min(w * 32 + lane, 95);
    uint32_t u0 = 0, u1 = 0, u2 = 0, u = 0;
    if (p == 0) {
      u0 = ldg_nc32((const uint32_t*)P.wr + t); u1 = ldg_nc32((const uint32_t*)P.wr + 96 + t); u2 = ldg_nc32((const uint32_t*)P.wr + 192 + t);
      u = ldg_nc32((const uint32_t*)P.wr + 36 * j + min(t, 35));
    }
    const int r = cx.cta * 16 + (p * 4 + w) * 2 + (lane >> 4);
    const float2 st = row_stats(P, r, lane);
    T = __shfl_sync(0xffffffffu, (T >> 3) + 1, 0);
    if ((lane & 15) == 0) stg128(sc + (OFF(st0) + r * 16), asu(st.x), asu(st.y), T, 0u);
    STAMPIF(1, 111);
    if (p == 0) {
      float s = (bf_lo(u0) + bf_hi(u0)) + (bf_lo(u1) + bf_hi(u1)) + (bf_lo(u2) + bf_hi(u2));
#pragma unroll
      for (int o = 1; o < 32; o <<= 1) s += shx(s, o);
      stsf(sb + SM_WR + 288 + w * 4, s);
      sts64(sb + SM_WR + min(t, 35) * 8, u << 16, u & 0xFFFF0000u);
    }
  }
#pragma unroll 1
  for (int L = 0; L < 2; L++) {
    lane = pin(lane);
    const uint32_t tg = 2 * T + L;
    float c_lo = 0.f, c_hi = 0.f;
    bool sel_lo = false, sel_hi = false;
    float acc[108];
#pragma unroll
    for (int k = 0; k < 108; k++) acc[k] = 0.f;
    fence_regs<108>(acc);
    {
      const uint32_t ah = L == 0 ? DHI(1024, 1) : DHI(128, 0);
      const uint32_t astep = L == 0 ? 2 : 128;
      const uint32_t a0 = (L == 0 ? DLO(sb + SM_A, 16) : DLO(sb + SM_A, 1024)) + p * 512;
      constexpr uint32_t bh = DHI(512, 0);
      if (L == 1) {
        const float ul = 1.f + rs_lo, uh = 1.f + rs_hi;
        const float vl = fmaxf(rcp(rs_lo * rs_lo) - EPS, 0.f), vh = fmaxf(rcp(rs_hi * rs_hi) - EPS, 0.f);
        c_lo = ul * rsq(vl * ul * ul + EPS);
        c_hi = uh * rsq(vh * uh * uh + EPS);
      }
      if (L == 1) mbar_wait(sb + BAR_AFULL + p * 8, 0);
      mbar_wait(sb + BAR_FULL, 0);
      if (L == 1 && (p == 1 || Q1_BOTH)) nb_sync(NB_FFN2, Q1_BOTH ? 352 : 224);
      CSTAMP(0); GSTAMP(120 + 2 * L);
      uint32_t e0 = 0, e1 = 0;
      bool prepped = false, gone = false;
      auto prep_ext = [&]() {
        const int row = p * 64 + w * 16 + g;
        if (L == 0) {
          const uint2 u0 = lds64(sb + SM_R + row * 8), u1 = lds64(sb + SM_R + row * 8 + 64);
          m_lo = asf(u0.x); c_lo = asf(u0.y); m_hi = asf(u1.x); c_hi = asf(u1.y);
        } else {
          const uint4 sv = lds128(sb + SM_SEL);
          sel_lo = (int)sv.x == row; sel_hi = (int)sv.x == row + 8;
          if (sel_lo) { m_lo = asf(sv.z); c_lo = asf(sv.w); }
          if (sel_hi) { m_hi = asf(sv.z); c_hi = asf(sv.w); }
        }
        const float hl = rbf(-m_lo), hh = rbf(-m_hi);
        const uint32_t em = selu(lane & 1, 0x0000FFFFu, 0xFFFFFFFFu);
        e0 = selu(lane & 2, selu(sel_lo && !(lane & 1), 0x3F803F80u, 0u), pack_bf16(hl, -m_lo - hl) & em);
        e1 = selu(lane & 2, selu(sel_hi && !(lane & 1), 0x3F803F80u, 0u), pack_bf16(hh, -m_hi - hh) & em);
      };
      bool pend = false;
#pragma unroll 1
      for (int r = 0; r < 3; r++) {
#pragma unroll
        for (int h = 0; h < 6; h++) {
          const uint32_t al = a0 + (h >> 1) * 1024 + (h & 1) * 2 * astep, bl = DLO(sb + SM_B, 128) + h * 864;
          const uint32_t nb = sb + BAR_FULL + ((h + 1) % 6) * 8, np = (r + (h == 5)) & 1;
          TSTAMP((6 * r + h) * 2);
          wg_fence();
          wgmma_ss_216(acc, al, ah, bl, bh);
          wgmma_ss_216(acc, al + astep, ah, bl + 16, bh);
          wg_commit();
          if (h == 5 && r == 2) break;
          const uint32_t ok = mbar_test(nb, np);
          if ((h == 1 || h == 3) && r == 0 && L == 1) mbar_wait(sb + BAR_AFULL + (h + 1 + p) * 8, 0);
          if (h == 0 && r == 1 && L == 0) {
          if (lane < 16) stg128(sc + (OFF(stats) + (ip * 4 + w) * 2048 + j * 256 + lane * 16), 0u, 0u, 0u, 0u);
          if (w == 3 && i < 15 && lane < 28) {
#pragma unroll
            for (int e = 0; e < 6; e++) stg128(sc + (OFF(halo) + ((ip + 2) * 8 + j) * 2688 + lane * 16) + e * 448, 0u, 0u, 0u, 0u);
          }
          if (w == 0 && lane < 2) stg128(sc + (OFF(cand) + (j * 32 + ip) * (CAND_W * 4) + lane * 16), 0u, 0u, 0u, 0u);
          }
          wg_wait<1>();
          if (first_lane && pend) mbar_arrive(sb + BAR_EMPTY + ((h + 5) % 6) * 8);
          pend = true;
          const bool hold = h == HOLD_C % 6 && r == HOLD_C / 6 && p == 1;
          if (hold || (!ok && !mbar_test(nb, np))) {
            wg_wait<0>();
            if (first_lane) mbar_arrive(sb + BAR_EMPTY + h * 8);
            pend = false;
            TSTAMP((6 * r + h) * 2 + 1);
            mbar_wait(nb, np);
            if (hold) {
              if (mbar_test(sb + BAR_FIX + 8, L)) { prep_ext(); prepped = true; }
              nb_sync(NB_STAG, 256);
            }
          }
        }
      }
      if (!prepped) {
        if (p == 0 && !gone && !mbar_test(sb + BAR_FIX, L)) { nb_arrive(NB_STAG, 256); gone = true; }
        mbar_wait(sb + BAR_FIX + p * 8, L);
        prep_ext();
      }
      wg_fence();
      wgmma_rs_216<DHI(128, 0)>(acc, e0, e1, 0u, 0u, DLO(sb + SM_BEXT, 0));
      wg_commit();
      if (p == 0 && !gone) nb_arrive(NB_STAG, 256);
      wg_wait<2>();
      if (first_lane && pend) mbar_arrive(sb + BAR_EMPTY + 32);
    }
    lane = pin(lane);
    const uint32_t fragoff = ip * 73728 + (9 * j) * 1024 + w * 256 + lane * 4;
    const uint32_t rboff = (min(lane, 17) >> 1) * 1024 + (lane < 18 ? lane & 1 : 0) * 128;
    const uint32_t hl16 = (lane < 4 ? lane : lane - 4) * 16;
    const uint32_t o_halo = pin(OFF(halo) + ((ip + (w == 3 ? 2 : 0)) * 8 + j) * 2688 + hl16);
    const uint32_t o_o = pin(OFF(obuf) + fragoff);
    nb_sync(NB_WG + p, 128);
    if ((o_halo | o_o) == 0xFFFFFFFFu) __trap();
    wg_wait<0>();
    fence_regs<108>(acc);
    if (first_lane) mbar_arrive(sb + BAR_EMPTY + 40);
    CSTAMP(1); GSTAMP(121 + 2 * L);
    {
      uint32_t Kh[9], Vh[9], Kl[9], Vl[9], Kx[9], Vx[9], Ql[9], Qh[9];
#pragma unroll
      for (int t = 0; t < 9; t++) {
        Kh[t] = pack_bf16(acc[4 * GI(1, t) + 2] * c_hi, acc[4 * GI(1, t) + 3] * c_hi);
        Vh[t] = pack_bf16(acc[4 * GI(2, t) + 2] * c_hi, acc[4 * GI(2, t) + 3] * c_hi);
        Ql[t] = pack_bf16(acc[4 * GI(0, t)], acc[4 * GI(0, t) + 1]);
        Qh[t] = pack_bf16(acc[4 * GI(0, t) + 2], acc[4 * GI(0, t) + 3]);
      }
      const uint32_t hbuf = sb + SM_A + p * 8192 + w * 2688 + hl16;
      if (w < 3) {
        if (lane >= 4) {
#pragma unroll
          for (int e = 0; e < 4; e++) sts128(hbuf + e * 448, Kh[2 * e], Kh[2 * e + 1], Vh[e], tg);
          sts128(hbuf + 4 * 448, Kh[8], Vh[4], Vh[5], tg);
          sts128(hbuf + 5 * 448, Vh[6], Vh[7], Vh[8], tg);
        }
      } else if (i < 15 && lane >= 4) {
#pragma unroll
        for (int e = 0; e < 4; e++) stg128(sc + o_halo + e * 448, Kh[2 * e], Kh[2 * e + 1], Vh[e], tg);
        stg128(sc + o_halo + 4 * 448, Kh[8], Vh[4], Vh[5], tg);
        stg128(sc + o_halo + 5 * 448, Vh[6], Vh[7], Vh[8], tg);
      }
      nb_sync(NB_WG + p, 128);
#pragma unroll
      for (int t = 0; t < 9; t++) {
        Kl[t] = pack_bf16(acc[4 * GI(1, t)] * c_lo, acc[4 * GI(1, t) + 1] * c_lo);
      }
#pragma unroll
      for (int t = 0; t < HALO_V; t++) Vl[t] = pack_bf16(acc[4 * GI(2, t)] * c_lo, acc[4 * GI(2, t) + 1] * c_lo);
      uint32_t dep = (Kl[0] ^ Kl[1] ^ Kl[2]) | (Kl[3] ^ Kl[4] ^ Kl[5]) | (Kl[6] ^ Kl[7] ^ Kl[8]);
#pragma unroll
      for (int t = 0; t < HALO_V; t += 3) dep |= Vl[t] ^ Vl[t + 1] ^ Vl[t + 2];
      const unsigned char* hp = (w > 0 ? smem + (hbuf - 2688 - sb) : sc + o_halo) + pin0(dep);
      uint4 hv[6];
#pragma unroll
      for (int e = 0; e < 6; e++)
        asm volatile("ld.relaxed.gpu.v4.b32 {%0,%1,%2,%3}, [%4];" : "=r"(hv[e].x), "=r"(hv[e].y), "=r"(hv[e].z), "=r"(hv[e].w) : "l"(hp + e * 448) : "memory");
      CSTAMP(2);
#pragma unroll
      for (int t = 0; t < 9; t++) {
        if (t >= HALO_V) Vl[t] = pack_bf16(acc[4 * GI(2, t)] * c_lo, acc[4 * GI(2, t) + 1] * c_lo);
        Vl[t] = movm(Vl[t]);
        Vh[t] = movm(Vh[t]);
      }
      uint32_t qa[4][2], qb[4][2];
      float s1[4][4], s2[4][4];
#pragma unroll
      for (int h = 0; h < 4; h++) {
        qa[h][0] = q >= h ? Ql[2 * h] : 0u; qa[h][1] = q >= h ? Qh[2 * h] : 0u;
        qb[h][0] = q <= h ? Ql[2 * h + 2] : 0u; qb[h][1] = q <= h ? Qh[2 * h + 2] : 0u;
      }
      const bool first = (i == 0 && w == 0);
      if (w == 0 && i > 0) {
        int n = 0;
#pragma unroll 1
        while (__any_sync(0xffffffffu, (orx(orx(orx(0, hv[0].w, tg), hv[1].w, tg), hv[2].w, tg) | orx(orx(orx(0, hv[3].w, tg), hv[4].w, tg), hv[5].w, tg)) != 0)) {
#pragma unroll
          for (int e = 0; e < 6; e++) rld128(hv[e], sc + o_halo + e * 448);
          if (++n > SPIN) TIMEOUT(__LINE__)
        }
      }
#pragma unroll
      for (int e = 0; e < 4; e++) { Kx[2 * e] = hv[e].x; Kx[2 * e + 1] = hv[e].y; Vx[e] = hv[e].z; }
      Kx[8] = hv[4].x; Vx[4] = hv[4].y; Vx[5] = hv[4].z; Vx[6] = hv[5].x; Vx[7] = hv[5].y; Vx[8] = hv[5].z;
      CSTAMP(3);
#pragma unroll
      for (int t = 0; t < 9; t++) Vx[t] = movm(Vx[t]);
#pragma unroll
      for (int h = 0; h < 4; h++) { mma8z(s1[h], qb[h][0], qb[h][1], Kl[2 * h + 2]); mma8z(s2[h], qb[h][0], qb[h][1], Kh[2 * h + 2]); }
#pragma unroll
      for (int h = 0; h < 4; h++) {
        mma16(s1[h], qa[h][0], qa[h][1], Ql[2 * h + 1], Qh[2 * h + 1], Kl[2 * h], Kl[2 * h + 1]);
        mma16(s2[h], qa[h][0], qa[h][1], Ql[2 * h + 1], Qh[2 * h + 1], Kh[2 * h], Kh[2 * h + 1]);
      }
      float s0[4][4];
#pragma unroll
      for (int h = 0; h < 4; h++) mma8z(s0[h], qb[h][0], qb[h][1], Kx[2 * h + 2]);
#pragma unroll
      for (int h = 0; h < 4; h++) mma16(s0[h], qa[h][0], qa[h][1], Ql[2 * h + 1], Qh[2 * h + 1], Kx[2 * h], Kx[2 * h + 1]);
      const bool pv0 = 2 * q > g, pv1 = 2 * q + 1 > g;
      const uint32_t PM = (pv0 ? 0x0000FFFFu : 0u) | (pv1 ? 0xFFFF0000u : 0u);
      const float kS = 0.23570226039551584f * 1.4426950408889634f;
      const float sc_lo = c_lo * kS, sc_hi = c_hi * kS;
      float sl[4][2], sh[4][2], ml[4], mh[4];
#pragma unroll
      for (int h = 0; h < 4; h++) {
        sh[h][0] = pv0 ? s1[h][2] : s2[h][2];
        sh[h][1] = pv1 ? s1[h][3] : s2[h][3];
        mh[h] = fmaxf(sh[h][0], sh[h][1]);
        sl[h][0] = pv0 ? (first ? -INFINITY : s0[h][0]) : s1[h][0];
        sl[h][1] = pv1 ? (first ? -INFINITY : s0[h][1]) : s1[h][1];
        ml[h] = fmaxf(sl[h][0], sl[h][1]);
      }
#pragma unroll
      for (int s = 1; s <= 2; s <<= 1) {
        float tl[4], th[4];
#pragma unroll
        for (int h = 0; h < 4; h++) { th[h] = shx(mh[h], s); tl[h] = shx(ml[h], s); }
#pragma unroll
        for (int h = 0; h < 4; h++) { mh[h] = fmaxf(mh[h], th[h]); ml[h] = fmaxf(ml[h], tl[h]); }
      }
      float o[4][3][4], den[4][4];
      uint32_t px[4];
#pragma unroll
      for (int h = 0; h < 4; h++) {
        const float bl = -ml[h] * sc_lo, bh = -mh[h] * sc_hi;
        const uint32_t pl = pack_bf16(ex2(fmaf(sl[h][0], sc_lo, bl)), ex2(fmaf(sl[h][1], sc_lo, bl)));
        const uint32_t ph = pack_bf16(ex2(fmaf(sh[h][0], sc_hi, bh)), ex2(fmaf(sh[h][1], sc_hi, bh)));
        mma8z(den[h], pl, ph, 0x3F803F80u);
        px[h] = pl & PM;
#pragma unroll
        for (int u = 0; u < 3; u++) mma16z(o[h][u], pl & ~PM, ph & PM, 0u, ph & ~PM, Vl[2 * h + u], Vh[2 * h + u]);
      }
#pragma unroll
      for (int h = 0; h < 4; h++)
#pragma unroll
        for (int u = 0; u < 3; u++) mma8(o[h][u], px[h], 0u, Vx[2 * h + u]);
      float il[4], ih[4];
#pragma unroll
      for (int h = 0; h < 4; h++) { il[h] = rcp(den[h][0]); ih[h] = rcp(den[h][2]); }
#pragma unroll
      for (int t = 0; t < 9; t++) {
        const int h = t == 8 ? 3 : t >> 1, u = t == 8 ? 2 : t & 1;
        float v0 = o[h][u][0], v1 = o[h][u][1], v2 = o[h][u][2], v3 = o[h][u][3], kl = il[h], kh = ih[h];
        if (u == 0 && h > 0 && q < h) {
          v0 = o[h - 1][2][0]; v1 = o[h - 1][2][1]; v2 = o[h - 1][2][2]; v3 = o[h - 1][2][3]; kl = il[h - 1]; kh = ih[h - 1];
        }
        stg32(sc + o_o + t * 1024, pack_bf16(v0 * kl, v1 * kl));
        stg32(sc + o_o + t * 1024 + 128, pack_bf16(v2 * kh, v3 * kh));
      }
    }
    CSTAMP(4);
    const uint32_t rbo = ldg_rlx32(sc + (o_o + rboff));
    lane = pin(lane);
    const uint32_t o_x = o_o + (OFF(xbuf) - OFF(obuf)), o_xrb = o_x + rboff;
    const uint32_t o_cf = OFF(cflag) + (ip * 32 + j * 4 + w) * 32 + lane * 4;
    if (L == 1 && first_lane) mbar_arrive(sb + BAR_HDONE + p * 8);
    flag_after(sc + o_cf, rbo, 8 * T + 2 * L, lane < 8);
    STAMPD(asf(rbo), L * 40 + p * 20 + 13);
    uint32_t resid[18];
    mbar_wait(sb + BAR_FULL + 16, 1); mbar_wait(sb + BAR_FULL + 32, 1);
    if (L == 0) {
      const uint32_t ra = sb + SM_A + (2 + p) * 8192 + (w * 16 + (lane & 15)) * 128;
#pragma unroll
      for (int t = 0; t < 9; t++) ldsm2(resid[2 * t], resid[2 * t + 1], ra + ((j + t) >> 3) * 16384 + ((((j + t) ^ lane) & 7) << 4));
      if (first_lane) mbar_arrive(sb + BAR_HDONE + p * 8 + pin0(resid[17]));
    } else {
#pragma unroll
      for (int t = 0; t < 9; t++) { resid[2 * t] = ldg_rlx32(sc + o_x + t * 1024); resid[2 * t + 1] = ldg_rlx32(sc + o_x + t * 1024 + 128); }
    }
    const uint32_t o_st = OFF(stats) + (ip * 4 + w) * 2048;
    const uint32_t o_stw = pin(o_st + j * 256 + (g + 8 * (q & 1)) * 16), o_str = pin(o_st + q * 512 + g * 16);
    const uint32_t o_cand = pin(OFF(cand) + (j * 32 + ip) * (CAND_W * 4) + q * 16);
    const uint32_t o_xc = pin(OFF(xcand) + (ip * 8 + j) * 192 + q * 16);
    float accw[36];
    float wr[18];
#pragma unroll
    for (int t = 0; t < 9; t++) { const uint2 u = lds64(sb + SM_WR + t * 32 + q * 8); wr[2 * t] = asf(u.x); wr[2 * t + 1] = asf(u.y); }
    const uint4 ws4 = lds128(sb + SM_WR + 288);
    const float wsum = asf(pin(asu(asf(ws4.x) + asf(ws4.y) + asf(ws4.z))));
    {
      float ul = 1.f, uh = 1.f, vl = 0.f, vh = 0.f;
      if (L == 1) {
        ul += rs_lo; uh += rs_hi; vl = -m_lo * rs_lo; vh = -m_hi * rs_hi;
        if (sel_lo || sel_hi) {
#pragma unroll
          for (int t = 0; t < 9; t++) {
            const uint32_t z = lds32(sb + SM_X2S + t * 16 + q * 4);
            if (sel_hi) resid[2 * t + 1] = z; else resid[2 * t] = z;
          }
          if (sel_hi) { uh = 1.f; vh = 0.f; } else { ul = 1.f; vl = 0.f; }
        }
        __syncwarp();
      }
#pragma unroll
      for (int t = 0; t < 9; t++) {
        accw[4 * t] = fmaf(bf_lo(resid[2 * t]), ul, vl); accw[4 * t + 1] = fmaf(bf_hi(resid[2 * t]), ul, vl);
        accw[4 * t + 2] = fmaf(bf_lo(resid[2 * t + 1]), uh, vh); accw[4 * t + 3] = fmaf(bf_hi(resid[2 * t + 1]), uh, vh);
      }
    }
    fence_regs<36>(accw);
    mbar_wait(sb + BAR_FULL, 1); mbar_wait(sb + BAR_FULL + 8, 1); mbar_wait(sb + BAR_FULL + 24, 1); mbar_wait(sb + BAR_FULL + 40, 1);
    {
      uint32_t wf = sb + BAR_WFULL + p * 72;
      uint32_t bl = DLO(sb + SM_B, 128);
      uint32_t half = p;
      mbar_wait(wf, L);
      CSTAMP(5);
#pragma unroll 1
      for (int c3 = 0; c3 < 3; c3++) {
        const uint32_t al = DLO(sb + SM_A, 1024) + half * 512;
        const uint32_t ae = sb + BAR_AEMPTY + half * 24;
#pragma unroll
        for (int cc = 0; cc < 3; cc++) {
          TSTAMP(36 + (c3 * 3 + cc) * 2);
          wg_fence();
          wgmma_ss_72(accw, al + cc * 1024, DHI(128, 0), bl + cc * 576, DHI(256, 0));
          wgmma_ss_72(accw, al + cc * 1024 + 128, DHI(128, 0), bl + cc * 576 + 144, DHI(256, 0));
          const uint32_t ok = mbar_test(wf + cc * 8 + 8, L);
          wgmma_ss_72(accw, al + cc * 1024 + 256, DHI(128, 0), bl + cc * 576 + 288, DHI(256, 0));
          wgmma_ss_72(accw, al + cc * 1024 + 384, DHI(128, 0), bl + cc * 576 + 432, DHI(256, 0));
          wg_commit();
          wg_wait<1>();
          if (cc > 0) { if (first_lane) { mbar_arrive(ae + cc * 8 - 8); if (cc == 2) mbar_arrive(sb + BAR_EMPTY + c3 * 16); } }
          else if (first_lane && c3 > 0) { mbar_arrive(sb + BAR_AEMPTY + 40 - half * 24); mbar_arrive(sb + BAR_EMPTY + c3 * 16 - 8); }
          if (!ok && (cc < 2 || c3 < 2)) mbar_wait(wf + cc * 8 + 8, L);
        }
        wf += 24; bl += 1728; half ^= 1;
      }
    }
    wg_wait<0>();
    fence_regs<36>(accw);
    if (first_lane) { mbar_arrive(sb + BAR_AEMPTY + (2 + 3 * p) * 8); mbar_arrive(sb + BAR_EMPTY + 40); }
    CSTAMP(6);
    uint32_t xw[18];
    uint32_t rb = 0;
    if (L == 0 && p == 0) {
#pragma unroll
      for (int t = 0; t < 9; t++) {
        stg32(sc + o_x + t * 1024, pack_bf16(accw[4 * t], accw[4 * t + 1]));
        stg32(sc + o_x + t * 1024 + 128, pack_bf16(accw[4 * t + 2], accw[4 * t + 3]));
      }
      rb = ldg_rlx32(sc + o_xrb);
      fence_regs<36>(accw);
    }
    {
      float a0[2] = {0.f, 0.f}, a1[2] = {0.f, 0.f}, a2[2] = {0.f, 0.f}, b0[2] = {0.f, 0.f}, b1[2] = {0.f, 0.f}, b2[2] = {0.f, 0.f};
#pragma unroll
      for (int t = 0; t < 9; t++) {
#pragma unroll
        for (int e = 0; e < 2; e++) {
          const float x = accw[4 * t + e], y = accw[4 * t + 2 + e];
          a0[e] += x; a1[e] = fmaf(x, x, a1[e]); a2[e] = fmaf(x, wr[2 * t + e], a2[e]);
          b0[e] += y; b1[e] = fmaf(y, y, b1[e]); b2[e] = fmaf(y, wr[2 * t + e], b2[e]);
        }
      }
      const bool od = q & 1;
      const float A0 = a0[0] + a0[1], A1 = a1[0] + a1[1], A2 = a2[0] + a2[1], B0 = b0[0] + b0[1], B1 = b1[0] + b1[1], B2 = b2[0] + b2[1];
      float k0 = od ? B0 : A0, k1 = od ? B1 : A1, k2 = od ? B2 : A2;
      k0 += shx(od ? A0 : B0, 1); k1 += shx(od ? A1 : B1, 1); k2 += shx(od ? A2 : B2, 1);
      k0 += shx(k0, 2); k1 += shx(k1, 2); k2 += shx(k2, 2);
      if (q < 2) stg128(sc + o_stw, asu(k0), asu(k1), asu(k2), tg);
      STAMPD(k0, L * 40 + p * 20 + 14);
    }
#pragma unroll
    for (int t = 0; t < 9; t++) {
      xw[2 * t] = pack_bf16(accw[4 * t], accw[4 * t + 1]);
      xw[2 * t + 1] = pack_bf16(accw[4 * t + 2], accw[4 * t + 3]);
    }
    float r_lo, r_hi;
    {
      uint4 u0 = ldg_rlx128(sc + o_str), u1 = ldg_rlx128(sc + o_str + 256), u2 = ldg_rlx128(sc + o_str + 128), u3 = ldg_rlx128(sc + o_str + 384);
      flag_after(sc + o_cf, rb, 8 * T + 1, lane < 8 && L == 0 && p == 0);
      STAMPD(asf(u3.w), L * 40 + p * 20 + 15);
      int n = 0;
#pragma unroll 1
      while (__any_sync(0xffffffffu, orx(orx(orx(orx(0, u0.w, tg), u1.w, tg), u2.w, tg), u3.w, tg) != 0)) {
        rld128(u0, sc + o_str); rld128(u1, sc + o_str + 256); rld128(u2, sc + o_str + 128); rld128(u3, sc + o_str + 384);
        if (++n > SPIN) TIMEOUT(__LINE__)
      }
      float a0 = asf(u0.x) + asf(u1.x), a1 = asf(u0.y) + asf(u1.y), a2 = asf(u0.z) + asf(u1.z);
      float b0 = asf(u2.x) + asf(u3.x), b1 = asf(u2.y) + asf(u3.y), b2 = asf(u2.z) + asf(u3.z);
#pragma unroll
      for (int s = 1; s <= 2; s <<= 1) {
        const float t0 = shx(a0, s), t1 = shx(a1, s), t2 = shx(a2, s), t3 = shx(b0, s), t4 = shx(b1, s), t5 = shx(b2, s);
        a0 += t0; a1 += t1; a2 += t2; b0 += t3; b1 += t4; b2 += t5;
      }
      m_lo = a0 * (1.f / 576.f); m_hi = b0 * (1.f / 576.f);
      rs_lo = rsq(fmaxf(a1 * (1.f / 576.f) - m_lo * m_lo, 0.f) + EPS);
      rs_hi = rsq(fmaxf(b1 * (1.f / 576.f) - m_hi * m_hi, 0.f) + EPS);
      r_lo = (a2 - m_lo * wsum) * rs_lo; r_hi = (b2 - m_hi * wsum) * rs_hi;
    }
    CSTAMP(7);
    if (ST_HOLD && L == 0 && p == ST_P && w == 0 && first_lane) mbar_arrive(sb + BAR_ST + pin0(asu(r_lo)));
    if (LATE_Q1 == 3 && L == 0 && p == 1 && w == 0 && first_lane) mbar_arrive(sb + BAR_ST + pin0(asu(r_lo)));
    int candrow = -1;
    {
      const uint32_t kl = fkey(r_lo), kh = fkey(r_hi);
      const bool hi = kh > kl;
      const uint32_t kb = hi ? kh : kl;
      const uint32_t mx = __reduce_max_sync(0xffffffffu, kb);
      if (first_lane) sts32(sb + SM_BEST + p * 16 + w * 4, mx);
      const uint32_t bal = __ballot_sync(0xffffffffu, kb == mx);
      const bool mine = (bal & ((1u << (lane & 28)) - 1u)) == 0u && kb == mx;
      const uint32_t x0 = hi ? xw[1] : xw[0], x1 = hi ? xw[3] : xw[2], x2 = hi ? xw[5] : xw[4], x3 = hi ? xw[7] : xw[6], x4 = hi ? xw[9] : xw[8];
      const uint32_t x5 = hi ? xw[11] : xw[10], x6 = hi ? xw[13] : xw[12], x7 = hi ? xw[15] : xw[14], x8 = hi ? xw[17] : xw[16];
      nb_sync(NB_WG + p, 128);
      const uint4 bs = lds128(sb + SM_BEST + p * 16);
      const bool best = (w > 0 ? bs.x < mx : true) && (w > 1 ? bs.y < mx : bs.y <= mx) && (w > 2 ? bs.z < mx : bs.z <= mx) && bs.w <= mx;
      if (best && mine) {
        if (q < 2) stg128(sc + o_cand, asu(hi ? r_hi : r_lo), (tg << 6) + (uint32_t)(w * 16 + g + (hi ? 8 : 0)), asu(hi ? m_hi : m_lo), asu(hi ? rs_hi : rs_lo));
        stg128(sc + o_xc, x0, x1, x2, tg);
        stg128(sc + o_xc + 64, x3, x4, x5, tg);
        stg128(sc + o_xc + 128, x6, x7, x8, tg);
      }
      candrow = __reduce_max_sync(0xffffffffu, best && mine ? g + (hi ? 8 : 0) : -1);
    }
    if (L == 0 && p == 1) {
#pragma unroll
      for (int t = 0; t < 9; t++) { stg32(sc + o_x + t * 1024, xw[2 * t]); stg32(sc + o_x + t * 1024 + 128, xw[2 * t + 1]); }
      rb = ldg_rlx32(sc + o_xrb);
    }
    const uint32_t stg = sb + SM_B + p * 13824 + w * 2304;
    unsigned char* obase = (unsigned char*)P.out + ((128 * i + 32 * w + p) * 1152 + 144 * j);
    if (L == 1) {
      const float ul = 1.f + rs_lo, uh = 1.f + rs_hi, vl = -m_lo * rs_lo, vh = -m_hi * rs_hi;
#pragma unroll
      for (int t = 0; t < 9; t++) {
        xw[2 * t] = pack_bf16(fmaf(accw[4 * t], ul, vl), fmaf(accw[4 * t + 1], ul, vl));
        xw[2 * t + 1] = pack_bf16(fmaf(accw[4 * t + 2], uh, vh), fmaf(accw[4 * t + 3], uh, vh));
      }
      mbar_wait(sb + BAR_EMPTY + p * 8, 1);
      const uint32_t sa = stg + (lane & 15) * 144;
#pragma unroll
      for (int t = 0; t < 8; t += 2) stsm4(sa + (lane >> 4) * 16 + t * 16, xw[2 * t], xw[2 * t + 1], xw[2 * t + 2], xw[2 * t + 3]);
      stsm2(sa + 128, xw[16], xw[17]);
      __syncwarp();
      if (p == 0 || !OUT_LATE) store_rows(stg, obase, candrow, lane);
    }
    CSTAMP(8);
    lane = pin(lane);
    const unsigned char* cp = sc + (OFF(cand) + (j * 32 + lane) * (CAND_W * 4));
    if (p == 0) {
      if (L == 1 && candrow >= 0) {
        const Winner wn = poll_winner(cp, ldg_rlx128(cp), tg);
        if (lane < 9 && wn.ci != ip) *(uint4*)(obase + (candrow * 2304 + lane * 16)) = lds128(stg + candrow * 144 + lane * 16);
      }
    } else {
      const uint32_t gr = w * 144 + (lane & 7) + (lane >> 4) * 8, gm = sb + SM_G + ((lane >> 3) & 1) * 46080;
      const uint32_t ga = gm + gr * 64 + (((lane >> 1) & 3) << 4), gl = gm + 36864 + gr * 16;
#define GADDR(s, u) ((u) < 4 ? (ga ^ ((u) << 4)) + (s) * 1024 : gl + (s) * 256)
      uint32_t wf[NPRE][5][4];
      mbar_wait(sb + BAR_GU, 0);
#pragma unroll
      for (int s = 0; s < NPRE - 2; s++)
#pragma unroll
        for (int u = 0; u < 5; u++) ldsm4t(wf[s][u], GADDR(s, u));
      const uint4 c0 = ldg_rlx128(cp);
#pragma unroll
      for (int s = NPRE - 2; s < NPRE; s++)
#pragma unroll
        for (int u = 0; u < 5; u++) ldsm4t(wf[s][u], GADDR(s, u));
      flag_after(sc + o_cf, rb, 8 * T + 1, lane < 8 && L == 0);
      const Winner wn = poll_winner(cp, c0, tg);
      if (w == 0 && first_lane) sts128(sb + SM_WIN, asu(wn.r), asu(wn.m), asu(wn.rstd), (uint32_t)(wn.ci * 64 + wn.rr));
      if (LATE_Q1 == 2 && L == 0 && w == 0 && first_lane) mbar_arrive(sb + BAR_ST + pin0(wn.ci));
      CSTAMP(9);
      if (!OUT_LATE && L == 1 && candrow >= 0 && lane < 9 && wn.ci != ip) *(uint4*)(obase + (candrow * 2304 + lane * 16)) = lds128(stg + candrow * 144 + lane * 16);
      {
        uint32_t hb[18];
        const unsigned char* xc = sc + (OFF(xcand) + wn.ci * 1536 + q * 16);
        const int fp = min(cx.cta / 3, 23);
        uint4 u[7];
        int n = 0;
#pragma unroll 1
        while (true) {
          uint32_t d = 0;
#pragma unroll
          for (int e = 0; e < 7; e++) u[e] = ldg_rlx128(xc + (e < 6 ? w * 384 + e * 64 : fp * 64));
#pragma unroll
          for (int e = 0; e < 7; e++) d = orx(d, u[e].w, tg);
          if (__all_sync(0xffffffffu, d == 0)) break;
          if (++n > SPIN) TIMEOUT(__LINE__)
        }
        if (LATE_Q1 == 1 && L == 0 && w == 0 && first_lane) mbar_arrive(sb + BAR_ST + pin0(u[0].x));
        if (OUT_LATE == 3 && L == 1) store_rows(stg, obase, wn.ci == ip ? candrow : -1, lane);
#pragma unroll
        for (int e = 0; e < 6; e++) { hb[3 * e] = u[e].x; hb[3 * e + 1] = u[e].y; hb[3 * e + 2] = u[e].z; }
        if (w == 0) sts128(sb + SM_XW + q * 16, u[6].x, u[6].y, u[6].z, u[6].w);
        const float nb = -wn.m * wn.rstd;
#pragma unroll
        for (int b = 0; b < 18; b++) hb[b] = pack_bf16(fmaf(bf_lo(hb[b]), wn.rstd, nb), fmaf(bf_hi(hb[b]), wn.rstd, nb));
        CSTAMP(10);
        float d[5][4];
#pragma unroll
        for (int u = 0; u < 5; u++) d[u][0] = d[u][1] = d[u][2] = d[u][3] = 0.f;
#pragma unroll
        for (int s = 0; s < 9; s++) {
#pragma unroll
          for (int u = 0; u < 5; u++) {
            uint32_t* f = wf[s % NPRE][u];
            mma16(d[u], f[0], f[1], f[2], f[3], hb[2 * s], hb[2 * s + 1]);
            if (s + NPRE < 9) ldsm4t(f, GADDR(s + NPRE, u));
          }
        }
        if (q == 0) {
#pragma unroll
          for (int u = 0; u < 5; u++) sts64(sb + R_FPART + w * 320 + (u * 8 + g) * 8, asu(d[u][0]), asu(d[u][2]));
        }
        nb_arrive(NB_FFN, 224);
        CSTAMP(11);
      }
      if (OUT_LATE == 1 && L == 1) store_rows(stg, obase, wn.ci == ip ? candrow : -1, lane);
    }
  }
  STAMPIF(w == 0 && lane == 0, 40 + p * 20 + 12);
  PROF_DUMP();
#undef g
#undef q
#undef first_lane
}

__device__ __forceinline__ void load_wo_a(const Ctx& cx, const Params& P, const uint32_t T, const int L, const int p, const int lane) {
  const unsigned char* src = P.sc->obuf[cx.i * 2 + p];
#pragma unroll
  for (int c = 0; c < 9; c++) w_expect(sb + BAR_WFULL + (9 * p + c) * 8, 8192);
  mbar_wait(sb + BAR_HDONE + p * 8, L);
  wait_flags<32>(P.sc->cflag[cx.i * 2 + p], 8 * T + 2 * L, lane);
  fence_async_glob();
  STAMP(100 + L * 2 + p);
#pragma unroll
  for (int c = 0; c < 9; c++) {
    const int e = 9 * p + c, s = e % 6;
    if (e == 3) mbar_wait(sb + BAR_HDONE + 8, L);
    if (e >= 6) mbar_wait(sb + BAR_AEMPTY + s * 8, (L ^ (e / 6) ^ 1) & 1);
    w_bulk(sb + SM_A + (2 * (s % 3) + s / 3) * 8192, src + c * 8192, 8192, sb + BAR_WFULL + e * 8);
    PSTAMP(48 + L * 36 + 18 + e);
  }
}

__device__ __forceinline__ void finalize_row(const Params& P, const Winner& wn, const uint32_t T, const int L, const int grp, const int a, const int lane) {
  const unsigned char* yp = (const unsigned char*)P.sc->ypart[grp] + (a * 32 + lane) * 16;
  const uint32_t par = L ^ 1;
  uint4 u0 = ldg_rlx128(yp), u1 = ldg_rlx128(yp + 1536), u2 = make_uint4(par, 0, 0, 0);
  if (a < 2) rld128(u2, yp + 3072);
  const int col = lane & 7;
  const uint32_t xw = lds32(sb + SM_XW + (col >> 1) * 16 + (grp % 3) * 4);
  const float xsel = (col & 1) ? bf_hi(xw) : bf_lo(xw);
  const float sg = rbf(rcp(1.f + ex2(-1.4426950408889634f * rbf(wn.r))));
  const float h = rbf((xsel - wn.m) * wn.rstd);
  unsigned char* dst = L == 0 ? (unsigned char*)P.sc->xsel + (((lane >> 3) & 1) * 576 + grp * 8 + col) * 4
                              : (unsigned char*)P.out + ((128 * (wn.ci >> 1) + 2 * wn.rr + (wn.ci & 1)) * 576 + grp * 8 + col) * 2;
  int n = 0;
#pragma unroll 1
  while (__any_sync(0xffffffffu, orx(orx(orx(0, u0.x, par), u1.x, par), u2.x, par) & 1)) {
    rld128(u0, yp); rld128(u1, yp + 1536);
    if (a < 2) rld128(u2, yp + 3072);
    if (++n > SPIN) TIMEOUT(__LINE__)
  }
  const float s0 = asf(u0.x) + asf(u1.x) + asf(u2.x), s1 = asf(u0.y) + asf(u1.y) + asf(u2.y);
  const float s2 = asf(u0.z) + asf(u1.z) + asf(u2.z), s3 = asf(u0.w) + asf(u1.w) + asf(u2.w);
  const float k0 = self(lane & 2, s2, s0) + shx(self(lane & 2, s0, s2), 2), k1 = self(lane & 2, s3, s1) + shx(self(lane & 2, s1, s3), 2);
  float k = self(lane & 4, k1, k0) + shx(self(lane & 4, k0, k1), 4);
  k += shx(k, 8); k += shx(k, 16);
  if (lane < 8) stsf(sb + SM_YRED + ((lane & 1) * 4 + (lane & 2) + (lane >> 2)) * 16 + a * 4, k);
  nb_sync(NB_AUX, 96);
  if (a == 0) {
    const uint4 yy = lds128(sb + SM_YRED + col * 16);
    const float xn = rbf(xsel + rbf(h + rbf(rbf(asf(yy.x) + asf(yy.y) + asf(yy.z)) * sg)));
    if (L == 0) { if (lane < 16) stg32(dst, ftag(lane < 8 ? xn : xn - xsel, T & 1)); }
    else if (lane < 8) *(unsigned short*)dst = (unsigned short)(asu(xn) >> 16);
  }
}

__device__ __forceinline__ void aux_role(const Ctx& cx, const Params& P, const int a, const int lane_) {
  int lane = lane_;
#define t (a * 32 + lane)
#define g (lane >> 2)
#define q (lane & 3)
  const int i = cx.i, j = cx.j, cta = cx.cta;
  unsigned char* const sc = (unsigned char*)P.sc;
  const int rk = 36 * i + 12 * a;
  const uint32_t o_bf = OFF(bflag) + (j * 48 + i * 3 + a) * 32 + (lane & 7) * 4;
  uint32_t T;
  {
    const int k0 = lane & 7, tt = min(lane >> 3, 2), col = (9 * j + tt) * 16;
    const unsigned char* src = (const unsigned char*)P.wqkv + ((i * 8 + k0) * 3456 + a * 1152 + col);
    const Unit b0 = unit_load(src), b1 = unit_load(src + 128 * 3456);
    T = ldg_rlx32(sc + o_bf);
    nb_arrive(NB_ORD, 352);
    STAMPIF(1, 96);
    const uint32_t d2 = tt == 2 ? (22 - 7 * a) * 512 : 3072;
    const uint32_t o = OFF(wq) + (j * 18 + (i >> 2)) * 13824 + ((i & 3) * 8 + k0) * 16 + (a * 8 + tt) * 512;
    const uint32_t r0 = unit_store(sc, b0, lane, o, o + 1536, o + d2);
    STAMPIF(1, 80);
    const uint32_t r1 = unit_store(sc, b1, lane, o + 55296, o + 55296 + 1536, o + 55296 + d2);
    T = __shfl_sync(0xffffffffu, (T >> 3) + 1, 0);
    flag_after(sc + o_bf, r0 ^ r1, 8 * T + 1, lane < 8);
    STAMPIF(1, 98);
    const Unit b2 = unit_load(src + 256 * 3456), b3 = unit_load(src + 384 * 3456);
    const bool qkv = k0 < 4;
    const int q0 = rk + k0 - 4, q1 = rk + 4 + k0;
    const Unit u0 = unit_load(qkv ? (const unsigned char*)P.wqkv + ((512 + 4 * i + k0) * 3456 + a * 1152 + col) : (const unsigned char*)P.wo + (q0 * 1152 + col));
    const Unit u1 = unit_load((const unsigned char*)P.wo + (q1 * 1152 + col));
    const uint32_t r2 = unit_store(sc, b2, lane, o + 2 * 55296, o + 2 * 55296 + 1536, o + 2 * 55296 + d2);
    const uint32_t r3 = unit_store(sc, b3, lane, o + 3 * 55296, o + 3 * 55296 + 1536, o + 3 * 55296 + d2);
    float cs[3][8];
#pragma unroll
    for (int m = 0; m < 3; m++) {
      const uint32_t* w0 = &b0.v[m].x; const uint32_t* w1 = &b1.v[m].x; const uint32_t* w2 = &b2.v[m].x; const uint32_t* w3 = &b3.v[m].x; const uint32_t* w4 = &u0.v[m].x;
#pragma unroll
      for (int e = 0; e < 4; e++) {
        const uint32_t z = qkv ? w4[e] : 0u;
        cs[m][2 * e] = (bf_lo(w0[e]) + bf_lo(w1[e])) + (bf_lo(w2[e]) + bf_lo(w3[e])) + bf_lo(z);
        cs[m][2 * e + 1] = (bf_hi(w0[e]) + bf_hi(w1[e])) + (bf_hi(w2[e]) + bf_hi(w3[e])) + bf_hi(z);
      }
    }
    flag_after(sc + o_bf, r2 ^ r3, 8 * T + 3, lane < 8);
    STAMPIF(1, 82);
#pragma unroll
    for (int st = 4; st >= 1; st >>= 1) {
      const bool up = lane & st;
#pragma unroll
      for (int m = 0; m < 3; m++)
#pragma unroll
        for (int e = 0; e < st; e++) cs[m][e] = (up ? cs[m][e + st] : cs[m][e]) + shx(up ? cs[m][e] : cs[m][e + st], st);
    }
    {
      const uint32_t oz = OFF(zpart) + j * 13824 + i * 864 + (a * 8 + tt) * 32 + k0 * 4;
      stg32(sc + oz, ftag(cs[0][0], 1)); stg32(sc + (oz + 96), ftag(cs[1][0], 1)); stg32(sc + (oz + (d2 >> 4)), ftag(cs[2][0], 1));
    }
    STAMPIF(1, 81);
    nb_sync(NB_GO, 128);
    mbar_wait(sb + BAR_FULL + LATE_WAIT * 8, 0);
    const uint32_t ow = OFF(wo) + j * 82944 + tt * 256;
    const uint32_t oa = qkv ? OFF(wq) + (j * 18 + 16 + (i >> 3)) * 13824 + (4 * (i & 7) + k0) * 16 + (a * 8 + tt) * 512 : ow + (q0 >> 4) * 2304 + (q0 & 15) * 16;
    const uint32_t ob = ow + (q1 >> 4) * 2304 + (q1 & 15) * 16;
    const uint32_t ra = unit_store(sc, u0, lane, oa, oa + (qkv ? 1536 : 768), oa + (qkv ? d2 : 1536));
    const uint32_t rb = unit_store(sc, u1, lane, ob, ob + 768, ob + 1536);
    STAMPIF(1, 113);
#pragma unroll
    for (int S = 0; S < 3; S++) stg64(sc + (OFF(ypart) + (a * 24 + g) * 4096 + cta * 32 + q * 8) + S * 32768, 0u, 0u);
    if (cta < 72 && t < 16) stg32(sc + (OFF(xsel) + (lane >> 3) * 2304 + cta * 32 + (lane & 7) * 4), (T & 1) ^ 1);
    uint4 sv, sw;
    int n = 0;
#pragma unroll 1
    while (true) {
      sv = ldg_rlx128(sc + (OFF(st0) + i * 2048 + t * 16)); sw = ldg_rlx128(sc + (OFF(st0) + i * 2048 + 1536 + lane * 16));
      if (__all_sync(0xffffffffu, ((sv.z ^ T) | (sw.z ^ T)) == 0)) break;
      if (++n > SPIN) TIMEOUT(__LINE__)
    }
    flag_after(sc + o_bf, ra ^ rb, 8 * T + 4, lane < 8);
    sts64(sb + SM_R + t * 8, sv.x, sv.y);
    sts64(sb + SM_R + 768 + lane * 8, sw.x, sw.y);
    STAMPIF(1, 94);
  }
  Winner wn;
  bool owner = false;
  uint32_t wd[5][3][8];
  auto load_wd = [&](uint32_t (*d)[8], const unsigned char* sk) {
#pragma unroll
    for (int S = 0; S < 3; S++) {
      const uint4 v0 = ldg_nc128(sk + S * 128), v1 = ldg_nc128(sk + S * 128 + 1152);
      d[S][0] = v0.x; d[S][1] = v1.x; d[S][2] = v0.y; d[S][3] = v1.y; d[S][4] = v0.z; d[S][5] = v1.z; d[S][6] = v0.w; d[S][7] = v1.w;
    }
  };
  auto perm_wd = [&](uint32_t (*d)[8]) {
#pragma unroll
    for (int S = 0; S < 3; S++)
#pragma unroll
      for (int u = 0; u < 4; u++) {
        const uint32_t x = d[S][2 * u], y = d[S][2 * u + 1];
        asm volatile("prmt.b32 %0, %2, %3, 0x5410;\nprmt.b32 %1, %2, %3, 0x7632;" : "=&r"(d[S][2 * u]), "=r"(d[S][2 * u + 1]) : "r"(x), "r"(y));
      }
  };
#pragma unroll
  for (int kb = 0; kb < 3; kb++)
#pragma unroll
    for (int S = 0; S < 3; S++)
#pragma unroll
      for (int e = 0; e < 8; e++) wd[kb][S][e] = 0u;
#pragma unroll 1
  for (int L = 0; L < 2; L++) {
    lane = pin(lane);
    const uint32_t o_part = OFF(zpart) + j * 13824, par = L ^ 1;
    const int pk = a * 18 + min(lane, 17);
    if (L == 1) {
      if (cta < 72) finalize_row(P, wn, T, 0, cta, a, lane);
      const int gi = min(lane, 26);
      uint4 wv[12];
      {
        const int pc = gi < 24 ? gi >> 3 : gi - 24, tc = gi < 24 ? gi & 7 : 8;
        const unsigned char* se = (const unsigned char*)P.wqkv + (rk * 3456 + pc * 1152 + (9 * j + tc) * 16);
#pragma unroll
        for (int r = 0; r < 12; r++) wv[r] = ldg_nc128(se + r * 3456);
      }
      STAMPIF(1, 85);
      nb_sync(NB_AUX, 96);
      uint4 xq[3];
      {
        const unsigned char* dp = sc + (OFF(xsel) + 2304 + rk * 4);
        int n = 0;
#pragma unroll 1
        while (true) {
#pragma unroll
          for (int e = 0; e < 3; e++) xq[e] = ldg_rlx128(dp + e * 16);
          if (__all_sync(0xffffffffu, (orx(orx(orx(0, xq[0].x, T), xq[1].x, T), xq[2].x, T) & 1) == 0)) break;
          if (++n > SPIN) TIMEOUT(__LINE__)
        }
        if (t == 0) {
          sts32(sb + SM_SEL, owner ? (wn.ci & 1) * 64 + wn.rr : 0x7FFFFFFFu);
          if (wn.ci != 2 * i) mbar_arrive(sb + BAR_FIX);
          if (wn.ci != 2 * i + 1) mbar_arrive(sb + BAR_FIX + 8);
        }
        STAMPIF(1, 88);
      }
      float s[8];
#pragma unroll
      for (int e = 0; e < 8; e++) s[e] = 0.f;
#pragma unroll
      for (int r = 0; r < 12; r++) {
        const float x = asf((&xq[0].x)[r]);
        s[0] = fmaf(x, bf_lo(wv[r].x), s[0]); s[1] = fmaf(x, bf_hi(wv[r].x), s[1]);
        s[2] = fmaf(x, bf_lo(wv[r].y), s[2]); s[3] = fmaf(x, bf_hi(wv[r].y), s[3]);
        s[4] = fmaf(x, bf_lo(wv[r].z), s[4]); s[5] = fmaf(x, bf_hi(wv[r].z), s[5]);
        s[6] = fmaf(x, bf_lo(wv[r].w), s[6]); s[7] = fmaf(x, bf_hi(wv[r].w), s[7]);
      }
      sts128(sb + SM_R + a * 864 + gi * 32, asu(s[0]), asu(s[1]), asu(s[2]), asu(s[3]));
      sts128(sb + SM_R + a * 864 + gi * 32 + 16, asu(s[4]), asu(s[5]), asu(s[6]), asu(s[7]));
      nb_sync(NB_AUX, 96);
      const uint32_t ad = sb + SM_R + pk * 16;
      const uint4 u0 = lds128(ad), u1 = lds128(ad + 864), u2 = lds128(ad + 1728);
      stg128(sc + (o_part + i * 864 + pk * 16), ftag(asf(u0.x) + asf(u1.x) + asf(u2.x), par), ftag(asf(u0.y) + asf(u1.y) + asf(u2.y), par),
             ftag(asf(u0.z) + asf(u1.z) + asf(u2.z), par), ftag(asf(u0.w) + asf(u1.w) + asf(u2.w), par));
      STAMPIF(1, 86);
    }
    if (owner) {
      uint2 u[3];
      int n = 0;
#pragma unroll 1
      while (true) {
#pragma unroll
        for (int m = 0; m < 3; m++) u[m] = ldg_rlx64(sc + (OFF(xsel) + t * 8) + m * 768);
        if (__all_sync(0xffffffffu, (orx(orx(orx(0, u[0].x, T), u[1].x, T), u[2].x, T) & 1) == 0)) break;
        if (++n > SPIN) TIMEOUT(__LINE__)
      }
      STAMPIF(1, 109);
      float s1 = 0.f, s2 = 0.f;
#pragma unroll
      for (int m = 0; m < 3; m++) {
        const float x0 = asf(u[m].x), x1 = asf(u[m].y);
        s1 += x0 + x1; s2 = fmaf(x0, x0, fmaf(x1, x1, s2));
        const unsigned cc = 96 * m + t - 36 * j;
        if (cc < 36u) sts32(sb + SM_X2S + cc * 4, __byte_perm(u[m].x, u[m].y, 0x7632));
      }
      wn.m = s1; wn.rstd = s2;
    }
    if (L == 0 || owner) {
      uint4 u[16];
      int n = 0;
#pragma unroll 1
      while (true) {
        uint32_t d0 = 0, d1 = 0;
#pragma unroll
        for (int e = 0; e < 16; e++) u[e] = ldg_rlx128(sc + (o_part + pk * 16) + e * 864);
        if (L == 1 && n == 0) {
#pragma unroll
          for (int s = 1; s < 32; s <<= 1) { wn.m += shx(wn.m, s); wn.rstd += shx(wn.rstd, s); }
          if (lane == 0) sts64(sb + SM_RED2 + a * 8, asu(wn.m), asu(wn.rstd));
        }
#pragma unroll
        for (int e = 0; e < 8; e++) { d0 = orx(d0, u[e].x, par); d1 = orx(d1, u[8 + e].x, par); }
        if (__all_sync(0xffffffffu, ((d0 | d1) & 1) == 0)) break;
        if (++n > SPIN) TIMEOUT(__LINE__)
      }
      STAMPIF(1, 118 + L);
      float4 z = make_float4(0.f, 0.f, 0.f, 0.f);
#pragma unroll
      for (int e = 0; e < 16; e++) { z.x += asf(u[e].x); z.y += asf(u[e].y); z.z += asf(u[e].z); z.w += asf(u[e].w); }
      const uint32_t h0 = pack_bf16(z.x, z.y), h1 = pack_bf16(z.z, z.w);
      const uint32_t l0 = pack_bf16(z.x - bf_lo(h0), z.y - bf_hi(h0)), l1 = pack_bf16(z.z - bf_lo(h1), z.w - bf_hi(h1));
      const uint32_t ad = sb + SM_BEXT + (pk >> 1) * 128 + (pk & 1) * 8;
      if (L == 0) {
        sts64(ad, h0, h1);
#pragma unroll
        for (int r = 3; r < 8; r++) sts64(ad + r * 16, 0u, 0u);
      }
      sts64(ad + 16 + L * 48, h0, h1); sts64(ad + 32 + L * 48, l0, l1);
      fence_async_smem();
      nb_sync(NB_AUX, 96);
      if (t == 0) {
        if (L == 1) {
          const uint4 ra = lds128(sb + SM_RED2);
          const uint2 rb = lds64(sb + SM_RED2 + 16);
          const float m2 = (asf(ra.x) + asf(ra.z) + asf(rb.x)) * (1.f / 576.f);
          const float rs2 = rsq(fmaxf((asf(ra.y) + asf(ra.w) + asf(rb.y)) * (1.f / 576.f) - m2 * m2, 0.f) + EPS);
          sts64(sb + SM_SEL + 8, asu(m2), asu(rs2));
          mbar_arrive(sb + BAR_FIX + (wn.ci & 1) * 8);
        } else {
          mbar_arrive(sb + BAR_FIX); mbar_arrive(sb + BAR_FIX + 8);
        }
        STAMP(83 + L * 4);
      }
    }
    lane = pin(lane);
    const unsigned char* const wsrc = (const unsigned char*)P.wd + ((ffn_c32(cta) + 2 * q) * 1152 + a * 384 + g * 16);
    if (L == 0) {
#pragma unroll
      for (int kb = 0; kb < 3; kb++) { load_wd(wd[kb], wsrc + (kb * 9216 + (kb ? pin0(wd[kb - 1][2][7]) : 0u))); perm_wd(wd[kb]); }
    }
    load_wd(wd[3], wsrc + 3 * 9216);
    load_wd(wd[4], wsrc + ((cta & 1) ? (ffn_c8(cta) - ffn_c32(cta)) * 1152 : 24 * 1152));
    perm_wd(wd[3]); perm_wd(wd[4]);
    const uint32_t o_y = pin(OFF(ypart) + (a * 24 + g) * 4096 + cta * 32 + q * 8 + pin0(wd[4][2][7]));
    STAMPIF(1, 89 + L);
    if (a == 2) load_wo_a(cx, P, T, L, 1, lane);
    nb_sync(NB_FFN, 224);
    {
      const uint32_t ad = sb + R_FPART + min(lane, 19) * 16;
      const uint4 u0 = lds128(ad), u1 = lds128(ad + 320), u2 = lds128(ad + 640), u3 = lds128(ad + 960);
      const uint4 wv = lds128(sb + SM_WIN);
      const float g0 = rbf((asf(u0.x) + asf(u1.x)) + (asf(u2.x) + asf(u3.x))), g1 = rbf((asf(u0.z) + asf(u1.z)) + (asf(u2.z) + asf(u3.z)));
      const float v0 = rbf((asf(u0.y) + asf(u1.y)) + (asf(u2.y) + asf(u3.y))), v1 = rbf((asf(u0.w) + asf(u1.w)) + (asf(u2.w) + asf(u3.w)));
      const float s0 = rbf(g0 * rcp(1.f + ex2(-1.4426950408889634f * g0))), s1 = rbf(g1 * rcp(1.f + ex2(-1.4426950408889634f * g1)));
      const uint32_t act = lane < 16 + (cta & 1) * 4 ? pack_bf16(s0 * v0, s1 * v1) : 0u;
      uint32_t b[5];
#pragma unroll
      for (int kb = 0; kb < 5; kb++) b[kb] = __shfl_sync(0xffffffffu, act, 4 * kb + q);
#pragma unroll
      for (int S = 0; S < 3; S++) {
        float y[4][4];
#pragma unroll
        for (int u = 0; u < 4; u++) mma8z(y[u], wd[2][S][2 * u], wd[2][S][2 * u + 1], b[2]);
#pragma unroll
        for (int u = 0; u < 4; u++) mma16(y[u], wd[0][S][2 * u], wd[0][S][2 * u + 1], wd[1][S][2 * u], wd[1][S][2 * u + 1], b[0], b[1]);
#pragma unroll
        for (int u = 0; u < 4; u++) mma16(y[u], wd[3][S][2 * u], wd[3][S][2 * u + 1], wd[4][S][2 * u], wd[4][S][2 * u + 1], b[3], b[4]);
        const float y0 = self(lane & 2, self(lane & 1, y[3][0], y[2][0]), self(lane & 1, y[1][0], y[0][0]));
        const float y1 = self(lane & 2, self(lane & 1, y[3][2], y[2][2]), self(lane & 1, y[1][2], y[0][2]));
        stg64(sc + o_y + S * 32768, ftag(y0, par), ftag(y1, par));
      }
      if (L == 0) nb_arrive(NB_FFN2, Q1_BOTH ? 352 : 224);
      wn.r = asf(wv.x); wn.m = asf(wv.y); wn.rstd = asf(wv.z); wn.ci = wv.w >> 6; wn.rr = wv.w & 63;
    }
    STAMPIF(1, 84 + L * 8);
    owner = (wn.ci >> 1) == i;
  }
  if (cta < 72) finalize_row(P, wn, T, 1, cta, a, lane);
  STAMPIF(1, 93);
  PROF_END();
#undef t
#undef g
#undef q
}

__device__ __forceinline__ int sched_box(const uint32_t at, const int a) {
  int r = -1;
#pragma unroll
  for (int b = 0; b < 6; b++) if (((at >> (4 * b)) & 15) != 15) r = a == (int)((at >> (4 * b)) & 15) ? b : r;
  return r;
}
__host__ __device__ constexpr int sched_first(const uint32_t at) { int b = 0; while (b < 6 && ((at >> (4 * b)) & 15) != 15) b++; return b; }
__host__ __device__ constexpr int sched_last(const uint32_t at) { int b = 5; while (b >= 0 && ((at >> (4 * b)) & 15) != 15) b--; return b; }
__device__ __forceinline__ void producer_role(const Ctx& cx, const Params& P, const int lane) {
  const int i = cx.i, j = cx.j;
  if (elect_one()) asm volatile("prefetch.tensormap [%0];" ::"l"(&P.mx) : "memory");
  const uint32_t T = __shfl_sync(0xffffffffu, (ldg_rlx32(P.sc->cflag[i * 2][j * 4]) >> 3) + 1, 0);
  const unsigned char* const wq = P.sc->wq[j][0];
  nb_sync(NB_START, 288);
#pragma unroll
  for (int s = 0; s < 2 * NA0; s++) w_tma3d(sb + SM_A + s * 8192, &P.mx, (s >> 1) * 64, s & 1, i * 64, sb + BAR_FULL + (s >> 1) * 16);
#pragma unroll
  for (int h = 0; h < 6; h++) w_expect(sb + BAR_FULL + h * 8, h & 1 ? 13824 : 13824 + 16384);
  STAMP(97);
  wait_flags<48>(P.sc->bflag[j], 8 * T + 1, lane);
  fence_async_glob();
  STAMP(120);
#pragma unroll
  for (int h = 0; h < 6; h++) {
    w_bulk(sb + SM_B + h * 13824, wq + h * 13824, 13824, sb + BAR_FULL + h * 8);
    if (!(h & 1) && h >= 2 * NA0) {
      w_tma3d(sb + SM_A + h * 8192, &P.mx, h * 32, 0, i * 64, sb + BAR_FULL + h * 8);
      w_tma3d(sb + SM_A + h * 8192 + 8192, &P.mx, h * 32, 1, i * 64, sb + BAR_FULL + h * 8);
    }
  }
  PSTAMP(0);
  nb_arrive(NB_GO, 128);
  mbar_wait(sb + BAR_FULL + PF_WAIT * 8, 0);
  w_prefetch((const unsigned char*)P.wd + cx.cta * 41472, 10368);
  const unsigned char* const xb = P.sc->xbuf[i * 2];
  const unsigned char* const fp = (const unsigned char*)P.sc->bflag[j] + lane * 32;
  uint32_t f0 = 0, f1 = 0;
#pragma unroll 1
  for (int L = 0; L < 2; L++) {
    if (L == 1 && !LATE_Q1) {
#pragma unroll 1
      for (int p = 0; p < 2; p++) {
        mbar_wait(sb + BAR_AEMPTY + (2 + 3 * p) * 8, 0);
        wait_flags<32>(P.sc->cflag[i * 2 + p], 8 * T + 1, lane);
        fence_async_glob();
        STAMP(104 + p);
#pragma unroll
        for (int a = 0; a < 3; a++) {
          const int s = 2 * a + p;
          w_expect(sb + BAR_AFULL + s * 8, 8192);
          w_bulk(sb + SM_A + s * 8192, xb + (p * 73728 + a * 8192), 8192, sb + BAR_AFULL + s * 8);
          PSTAMP(48 + 36 + 3 * p + a);
        }
      }
    }
#pragma unroll 1
    for (int a = 3; a < 15; a++) {
      if (a == 12) {
        load_wo_a(cx, P, T, L, 0, lane);
        if (L == 1) break;
        if (LATE_Q1) {
#pragma unroll 1
          for (int b = LATE_G0; b < 6; b++) {
            if (LATE_GGAP) { const int c0 = clock(); while ((int)(clock() - c0) < LATE_GGAP) {} }
            load_gu(P, cx.cta, 0, b, sb + BAR_GU);
          }
#pragma unroll 1
          for (int p = 0; p < 2; p++) {
            mbar_wait(sb + BAR_AEMPTY + (2 + 3 * p) * 8, 0);
            wait_flags<32>(P.sc->cflag[i * 2 + p], 8 * T + 1, lane);
            STAMP(104 + p);
          }
          fence_async_glob();
          mbar_wait(sb + BAR_ST, 0);
#pragma unroll 1
          for (int s = 0; s < 3; s++) {
            const uint32_t fb = sb + BAR_FULL + s * 16, ab = sb + BAR_AFULL + s * 16, db = sb + SM_B + s * 27648, da = sb + SM_A + s * 16384;
            mbar_wait(sb + BAR_EMPTY + s * 16, 1);
            w_expect(fb, 13824);
            w_bulk(db, wq + s * 27648, 13824, fb);
            w_expect(ab, 8192);
            w_bulk(da, xb + s * 8192, 8192, ab);
            w_expect(ab + 8, 8192);
            w_bulk(da + 8192, xb + (73728 + s * 8192), 8192, ab + 8);
            mbar_wait(sb + BAR_EMPTY + s * 16 + 8, 1);
            w_expect(fb + 8, 13824);
            w_bulk(db + 13824, wq + (s * 27648 + 13824), 13824, fb + 8);
          }
          break;
        }
      }
      const int r = (a * 11) >> 5, s = a - 3 * r;
      const uint32_t fb = sb + BAR_FULL + s * 16, da = sb + SM_A + s * 16384, db = sb + SM_B + s * 27648;
      const unsigned char* bsrc = wq + (a < 9 ? a : a < 12 ? 72 - 6 * j + s : s) * 27648;
      const unsigned char* asrc = xb + a * 8192;
      const int kc = (a < 9 ? a : j + a - 10) * 64;
      const int amode = a == 9 || a > 11 ? 0 : L == 0 ? 1 : a < 9 ? 2 : 0;
      mbar_wait(sb + BAR_EMPTY + s * 16, (r & 1) ^ 1);
      if (ST_HOLD && a == ST_HOLD) mbar_wait(sb + BAR_ST, 0);
      if (L == 0) {
        if (a == 4 || a == 8) {
          const uint32_t need = 8 * T + (a == 4 ? 3 : 4);
          if (__any_sync(0xffffffffu, (int)((f0 - need) | (f1 - need)) < 0)) wait_flags<48>(P.sc->bflag[j], need, lane);
          fence_async_glob();
          STAMP(120 + (a >> 1));
        }
        if (a == 3 || a == 7) { f0 = ldg_rlx32(fp); f1 = ldg_rlx32(fp + (lane < 16 ? 1024 : 0)); }
      }
      w_bulk(db, bsrc, 13824, fb);
      w_expect(fb, amode ? 13824 + 16384 : 13824);
      mbar_wait(sb + BAR_EMPTY + s * 16 + 8, (r & 1) ^ 1);
      if (amode == 1) {
        w_tma3d(da, &P.mx, kc, 0, i * 64, fb);
        w_tma3d(da + 8192, &P.mx, kc, 1, i * 64, fb);
      } else if (amode == 2) {
        w_bulk(da, asrc, 8192, fb);
        w_bulk(da + 8192, asrc + 73728, 8192, fb);
      }
      w_bulk(db + 13824, bsrc + 13824, 13824, fb + 8);
      w_expect(fb + 8, 13824);
      PSTAMP(a < 12 ? L * 24 + a : 12 + a);
      if (L == 0) {
        {
          if (a >= WD_PF && a < WD_PF + 3) w_prefetch((const unsigned char*)P.wd + (cx.cta * 4 + a - WD_PF + 1) * 10368, 10368);
          if (a >= PG_0 && a < PG_0 + 6) w_prefetch((const unsigned char*)P.wg + ((a - PG_0) * 128 + cx.cta) * 6912, 6912);
        }
        if (a == 3) w_expect(sb + BAR_GU, 12 * (6144 + (cx.cta & 1) * 1536));
        {
          const int bu = sched_box(U_AT, a), bg = sched_box(G_AT, a);
          if (bu >= 0) load_gu(P, cx.cta, 1, bu, sb + BAR_GU);
          if (bg >= 0) load_gu(P, cx.cta, 0, bg, sb + BAR_GU);
          if (a == U_WIN) {
#pragma unroll 1
            for (int b = sched_first(U_AT); b <= sched_last(U_AT); b++) {
              const int c0 = clock();
              while ((int)(clock() - c0) < U_GAP) {}
              load_gu(P, cx.cta, 1, b, sb + BAR_GU);
            }
          }
          if (a == G_WIN) {
#pragma unroll 1
            for (int b = sched_first(G_AT); b <= sched_last(G_AT); b++) {
              const int c0 = clock();
              while ((int)(clock() - c0) < G_GAP) {}
              load_gu(P, cx.cta, 0, b, sb + BAR_GU);
            }
          }
        }
      }
    }
  }
}

template <bool BY_SMID>
__global__ void __launch_bounds__(384, 1) fused_kernel(const __grid_constant__ Params P) {
  extern __shared__ __align__(1024) unsigned char smem[];
  Ctx cx;
  STAMPIF(threadIdx.x == 64, 125);
  unsigned id;
  if (BY_SMID) asm volatile("mov.u32 %0, %%smid;" : "=r"(id)); else id = blockIdx.x;
  const int work = __shfl_sync(0xffffffffu, (int)P.work[min(id, 131u)], 0);
  const int warp = __shfl_sync(0xffffffffu, (int)(threadIdx.x >> 5), 0), lane = threadIdx.x & 31;
  if (work < 0) {
    if (warp == 0) {
      const int sp = -1 - work;
      if (lane == 0) { mbar_init(sb, 1); fence_async_smem(); }
      __syncwarp();
      __nanosleep(SPARE_DELAY);
#pragma unroll 1
      for (int k = 32 + sp; k < 72; k += 4) w_prefetch((const unsigned char*)P.wqkv + k * 27648, 27648);
#pragma unroll 1
      for (int k = sp; k < 24; k += 4) w_prefetch((const unsigned char*)P.wo + k * 27648, 27648);
#pragma unroll 1
      for (int k = sp; k < X_NU; k += 4) w_prefetch((const unsigned char*)P.wu + k * 27648, 27648);
      w_expect(sb, 16);
      w_bulk(sb + 128, P.wr, 16, sb);
      mbar_wait(sb, 0);
    }
    return;
  }
  cx.cta = work; cx.i = work >> 3; cx.j = work & 7;
  STAMPIF(threadIdx.x == 32, 95);
  if (warp < 8) {
    if (warp == 0) {
      if (elect_one()) {
        if ((uint32_t)__cvta_generic_to_shared(smem) != sb) __trap();
#pragma unroll
        for (int b = 0; b < 48; b++) mbar_init(sb + SM_BAR + b * 8, b < 34 ? 1 : b < 42 ? 4 : 8);
        fence_async_smem();
      }
      __syncwarp();
    }
    consumer_role(cx, P, smem, warp >> 2, warp & 3, lane);
  } else if (warp < 11) {
    aux_role(cx, P, warp - 8, lane);
  } else {
    producer_role(cx, P, lane);
  }
}

int work_of_smid(int smid) {
  const int t = smid >> 1;
  if (t == 60 || t == 61) return -1 - ((t - 60) * 2 + (smid & 1));
  const int gpc = t < 32 ? t & 7 : t < 60 ? 1 + (t - 32) % 7 : 0;
  const int x = 2 * (t < 32 ? t >> 3 : t < 60 ? 4 + (t - 32) / 7 : t - 58) + (smid & 1);
  const int blk[8] = {6, 0, 2, 3, 4, 7, 5, 1}, b = blk[gpc];
  return ((b >> 1) * 4 + (x & 1) + (x >> 3) * 2) * 8 + (b & 1) * 4 + ((x >> 1) & 3);
}

typedef CUresult (*EncodeFn)(CUtensorMap*, CUtensorMapDataType, cuuint32_t, void*, const cuuint64_t*, const cuuint64_t*,
                             const cuuint32_t*, const cuuint32_t*, CUtensorMapInterleave, CUtensorMapSwizzle,
                             CUtensorMapL2promotion, CUtensorMapFloatOOBfill);

void make_map(EncodeFn enc, CUtensorMap* m, const void* base, int rank, const cuuint64_t* dims, const cuuint64_t* strides,
              const cuuint32_t* box, CUtensorMapSwizzle sw, CUtensorMapL2promotion promo = CU_TENSOR_MAP_L2_PROMOTION_L2_128B) {
  const cuuint32_t es[3] = {1, 1, 1};
  enc(m, CU_TENSOR_MAP_DATA_TYPE_BFLOAT16, rank, const_cast<void*>(base), dims, strides, box, es, CU_TENSOR_MAP_INTERLEAVE_NONE, sw,
      promo, CU_TENSOR_MAP_FLOAT_OOB_FILL_NONE);
}

}

extern "C" void kernel_launch(void* const* d_in, const int* in_sizes, int n_in, void* d_out, int out_size) {
  (void)in_sizes; (void)n_in; (void)out_size;
  static EncodeFn enc = nullptr;
  static int nsm = 0;
  static void* scr = nullptr;
  if (!enc) {
    void* f = nullptr;
    cudaDriverEntryPointQueryResult qr;
    cudaGetDriverEntryPoint("cuTensorMapEncodeTiled", &f, cudaEnableDefault, &qr);
    enc = (EncodeFn)f;
    cudaGetSymbolAddress(&scr, g_scratch);
    int dev = 0;
    cudaGetDevice(&dev);
    cudaDeviceGetAttribute(&nsm, cudaDevAttrMultiProcessorCount, dev);
    cudaFuncSetAttribute(fused_kernel<true>, cudaFuncAttributeMaxDynamicSharedMemorySize, SM_TOTAL);
    cudaFuncSetAttribute(fused_kernel<false>, cudaFuncAttributeMaxDynamicSharedMemorySize, SM_TOTAL);
  }
  Params P;
  P.x = (const __nv_bfloat16*)d_in[0];
  P.wqkv = (const __nv_bfloat16*)d_in[1];
  P.wo = (const __nv_bfloat16*)d_in[2];
  P.wr = (const __nv_bfloat16*)d_in[4];
  P.wg = (const __nv_bfloat16*)d_in[5];
  P.wu = (const __nv_bfloat16*)d_in[6];
  P.wd = (const __nv_bfloat16*)d_in[7];
  P.out = (__nv_bfloat16*)d_out;
  P.sc = (Scratch*)scr;
  for (int k = 0; k < 136; k++) P.work[k] = (signed char)(nsm == 132 ? (k < 132 ? work_of_smid(k) : -1) : (k < 128 ? k : k < 132 ? 127 - k : -1));
  {
    const cuuint64_t dims[3] = {576, 2, 1024}, str[2] = {1152, 2304};
    const cuuint32_t box[3] = {64, 1, 64};
    make_map(enc, &P.mx, P.x, 3, dims, str, box, CU_TENSOR_MAP_SWIZZLE_128B);
  }
  {
    const cuuint64_t dims[2] = {4608, 576}, str[1] = {9216};
    const cuuint32_t box[2] = {32, 96}, box8[2] = {8, 96};
    make_map(enc, &P.mg, d_in[5], 2, dims, str, box, CU_TENSOR_MAP_SWIZZLE_64B);
    make_map(enc, &P.mu, d_in[6], 2, dims, str, box, CU_TENSOR_MAP_SWIZZLE_64B);
    make_map(enc, &P.mg8, d_in[5], 2, dims, str, box8, CU_TENSOR_MAP_SWIZZLE_NONE);
    make_map(enc, &P.mu8, d_in[6], 2, dims, str, box8, CU_TENSOR_MAP_SWIZZLE_NONE);
  }
  if (nsm == 132) fused_kernel<true><<<132, 384, SM_TOTAL>>>(P);
  else fused_kernel<false><<<132, 384, SM_TOTAL>>>(P);
}
```

```cpp
#include <cuda_runtime.h>
#include <cuda.h>
#include <cuda_bf16.h>
#include <stdint.h>
#include <stddef.h>

namespace {

#define NPRE_ 4
constexpr int NPRE = NPRE_;
#define X_NU 192
#define CAND_W 8
#define HALO_V 0
#define X_DELAY 200
#define X_STEP 100
#define HOLD_C 13
#define NA0 3
#define B2_AT 0
#define LATE_WAIT 3
#define OUT_LATE 0
#define U_AT 0xFFFF75
#define G_AT 0xEEEEEB
#define PG_0 6
#define WD_PF 3
#define U_WIN 11
#define G_WIN 11
#define G_GAP 300
#define U_GAP 400
#define ST_HOLD 0
#define ST_P 1
#define LATE_Q1 1
#define LATE_G0 1
#define LATE_GGAP 600
#define Q1_BOTH 1
#define A32 1
#define WD_RES 1
#define REG_AUX 200
#define REG_CONS 152
#define REG_AT 1
#define WD_TRIG 0
#define PF_WAIT 0
#define POLL_GAP 100
#define SPARE_DELAY 400
constexpr float EPS = 1e-5f;
constexpr int SPIN = 1 << 22;
#define TIMEOUT(line) __trap();

struct __align__(128) Scratch {
  uint32_t bflag[8][48][8];
  uint32_t cflag[32][32][8];
  uint32_t halo[32][8][672];
  uint32_t stats[32][4][8][64];
  uint32_t cand[8][32][CAND_W];
  uint32_t xcand[32][8][48];
  uint32_t ypart[72][128][8];
  uint32_t zpart[8][16][216];
  uint32_t st0[2048][4];
  uint32_t xsel[2][576];
  unsigned char wq[8][9][27648];
  unsigned char wo[8][3][27648];
  unsigned char obuf[32][73728];
  unsigned char xbuf[32][73728];
};
__device__ Scratch g_scratch;
#define OFF(f) ((uint32_t)offsetof(Scratch, f))
#define STAMPD(v, k) do {} while (0)
#define STAMPIF(c, k) do {} while (0)
#define STAMP(k) do {} while (0)

constexpr uint32_t sb = 1024;
constexpr uint32_t SM_A = 0;
constexpr uint32_t SM_B = 49152;
constexpr uint32_t SM_G = 132096;
constexpr uint32_t SM_BEXT = 224256;

constexpr uint32_t SM_WIN = 227712;
constexpr uint32_t SM_XW = 228320;
constexpr uint32_t SM_YRED = 228448;
constexpr uint32_t SM_X2S = 228576;
constexpr uint32_t SM_RED2 = 228736;
constexpr uint32_t SM_WR = 228864;
constexpr uint32_t SM_R = 229168;
constexpr uint32_t SM_BEST = 231760;
constexpr uint32_t SM_SEL = 231824;
constexpr uint32_t SM_BAR = 231840;
constexpr uint32_t SM_TOTAL = 232448;
constexpr uint32_t R_FPART = SM_R;
constexpr uint32_t BAR_FULL = SM_BAR  , BAR_AFULL = SM_BAR + 48  , BAR_WFULL = SM_BAR + 96  , BAR_ST = SM_BAR + 240, BAR_GU = SM_BAR + 248,
                   BAR_FIX = SM_BAR + 256  , BAR_AEMPTY = SM_BAR + 272  , BAR_HDONE = SM_BAR + 320  ,
                   BAR_EMPTY = SM_BAR + 336  ;
enum { NB_WG = 1  , NB_STAG = 3, NB_AUX = 4, NB_FFN2 = 5, NB_FFN = 8, NB_START = 9, NB_GO = 6, NB_ORD = 7 };

struct Params {
  const __nv_bfloat16 *wqkv, *x, *wr, *wo;
  Scratch* sc;
  const __nv_bfloat16 *wd, *wg, *wu;
  __nv_bfloat16* out;
  signed char work[136];
  CUtensorMap mx, mg, mu, mg8, mu8;
};

__device__ __forceinline__ void mbar_init(uint32_t bar, int cnt) { asm volatile("mbarrier.init.shared::cta.b64 [%0], %1;" ::"r"(bar), "r"(cnt) : "memory"); }
__device__ __forceinline__ void mbar_arrive(uint32_t bar) { asm volatile("mbarrier.arrive.shared::cta.b64 _, [%0];" ::"r"(bar) : "memory"); }
__device__ __forceinline__ void mbar_wait(uint32_t bar, uint32_t par) {
  asm volatile("{\n.reg .pred p;\nLOOP:\nmbarrier.try_wait.parity.shared::cta.b64 p, [%0], %1;\n@!p bra.uni LOOP;\n}\n" ::"r"(bar), "r"(par) : "memory");
}
__device__ __forceinline__ uint32_t mbar_test(uint32_t bar, uint32_t par) {
  uint32_t ok;
  asm volatile("{\n.reg .pred p;\nmbarrier.test_wait.parity.shared::cta.b64 p, [%1], %2;\nselp.u32 %0,1,0,p;\n}" : "=r"(ok) : "r"(bar), "r"(par) : "memory");
  return ok;
}
__device__ __forceinline__ bool elect_one() {
  uint32_t ok;
  asm volatile("{\n.reg .pred p;\nelect.sync _|p, 0xffffffff;\nselp.u32 %0, 1, 0, p;\n}" : "=r"(ok));
  return ok;
}
__device__ __forceinline__ float ex2(float x) { float r; asm("ex2.approx.ftz.f32 %0, %1;" : "=f"(r) : "f"(x)); return r; }
__device__ __forceinline__ float rsq(float x) { float r; asm("rsqrt.approx.ftz.f32 %0, %1;" : "=f"(r) : "f"(x)); return r; }
__device__ __forceinline__ float rcp(float x) { float r; asm("rcp.approx.ftz.f32 %0, %1;" : "=f"(r) : "f"(x)); return r; }
__device__ __forceinline__ void w_expect(uint32_t bar, uint32_t bytes) {
  asm volatile("{\n.reg .pred p;\nelect.sync _|p, 0xffffffff;\n@p mbarrier.arrive.expect_tx.shared::cta.b64 _, [%0], %1;\n}" ::"r"(bar), "r"(bytes) : "memory");
}
__device__ __forceinline__ void w_bulk(uint32_t dst, const void* src, uint32_t bytes, uint32_t bar) {
  asm volatile("{\n.reg .pred p;\nelect.sync _|p, 0xffffffff;\n@p cp.async.bulk.shared::cluster.global.mbarrier::complete_tx::bytes [%0], [%1], %2, [%3];\n}" ::"r"(dst), "l"(src), "r"(bytes), "r"(bar) : "memory");
}
__device__ __forceinline__ void w_tma2d(uint32_t dst, const CUtensorMap* m, int c0, int c1, uint32_t bar) {
  asm volatile("{\n.reg .pred p;\nelect.sync _|p, 0xffffffff;\n@p cp.async.bulk.tensor.2d.shared::cluster.global.mbarrier::complete_tx::bytes [%0], [%1, {%3, %4}], [%2];\n}" ::"r"(dst), "l"(m), "r"(bar), "r"(c0), "r"(c1) : "memory");
}
__device__ __forceinline__ void w_tma3d(uint32_t dst, const CUtensorMap* m, int c0, int c1, int c2, uint32_t bar) {
  asm volatile("{\n.reg .pred p;\nelect.sync _|p, 0xffffffff;\n@p cp.async.bulk.tensor.3d.shared::cluster.global.mbarrier::complete_tx::bytes [%0], [%1, {%3, %4, %5}], [%2];\n}" ::"r"(dst), "l"(m), "r"(bar), "r"(c0), "r"(c1), "r"(c2) : "memory");
}
__device__ __forceinline__ void w_prefetch(const void* src, uint32_t bytes) {
  asm volatile("{\n.reg .pred p;\nelect.sync _|p, 0xffffffff;\n@p cp.async.bulk.prefetch.L2.global [%0], %1;\n}" ::"l"(src), "r"(bytes) : "memory");
}
__device__ __forceinline__ void nb_sync(int id, int n) { asm volatile("bar.sync %0, %1;" ::"r"(id), "r"(n) : "memory"); }
__device__ __forceinline__ void nb_arrive(int id, int n) { asm volatile("bar.arrive %0, %1;" ::"r"(id), "r"(n) : "memory"); }
__device__ __forceinline__ void fence_async_smem() { asm volatile("fence.proxy.async.shared::cta;" ::: "memory"); }
__device__ __forceinline__ void fence_async_glob() { asm volatile("fence.proxy.async.global;" ::: "memory"); }
__device__ __forceinline__ void flag_after(void* p, uint32_t readback, uint32_t T, bool writer) {
  asm volatile("{\n.reg .pred p;\n.reg .u32 v;\nsetp.ne.u32 p, %3, 0;\nor.b32 v, %1, %2;\nmin.u32 v, v, %2;\n@p st.relaxed.gpu.global.u32 [%0], v;\n}"
               ::"l"(p), "r"(readback), "r"(T), "r"((uint32_t)writer) : "memory");
}
__device__ __forceinline__ uint4 ldg_rlx128(const void* p) { uint4 v; asm volatile("ld.relaxed.gpu.global.v4.b32 {%0,%1,%2,%3}, [%4];" : "=r"(v.x), "=r"(v.y), "=r"(v.z), "=r"(v.w) : "l"(p) : "memory"); return v; }
__device__ __forceinline__ uint2 ldg_rlx64(const void* p) { uint2 v; asm volatile("ld.relaxed.gpu.global.v2.b32 {%0,%1}, [%2];" : "=r"(v.x), "=r"(v.y) : "l"(p) : "memory"); return v; }
__device__ __forceinline__ void rld128(uint4& v, const void* p) { asm volatile("ld.relaxed.gpu.global.v4.b32 {%0,%1,%2,%3}, [%4];" : "+r"(v.x), "+r"(v.y), "+r"(v.z), "+r"(v.w) : "l"(p) : "memory"); }
__device__ __forceinline__ uint32_t ldg_rlx32(const void* p) { uint32_t v; asm volatile("ld.relaxed.gpu.global.b32 %0, [%1];" : "=r"(v) : "l"(p) : "memory"); return v; }
#define NC_HINT ""
__device__ __forceinline__ uint4 ldg_nc128(const void* p) { uint4 v; asm volatile("ld.global.nc" NC_HINT ".v4.b32 {%0,%1,%2,%3}, [%4];" : "=r"(v.x), "=r"(v.y), "=r"(v.z), "=r"(v.w) : "l"(p)); return v; }
#define WD_HINT ".nc.L1::no_allocate"
__device__ __forceinline__ uint4 ldg_wd128(const void* p) { uint4 v; asm volatile("ld.global" WD_HINT ".v4.b32 {%0,%1,%2,%3}, [%4];" : "=r"(v.x), "=r"(v.y), "=r"(v.z), "=r"(v.w) : "l"(p)); return v; }
__device__ __forceinline__ uint32_t ldg_nc32(const void* p) { uint32_t v; asm volatile("ld.global.nc.L1::no_allocate.b32 %0, [%1];" : "=r"(v) : "l"(p)); return v; }
__device__ __forceinline__ void stg128(void* p, uint32_t a, uint32_t b, uint32_t c, uint32_t d) { asm volatile("st.relaxed.gpu.global.v4.b32 [%0], {%1,%2,%3,%4};" ::"l"(p), "r"(a), "r"(b), "r"(c), "r"(d) : "memory"); }
__device__ __forceinline__ void stg64(void* p, uint32_t a, uint32_t b) { asm volatile("st.relaxed.gpu.global.v2.b32 [%0], {%1,%2};" ::"l"(p), "r"(a), "r"(b) : "memory"); }
__device__ __forceinline__ void stg32(void* p, uint32_t a) { asm volatile("st.relaxed.gpu.global.b32 [%0], %1;" ::"l"(p), "r"(a) : "memory"); }
__device__ __forceinline__ void sts128(uint32_t a, uint32_t x, uint32_t y, uint32_t z, uint32_t w) { asm volatile("st.shared.v4.b32 [%0], {%1,%2,%3,%4};" ::"r"(a), "r"(x), "r"(y), "r"(z), "r"(w) : "memory"); }
__device__ __forceinline__ void sts64(uint32_t a, uint32_t x, uint32_t y) { asm volatile("st.shared.v2.b32 [%0], {%1,%2};" ::"r"(a), "r"(x), "r"(y) : "memory"); }
__device__ __forceinline__ void sts32(uint32_t a, uint32_t x) { asm volatile("st.shared.b32 [%0], %1;" ::"r"(a), "r"(x) : "memory"); }
__device__ __forceinline__ void stsf(uint32_t a, float x) { sts32(a, __float_as_uint(x)); }
__device__ __forceinline__ uint4 lds128(uint32_t a) { uint4 v; asm volatile("ld.shared.v4.b32 {%0,%1,%2,%3}, [%4];" : "=r"(v.x), "=r"(v.y), "=r"(v.z), "=r"(v.w) : "r"(a) : "memory"); return v; }
__device__ __forceinline__ uint2 lds64(uint32_t a) { uint2 v; asm volatile("ld.shared.v2.b32 {%0,%1}, [%2];" : "=r"(v.x), "=r"(v.y) : "r"(a) : "memory"); return v; }
__device__ __forceinline__ uint32_t lds32(uint32_t a) { uint32_t v; asm volatile("ld.shared.b32 %0, [%1];" : "=r"(v) : "r"(a) : "memory"); return v; }
__device__ __forceinline__ uint32_t pack_bf16(float lo, float hi) { uint32_t r; asm("cvt.rn.bf16x2.f32 %0, %1, %2;" : "=r"(r) : "f"(hi), "f"(lo)); return r; }
__device__ __forceinline__ float bf_lo(uint32_t w) { return __uint_as_float(w << 16); }
__device__ __forceinline__ float bf_hi(uint32_t w) { return __uint_as_float(w & 0xFFFF0000u); }
__device__ __forceinline__ float rbf(float x) { return bf_lo(pack_bf16(x, 0.f)); }
__device__ __forceinline__ float asf(uint32_t u) { return __uint_as_float(u); }
__device__ __forceinline__ uint32_t asu(float f) { return __float_as_uint(f); }
__device__ __forceinline__ float shx(float v, int m) { return __shfl_xor_sync(0xffffffffu, v, m); }
__device__ __forceinline__ uint32_t movm(uint32_t a) { uint32_t o; asm volatile("movmatrix.sync.aligned.m8n8.trans.b16 %0, %1;" : "=r"(o) : "r"(a)); return o; }
__device__ __forceinline__ void ldsm2(uint32_t& a, uint32_t& b, uint32_t addr) { asm volatile("ldmatrix.sync.aligned.m8n8.x2.shared.b16 {%0,%1}, [%2];" : "=r"(a), "=r"(b) : "r"(addr) : "memory"); }
__device__ __forceinline__ void ldsm4t(uint32_t* r, uint32_t addr) { asm volatile("ldmatrix.sync.aligned.m8n8.x4.trans.shared.b16 {%0,%1,%2,%3}, [%4];" : "=r"(r[0]), "=r"(r[1]), "=r"(r[2]), "=r"(r[3]) : "r"(addr) : "memory"); }
__device__ __forceinline__ void stsm4(uint32_t addr, uint32_t a, uint32_t b, uint32_t c, uint32_t d) { asm volatile("stmatrix.sync.aligned.m8n8.x4.shared.b16 [%0], {%1,%2,%3,%4};" ::"r"(addr), "r"(a), "r"(b), "r"(c), "r"(d) : "memory"); }
__device__ __forceinline__ void stsm2(uint32_t addr, uint32_t a, uint32_t b) { asm volatile("stmatrix.sync.aligned.m8n8.x2.shared.b16 [%0], {%1,%2};" ::"r"(addr), "r"(a), "r"(b) : "memory"); }
__device__ __forceinline__ void mma16(float* d, uint32_t a0, uint32_t a1, uint32_t a2, uint32_t a3, uint32_t b0, uint32_t b1) {
  asm volatile("mma.sync.aligned.m16n8k16.row.col.f32.bf16.bf16.f32 {%0,%1,%2,%3},{%4,%5,%6,%7},{%8,%9},{%0,%1,%2,%3};"
               : "+f"(d[0]), "+f"(d[1]), "+f"(d[2]), "+f"(d[3]) : "r"(a0), "r"(a1), "r"(a2), "r"(a3), "r"(b0), "r"(b1));
}
__device__ __forceinline__ void mma16z(float* d, uint32_t a0, uint32_t a1, uint32_t a2, uint32_t a3, uint32_t b0, uint32_t b1) {
  asm volatile("mma.sync.aligned.m16n8k16.row.col.f32.bf16.bf16.f32 {%0,%1,%2,%3},{%4,%5,%6,%7},{%8,%9},{%10,%10,%10,%10};"
               : "=f"(d[0]), "=f"(d[1]), "=f"(d[2]), "=f"(d[3]) : "r"(a0), "r"(a1), "r"(a2), "r"(a3), "r"(b0), "r"(b1), "f"(0.f));
}
__device__ __forceinline__ void mma8(float* d, uint32_t a0, uint32_t a1, uint32_t b0) {
  asm volatile("mma.sync.aligned.m16n8k8.row.col.f32.bf16.bf16.f32 {%0,%1,%2,%3},{%4,%5},{%6},{%0,%1,%2,%3};"
               : "+f"(d[0]), "+f"(d[1]), "+f"(d[2]), "+f"(d[3]) : "r"(a0), "r"(a1), "r"(b0));
}
__device__ __forceinline__ uint32_t pin(uint32_t v) { uint32_t r; asm volatile("shfl.sync.bfly.b32 %0, %1, 0, 31, 0xffffffff;" : "=r"(r) : "r"(v)); return r; }
__device__ __forceinline__ uint32_t pin0(uint32_t v) { uint32_t r; asm volatile("{\n.reg .u32 t;\nor.b32 t, %1, 1;\nbfind.shiftamt.u32 %0, t;\nshr.u32 %0, %0, 5;\n}" : "=r"(r) : "r"(v)); return r; }
__device__ __forceinline__ void mma8z(float* d, uint32_t a0, uint32_t a1, uint32_t b0) {
  asm volatile("mma.sync.aligned.m16n8k8.row.col.f32.bf16.bf16.f32 {%0,%1,%2,%3},{%4,%5},{%6},{%7,%7,%7,%7};"
               : "=f"(d[0]), "=f"(d[1]), "=f"(d[2]), "=f"(d[3]) : "r"(a0), "r"(a1), "r"(b0), "f"(0.f));
}
__device__ __forceinline__ void wg_fence() { asm volatile("wgmma.fence.sync.aligned;" ::: "memory"); }
__device__ __forceinline__ void wg_commit() { asm volatile("wgmma.commit_group.sync.aligned;" ::: "memory"); }
template <int N> __device__ __forceinline__ void wg_wait() { asm volatile("wgmma.wait_group.sync.aligned %0;" ::"n"(N) : "memory"); }
template <int N> __device__ __forceinline__ void fence_regs(float* d) {
#pragma unroll
  for (int k = 0; k < N; k++) asm volatile("" : "+f"(d[k])::"memory");
}
__host__ __device__ constexpr uint32_t DLO(uint32_t addr, uint32_t lbo) { return (addr >> 4) | ((lbo >> 4) << 16); }
__host__ __device__ constexpr uint32_t DHI(uint32_t sbo, uint32_t swz) { return (sbo >> 4) | (swz << 30); }
template <int N>
__device__ __forceinline__ void wait_flags(const void* base, const uint32_t V, const int lane) {
  const unsigned char* p = (const unsigned char*)base + lane * 32;
  const unsigned char* p2 = p + (lane < N - 32 ? 1024 : 0);
  uint32_t a0 = ldg_rlx32(p), a1 = N > 32 ? ldg_rlx32(p2) : V;
  __nanosleep(POLL_GAP);
  int n = 0;
#pragma unroll 1
  while (true) {
    const uint32_t b0 = ldg_rlx32(p), b1 = N > 32 ? ldg_rlx32(p2) : V;
    if (__all_sync(0xffffffffu, (int)((a0 - V) | (a1 - V)) >= 0)) break;
    a0 = ldg_rlx32(p); a1 = N > 32 ? ldg_rlx32(p2) : V;
    if (__all_sync(0xffffffffu, (int)((b0 - V) | (b1 - V)) >= 0)) break;
    if (++n > SPIN) TIMEOUT(__LINE__)
  }
}
__device__ __forceinline__ uint32_t ftag(float v, uint32_t par) { return (asu(v) & ~1u) | par; }
__device__ __forceinline__ uint32_t selu(uint32_t c, uint32_t a, uint32_t b) { uint32_t r; asm("{\n.reg .pred p;\nsetp.ne.u32 p, %1, 0;\nselp.b32 %0, %2, %3, p;\n}" : "=r"(r) : "r"(c), "r"(a), "r"(b)); return r; }
__device__ __forceinline__ float self(uint32_t c, float a, float b) { return asf(selu(c, asu(a), asu(b))); }
__device__ __forceinline__ uint32_t orx(uint32_t acc, uint32_t a, uint32_t ref) { uint32_t r; asm("lop3.b32 %0, %1, %2, %3, 0xF6;" : "=r"(r) : "r"(acc), "r"(a), "r"(ref)); return r; }
__device__ __forceinline__ uint32_t fkey(float r) {
  uint32_t u = asu(r);
  u = (u & 0x80000000u) ? ~u : (u | 0x80000000u);
  return (r == r) ? u : 0u;
}
__host__ __device__ constexpr int GI(int part, int t) { return t < 8 ? part * 8 + t : 24 + part; }

__device__ __forceinline__ void wgmma_ss_216(float* d, uint32_t al, uint32_t ah, uint32_t bl, uint32_t bh) {
  asm volatile("{\n.reg .b64 da, db;\nmov.b64 da, {%108, %109};\nmov.b64 db, {%110, %111};\n"
      "wgmma.mma_async.sync.aligned.m64n216k16.f32.bf16.bf16 {"
      "%0,%1,%2,%3,%4,%5,%6,%7,%8,%9,%10,%11,%12,%13,%14,%15,%16,%17,%18,%19,%20,%21,%22,%23,%24,%25,%26,"
      "%27,%28,%29,%30,%31,%32,%33,%34,%35,%36,%37,%38,%39,%40,%41,%42,%43,%44,%45,%46,%47,%48,%49,%50,%51,%52,%53,"
      "%54,%55,%56,%57,%58,%59,%60,%61,%62,%63,%64,%65,%66,%67,%68,%69,%70,%71,%72,%73,%74,%75,%76,%77,%78,%79,%80,"
      "%81,%82,%83,%84,%85,%86,%87,%88,%89,%90,%91,%92,%93,%94,%95,%96,%97,%98,%99,%100,%101,%102,%103,%104,%105,%106,%107"
      "}, da, db, 1, 1, 1, 0, 1;\n}\n"
      : "+f"(d[0]), "+f"(d[1]), "+f"(d[2]), "+f"(d[3]), "+f"(d[4]), "+f"(d[5]), "+f"(d[6]), "+f"(d[7]), "+f"(d[8]),
        "+f"(d[9]), "+f"(d[10]), "+f"(d[11]), "+f"(d[12]), "+f"(d[13]), "+f"(d[14]), "+f"(d[15]), "+f"(d[16]), "+f"(d[17]),
        "+f"(d[18]), "+f"(d[19]), "+f"(d[20]), "+f"(d[21]), "+f"(d[22]), "+f"(d[23]), "+f"(d[24]), "+f"(d[25]), "+f"(d[26]),
        "+f"(d[27]), "+f"(d[28]), "+f"(d[29]), "+f"(d[30]), "+f"(d[31]), "+f"(d[32]), "+f"(d[33]), "+f"(d[34]), "+f"(d[35]),
        "+f"(d[36]), "+f"(d[37]), "+f"(d[38]), "+f"(d[39]), "+f"(d[40]), "+f"(d[41]), "+f"(d[42]), "+f"(d[43]), "+f"(d[44]),
        "+f"(d[45]), "+f"(d[46]), "+f"(d[47]), "+f"(d[48]), "+f"(d[49]), "+f"(d[50]), "+f"(d[51]), "+f"(d[52]), "+f"(d[53]),
        "+f"(d[54]), "+f"(d[55]), "+f"(d[56]), "+f"(d[57]), "+f"(d[58]), "+f"(d[59]), "+f"(d[60]), "+f"(d[61]), "+f"(d[62]),
        "+f"(d[63]), "+f"(d[64]), "+f"(d[65]), "+f"(d[66]), "+f"(d[67]), "+f"(d[68]), "+f"(d[69]), "+f"(d[70]), "+f"(d[71]),
        "+f"(d[72]), "+f"(d[73]), "+f"(d[74]), "+f"(d[75]), "+f"(d[76]), "+f"(d[77]), "+f"(d[78]), "+f"(d[79]), "+f"(d[80]),
        "+f"(d[81]), "+f"(d[82]), "+f"(d[83]), "+f"(d[84]), "+f"(d[85]), "+f"(d[86]), "+f"(d[87]), "+f"(d[88]), "+f"(d[89]),
        "+f"(d[90]), "+f"(d[91]), "+f"(d[92]), "+f"(d[93]), "+f"(d[94]), "+f"(d[95]), "+f"(d[96]), "+f"(d[97]), "+f"(d[98]),
        "+f"(d[99]), "+f"(d[100]), "+f"(d[101]), "+f"(d[102]), "+f"(d[103]), "+f"(d[104]), "+f"(d[105]), "+f"(d[106]), "+f"(d[107])
      : "r"(al), "r"(ah), "r"(bl), "r"(bh));
}
__device__ __forceinline__ void wgmma_ss_72(float* d, uint32_t al, uint32_t ah, uint32_t bl, uint32_t bh) {
  asm volatile("{\n.reg .b64 da, db;\nmov.b64 da, {%36, %37};\nmov.b64 db, {%38, %39};\n"
      "wgmma.mma_async.sync.aligned.m64n72k16.f32.bf16.bf16 {"
      "%0,%1,%2,%3,%4,%5,%6,%7,%8,%9,%10,%11,%12,%13,%14,%15,%16,%17,%18,%19,%20,%21,%22,%23,%24,%25,%26,"
      "%27,%28,%29,%30,%31,%32,%33,%34,%35"
      "}, da, db, 1, 1, 1, 0, 1;\n}\n"
      : "+f"(d[0]), "+f"(d[1]), "+f"(d[2]), "+f"(d[3]), "+f"(d[4]), "+f"(d[5]), "+f"(d[6]), "+f"(d[7]), "+f"(d[8]),
        "+f"(d[9]), "+f"(d[10]), "+f"(d[11]), "+f"(d[12]), "+f"(d[13]), "+f"(d[14]), "+f"(d[15]), "+f"(d[16]), "+f"(d[17]),
        "+f"(d[18]), "+f"(d[19]), "+f"(d[20]), "+f"(d[21]), "+f"(d[22]), "+f"(d[23]), "+f"(d[24]), "+f"(d[25]), "+f"(d[26]),
        "+f"(d[27]), "+f"(d[28]), "+f"(d[29]), "+f"(d[30]), "+f"(d[31]), "+f"(d[32]), "+f"(d[33]), "+f"(d[34]), "+f"(d[35])
      : "r"(al), "r"(ah), "r"(bl), "r"(bh));
}
template <uint32_t BH>
__device__ __forceinline__ void wgmma_rs_216(float* d, uint32_t a0, uint32_t a1, uint32_t a2, uint32_t a3, uint32_t bl) {
  asm volatile("{\n.reg .b64 db;\nmov.b64 db, {%112, %113};\n"
      "wgmma.mma_async.sync.aligned.m64n216k16.f32.bf16.bf16 {"
      "%0,%1,%2,%3,%4,%5,%6,%7,%8,%9,%10,%11,%12,%13,%14,%15,%16,%17,%18,%19,%20,%21,%22,%23,%24,%25,%26,"
      "%27,%28,%29,%30,%31,%32,%33,%34,%35,%36,%37,%38,%39,%40,%41,%42,%43,%44,%45,%46,%47,%48,%49,%50,%51,%52,%53,"
      "%54,%55,%56,%57,%58,%59,%60,%61,%62,%63,%64,%65,%66,%67,%68,%69,%70,%71,%72,%73,%74,%75,%76,%77,%78,%79,%80,"
      "%81,%82,%83,%84,%85,%86,%87,%88,%89,%90,%91,%92,%93,%94,%95,%96,%97,%98,%99,%100,%101,%102,%103,%104,%105,%106,%107"
      "}, {%108,%109,%110,%111}, db, 1, 1, 1, 1;\n}\n"
      : "+f"(d[0]), "+f"(d[1]), "+f"(d[2]), "+f"(d[3]), "+f"(d[4]), "+f"(d[5]), "+f"(d[6]), "+f"(d[7]), "+f"(d[8]),
        "+f"(d[9]), "+f"(d[10]), "+f"(d[11]), "+f"(d[12]), "+f"(d[13]), "+f"(d[14]), "+f"(d[15]), "+f"(d[16]), "+f"(d[17]),
        "+f"(d[18]), "+f"(d[19]), "+f"(d[20]), "+f"(d[21]), "+f"(d[22]), "+f"(d[23]), "+f"(d[24]), "+f"(d[25]), "+f"(d[26]),
        "+f"(d[27]), "+f"(d[28]), "+f"(d[29]), "+f"(d[30]), "+f"(d[31]), "+f"(d[32]), "+f"(d[33]), "+f"(d[34]), "+f"(d[35]),
        "+f"(d[36]), "+f"(d[37]), "+f"(d[38]), "+f"(d[39]), "+f"(d[40]), "+f"(d[41]), "+f"(d[42]), "+f"(d[43]), "+f"(d[44]),
        "+f"(d[45]), "+f"(d[46]), "+f"(d[47]), "+f"(d[48]), "+f"(d[49]), "+f"(d[50]), "+f"(d[51]), "+f"(d[52]), "+f"(d[53]),
        "+f"(d[54]), "+f"(d[55]), "+f"(d[56]), "+f"(d[57]), "+f"(d[58]), "+f"(d[59]), "+f"(d[60]), "+f"(d[61]), "+f"(d[62]),
        "+f"(d[63]), "+f"(d[64]), "+f"(d[65]), "+f"(d[66]), "+f"(d[67]), "+f"(d[68]), "+f"(d[69]), "+f"(d[70]), "+f"(d[71]),
        "+f"(d[72]), "+f"(d[73]), "+f"(d[74]), "+f"(d[75]), "+f"(d[76]), "+f"(d[77]), "+f"(d[78]), "+f"(d[79]), "+f"(d[80]),
        "+f"(d[81]), "+f"(d[82]), "+f"(d[83]), "+f"(d[84]), "+f"(d[85]), "+f"(d[86]), "+f"(d[87]), "+f"(d[88]), "+f"(d[89]),
        "+f"(d[90]), "+f"(d[91]), "+f"(d[92]), "+f"(d[93]), "+f"(d[94]), "+f"(d[95]), "+f"(d[96]), "+f"(d[97]), "+f"(d[98]),
        "+f"(d[99]), "+f"(d[100]), "+f"(d[101]), "+f"(d[102]), "+f"(d[103]), "+f"(d[104]), "+f"(d[105]), "+f"(d[106]), "+f"(d[107])
      : "r"(a0), "r"(a1), "r"(a2), "r"(a3), "r"(bl), "n"(BH));
}

struct Ctx {
  int i, j, cta;
};
#define TSTAMP(k) do {} while (0)
#define PSTAMP(k) do {} while (0)
#define PROF_DUMP() do {} while (0)
#define PROF_END() do {} while (0)
#define GSTAMP(k) do {} while (0)
#define CSTAMP(k) STAMPIF(1, L * 40 + p * 20 + (k))

__device__ __forceinline__ int ffn_c32(int cta) { return 32 * cta; }
__device__ __forceinline__ int ffn_c8(int cta) { return 4096 + 8 * (cta >> 1); }
__device__ __forceinline__ void load_gu(const Params& P, const int cta_, const int mat, const int b, const uint32_t bar) {
  const int cta = cta_;
  w_tma2d(sb + SM_G + mat * 46080 + b * 6144, &P.mg + mat, ffn_c32(cta), b * 96, bar);
  if (cta & 1) w_tma2d(sb + SM_G + mat * 46080 + 36864 + b * 1536, &P.mg8 + mat, ffn_c8(cta), b * 96, bar);
}

struct Winner { float r, m, rstd; int ci, rr; };

__device__ __forceinline__ Winner poll_winner(const void* p, uint4 v, const uint32_t tg) {
  int n = 0;
#pragma unroll 1
  while (!__all_sync(0xffffffffu, ((v.y ^ (tg << 6)) >> 6) == 0)) {
    rld128(v, p);
    if (++n > SPIN) TIMEOUT(__LINE__)
  }
  uint32_t key = fkey(asf(v.x));
  uint32_t mx = __reduce_max_sync(0xffffffffu, key);
  int src = __ffs(__ballot_sync(0xffffffffu, key == mx)) - 1;
  Winner w;
  w.ci = src;
  w.r = asf(__shfl_sync(0xffffffffu, v.x, src));
  w.rr = (int)__shfl_sync(0xffffffffu, v.y, src) & 63;
  w.m = asf(__shfl_sync(0xffffffffu, v.z, src));
  w.rstd = asf(__shfl_sync(0xffffffffu, v.w, src));
  return w;
}

__device__ __forceinline__ float2 row_stats(const Params& P, const int r, const int lane) {
  const unsigned char* src = (const unsigned char*)P.x + (((r & ~127) + 2 * (r & 63) + ((r >> 6) & 1)) * 1152 + (lane & 15) * 16);
  uint4 v[4];
#pragma unroll
  for (int m = 0; m < 4; m++) v[m] = ldg_nc128(src + m * 256);
  uint2 v4;
  asm volatile("ld.global.nc.v2.b32 {%0,%1}, [%2];" : "=r"(v4.x), "=r"(v4.y) : "l"(src + (1024 - (lane & 15) * 8)));
  nb_arrive(NB_START, 288 + pin0(v4.x));
  const float sft = __shfl_sync(0xffffffffu, bf_lo(v[0].x), lane & 16);
  float s1 = 0.f, s2 = 0.f, s3 = 0.f;
#pragma unroll
  for (int e = 0; e < 18; e++) {
    const uint32_t u = e < 16 ? (&v[0].x)[e] : (&v4.x)[e - 16];
    const float d0 = bf_lo(u) - sft, d1 = bf_hi(u) - sft;
    s1 += d0 + d1; s2 = fmaf(d0, d0, s2); s3 = fmaf(d1, d1, s3);
  }
  s2 += s3;
#pragma unroll
  for (int o = 1; o < 16; o <<= 1) { s1 += shx(s1, o); s2 += shx(s2, o); }
  s1 *= (1.f / 576.f);
  return make_float2(s1 + sft, rsq(fmaxf(s2 * (1.f / 576.f) - s1 * s1, 0.f) + EPS));
}

struct Unit { uint4 v[3]; };
__device__ __forceinline__ Unit unit_load(const unsigned char* src) {
  Unit u;
#pragma unroll
  for (int m = 0; m < 3; m++) u.v[m] = ldg_nc128(src + m * 48);
  return u;
}
__device__ __forceinline__ uint32_t unit_store(unsigned char* sc, const Unit& u, const int lane, const uint32_t o0, const uint32_t o1, const uint32_t o2) {
  stg128(sc + o0, u.v[0].x, u.v[0].y, u.v[0].z, u.v[0].w);
  stg128(sc + o1, u.v[1].x, u.v[1].y, u.v[1].z, u.v[1].w);
  stg128(sc + o2, u.v[2].x, u.v[2].y, u.v[2].z, u.v[2].w);
  return ldg_rlx32(sc + ((lane & 3) == 0 ? o0 : (lane & 3) == 1 ? o1 : o2));
}

__device__ __forceinline__ void store_rows(const uint32_t stg, unsigned char* obase, const int skip, const int lane) {
#pragma unroll
  for (int m = 0; m < 5; m++) {
    const int e = lane + 32 * m, r = (e * 57) >> 9;
    const uint4 v = lds128(stg + min(e, 143) * 16);
    if (e < 144 && r != skip) *(uint4*)(obase + (r * (2304 - 144) + e * 16)) = v;
  }
}

__device__ __forceinline__ void consumer_role(const Ctx& cx, const Params& P, const unsigned char* smem, const int p, const int w, const int lane_) {
  int lane = lane_;
#define g (lane >> 2)
#define q (lane & 3)
#define first_lane (lane == 0)
  const int i = cx.i, j = cx.j, ip = i * 2 + p;
  unsigned char* const sc = (unsigned char*)P.sc;
  float m_lo = 0.f, m_hi = 0.f, rs_lo = 0.f, rs_hi = 0.f;
  uint32_t T = ldg_rlx32(P.sc->cflag[ip][j * 4 + w]);
  nb_sync(NB_ORD, 352);
  if (X_DELAY) { const int c0 = clock(); while ((int)(clock() - c0) < X_DELAY + (p * 4 + w) * X_STEP) {} }
  {
    const int t = min(w * 32 + lane, 95);
    uint32_t u0 = 0, u1 = 0, u2 = 0, u = 0;
    if (p == 0) {
      u0 = ldg_nc32((const uint32_t*)P.wr + t); u1 = ldg_nc32((const uint32_t*)P.wr + 96 + t); u2 = ldg_nc32((const uint32_t*)P.wr + 192 + t);
      u = ldg_nc32((const uint32_t*)P.wr + 36 * j + min(t, 35));
    }
    const int r = cx.cta * 16 + (p * 4 + w) * 2 + (lane >> 4);
    const float2 st = row_stats(P, r, lane);
    T = __shfl_sync(0xffffffffu, (T >> 3) + 1, 0);
    if ((lane & 15) == 0) stg128(sc + (OFF(st0) + r * 16), asu(st.x), asu(st.y), T, 0u);
    STAMPIF(1, 111);
    if (p == 0) {
      float s = (bf_lo(u0) + bf_hi(u0)) + (bf_lo(u1) + bf_hi(u1)) + (bf_lo(u2) + bf_hi(u2));
#pragma unroll
      for (int o = 1; o < 32; o <<= 1) s += shx(s, o);
      stsf(sb + SM_WR + 288 + w * 4, s);
      sts64(sb + SM_WR + min(t, 35) * 8, u << 16, u & 0xFFFF0000u);
    }
  }
#pragma unroll 1
  for (int L = 0; L < 2; L++) {
    lane = pin(lane);
    const uint32_t tg = 2 * T + L;
    float c_lo = 0.f, c_hi = 0.f;
    bool sel_lo = false, sel_hi = false;
    float acc[108];
#pragma unroll
    for (int k = 0; k < 108; k++) acc[k] = 0.f;
    fence_regs<108>(acc);
    {
      const uint32_t ah = L == 0 ? DHI(1024, 1) : DHI(128, 0);
      const uint32_t astep = L == 0 ? 2 : 128;
      const uint32_t a0 = (L == 0 ? DLO(sb + SM_A, 16) : DLO(sb + SM_A, 1024)) + p * 512;
      constexpr uint32_t bh = DHI(512, 0);
      if (L == 1) {
        const float ul = 1.f + rs_lo, uh = 1.f + rs_hi;
        const float vl = fmaxf(rcp(rs_lo * rs_lo) - EPS, 0.f), vh = fmaxf(rcp(rs_hi * rs_hi) - EPS, 0.f);
        c_lo = ul * rsq(vl * ul * ul + EPS);
        c_hi = uh * rsq(vh * uh * uh + EPS);
      }
      if (L == 1) mbar_wait(sb + BAR_AFULL + p * 8, 0);
      mbar_wait(sb + BAR_FULL, 0);
      if (L == 1 && (p == 1 || Q1_BOTH)) nb_sync(NB_FFN2, Q1_BOTH ? 352 : 224);
      CSTAMP(0); GSTAMP(120 + 2 * L);
      uint32_t e0 = 0, e1 = 0;
      bool prepped = false, gone = false;
      auto prep_ext = [&]() {
        const int row = p * 64 + w * 16 + g;
        if (L == 0) {
          const uint2 u0 = lds64(sb + SM_R + row * 8), u1 = lds64(sb + SM_R + row * 8 + 64);
          m_lo = asf(u0.x); c_lo = asf(u0.y); m_hi = asf(u1.x); c_hi = asf(u1.y);
        } else {
          const uint4 sv = lds128(sb + SM_SEL);
          sel_lo = (int)sv.x == row; sel_hi = (int)sv.x == row + 8;
          if (sel_lo) { m_lo = asf(sv.z); c_lo = asf(sv.w); }
          if (sel_hi) { m_hi = asf(sv.z); c_hi = asf(sv.w); }
        }
        const float hl = rbf(-m_lo), hh = rbf(-m_hi);
        const uint32_t em = selu(lane & 1, 0x0000FFFFu, 0xFFFFFFFFu);
        e0 = selu(lane & 2, selu(sel_lo && !(lane & 1), 0x3F803F80u, 0u), pack_bf16(hl, -m_lo - hl) & em);
        e1 = selu(lane & 2, selu(sel_hi && !(lane & 1), 0x3F803F80u, 0u), pack_bf16(hh, -m_hi - hh) & em);
      };
      bool pend = false;
#pragma unroll 1
      for (int r = 0; r < 3; r++) {
#pragma unroll
        for (int h = 0; h < 6; h++) {
          const uint32_t al = a0 + (h >> 1) * 1024 + (h & 1) * 2 * astep, bl = DLO(sb + SM_B, 128) + h * 864;
          const uint32_t nb = sb + BAR_FULL + ((h + 1) % 6) * 8, np = (r + (h == 5)) & 1;
          TSTAMP((6 * r + h) * 2);
          wg_fence();
          wgmma_ss_216(acc, al, ah, bl, bh);
          wgmma_ss_216(acc, al + astep, ah, bl + 16, bh);
          wg_commit();
          if (h == 5 && r == 2) break;
          const uint32_t ok = mbar_test(nb, np);
          if ((h == 1 || h == 3) && r == 0 && L == 1) mbar_wait(sb + BAR_AFULL + (h + 1 + p) * 8, 0);
          if (h == 0 && r == 1 && L == 0) {
          if (lane < 16) stg128(sc + (OFF(stats) + (ip * 4 + w) * 2048 + j * 256 + lane * 16), 0u, 0u, 0u, 0u);
          if (w == 3 && i < 15 && lane < 28) {
#pragma unroll
            for (int e = 0; e < 6; e++) stg128(sc + (OFF(halo) + ((ip + 2) * 8 + j) * 2688 + lane * 16) + e * 448, 0u, 0u, 0u, 0u);
          }
          if (w == 0 && lane < 2) stg128(sc + (OFF(cand) + (j * 32 + ip) * (CAND_W * 4) + lane * 16), 0u, 0u, 0u, 0u);
          }
          wg_wait<1>();
          if (first_lane && pend) mbar_arrive(sb + BAR_EMPTY + ((h + 5) % 6) * 8);
          pend = true;
          const bool hold = h == HOLD_C % 6 && r == HOLD_C / 6 && p == 1;
          if (hold || (!ok && !mbar_test(nb, np))) {
            wg_wait<0>();
            if (first_lane) mbar_arrive(sb + BAR_EMPTY + h * 8);
            pend = false;
            TSTAMP((6 * r + h) * 2 + 1);
            mbar_wait(nb, np);
            if (hold) {
              if (mbar_test(sb + BAR_FIX + 8, L)) { prep_ext(); prepped = true; }
              nb_sync(NB_STAG, 256);
            }
          }
        }
      }
      if (!prepped) {
        if (p == 0 && !gone && !mbar_test(sb + BAR_FIX, L)) { nb_arrive(NB_STAG, 256); gone = true; }
        mbar_wait(sb + BAR_FIX + p * 8, L);
        prep_ext();
      }
      wg_fence();
      wgmma_rs_216<DHI(128, 0)>(acc, e0, e1, 0u, 0u, DLO(sb + SM_BEXT, 0));
      wg_commit();
      if (p == 0 && !gone) nb_arrive(NB_STAG, 256);
      wg_wait<2>();
      if (first_lane && pend) mbar_arrive(sb + BAR_EMPTY + 32);
    }
    lane = pin(lane);
    const uint32_t fragoff = ip * 73728 + (9 * j) * 1024 + w * 256 + lane * 4;
    const uint32_t rboff = (min(lane, 17) >> 1) * 1024 + (lane < 18 ? lane & 1 : 0) * 128;
    const uint32_t hl16 = (lane < 4 ? lane : lane - 4) * 16;
    const uint32_t o_halo = pin(OFF(halo) + ((ip + (w == 3 ? 2 : 0)) * 8 + j) * 2688 + hl16);
    const uint32_t o_o = pin(OFF(obuf) + fragoff);
    nb_sync(NB_WG + p, 128);
    if ((o_halo | o_o) == 0xFFFFFFFFu) __trap();
    wg_wait<0>();
    fence_regs<108>(acc);
    if (first_lane) mbar_arrive(sb + BAR_EMPTY + 40);
    CSTAMP(1); GSTAMP(121 + 2 * L);
    {
      uint32_t Kh[9], Vh[9], Kl[9], Vl[9], Kx[9], Vx[9], Ql[9], Qh[9];
#pragma unroll
      for (int t = 0; t < 9; t++) {
        Kh[t] = pack_bf16(acc[4 * GI(1, t) + 2] * c_hi, acc[4 * GI(1, t) + 3] * c_hi);
        Vh[t] = pack_bf16(acc[4 * GI(2, t) + 2] * c_hi, acc[4 * GI(2, t) + 3] * c_hi);
        Ql[t] = pack_bf16(acc[4 * GI(0, t)], acc[4 * GI(0, t) + 1]);
        Qh[t] = pack_bf16(acc[4 * GI(0, t) + 2], acc[4 * GI(0, t) + 3]);
      }
      const uint32_t hbuf = sb + SM_A + p * 8192 + w * 2688 + hl16;
      if (w < 3) {
        if (lane >= 4) {
#pragma unroll
          for (int e = 0; e < 4; e++) sts128(hbuf + e * 448, Kh[2 * e], Kh[2 * e + 1], Vh[e], tg);
          sts128(hbuf + 4 * 448, Kh[8], Vh[4], Vh[5], tg);
          sts128(hbuf + 5 * 448, Vh[6], Vh[7], Vh[8], tg);
        }
      } else if (i < 15 && lane >= 4) {
#pragma unroll
        for (int e = 0; e < 4; e++) stg128(sc + o_halo + e * 448, Kh[2 * e], Kh[2 * e + 1], Vh[e], tg);
        stg128(sc + o_halo + 4 * 448, Kh[8], Vh[4], Vh[5], tg);
        stg128(sc + o_halo + 5 * 448, Vh[6], Vh[7], Vh[8], tg);
      }
      nb_sync(NB_WG + p, 128);
#pragma unroll
      for (int t = 0; t < 9; t++) {
        Kl[t] = pack_bf16(acc[4 * GI(1, t)] * c_lo, acc[4 * GI(1, t) + 1] * c_lo);
      }
#pragma unroll
      for (int t = 0; t < HALO_V; t++) Vl[t] = pack_bf16(acc[4 * GI(2, t)] * c_lo, acc[4 * GI(2, t) + 1] * c_lo);
      uint32_t dep = (Kl[0] ^ Kl[1] ^ Kl[2]) | (Kl[3] ^ Kl[4] ^ Kl[5]) | (Kl[6] ^ Kl[7] ^ Kl[8]);
#pragma unroll
      for (int t = 0; t < HALO_V; t += 3) dep |= Vl[t] ^ Vl[t + 1] ^ Vl[t + 2];
      const unsigned char* hp = (w > 0 ? smem + (hbuf - 2688 - sb) : sc + o_halo) + pin0(dep);
      uint4 hv[6];
#pragma unroll
      for (int e = 0; e < 6; e++)
        asm volatile("ld.relaxed.gpu.v4.b32 {%0,%1,%2,%3}, [%4];" : "=r"(hv[e].x), "=r"(hv[e].y), "=r"(hv[e].z), "=r"(hv[e].w) : "l"(hp + e * 448) : "memory");
      CSTAMP(2);
#pragma unroll
      for (int t = 0; t < 9; t++) {
        if (t >= HALO_V) Vl[t] = pack_bf16(acc[4 * GI(2, t)] * c_lo, acc[4 * GI(2, t) + 1] * c_lo);
        Vl[t] = movm(Vl[t]);
        Vh[t] = movm(Vh[t]);
      }
      uint32_t qa[4][2], qb[4][2];
      float s1[4][4], s2[4][4];
#pragma unroll
      for (int h = 0; h < 4; h++) {
        qa[h][0] = q >= h ? Ql[2 * h] : 0u; qa[h][1] = q >= h ? Qh[2 * h] : 0u;
        qb[h][0] = q <= h ? Ql[2 * h + 2] : 0u; qb[h][1] = q <= h ? Qh[2 * h + 2] : 0u;
      }
      const bool first = (i == 0 && w == 0);
      if (w == 0 && i > 0) {
        int n = 0;
#pragma unroll 1
        while (__any_sync(0xffffffffu, (orx(orx(orx(0, hv[0].w, tg), hv[1].w, tg), hv[2].w, tg) | orx(orx(orx(0, hv[3].w, tg), hv[4].w, tg), hv[5].w, tg)) != 0)) {
#pragma unroll
          for (int e = 0; e < 6; e++) rld128(hv[e], sc + o_halo + e * 448);
          if (++n > SPIN) TIMEOUT(__LINE__)
        }
      }
#pragma unroll
      for (int e = 0; e < 4; e++) { Kx[2 * e] = hv[e].x; Kx[2 * e + 1] = hv[e].y; Vx[e] = hv[e].z; }
      Kx[8] = hv[4].x; Vx[4] = hv[4].y; Vx[5] = hv[4].z; Vx[6] = hv[5].x; Vx[7] = hv[5].y; Vx[8] = hv[5].z;
      CSTAMP(3);
#pragma unroll
      for (int t = 0; t < 9; t++) Vx[t] = movm(Vx[t]);
#pragma unroll
      for (int h = 0; h < 4; h++) { mma8z(s1[h], qb[h][0], qb[h][1], Kl[2 * h + 2]); mma8z(s2[h], qb[h][0], qb[h][1], Kh[2 * h + 2]); }
#pragma unroll
      for (int h = 0; h < 4; h++) {
        mma16(s1[h], qa[h][0], qa[h][1], Ql[2 * h + 1], Qh[2 * h + 1], Kl[2 * h], Kl[2 * h + 1]);
        mma16(s2[h], qa[h][0], qa[h][1], Ql[2 * h + 1], Qh[2 * h + 1], Kh[2 * h], Kh[2 * h + 1]);
      }
      float s0[4][4];
#pragma unroll
      for (int h = 0; h < 4; h++) mma8z(s0[h], qb[h][0], qb[h][1], Kx[2 * h + 2]);
#pragma unroll
      for (int h = 0; h < 4; h++) mma16(s0[h], qa[h][0], qa[h][1], Ql[2 * h + 1], Qh[2 * h + 1], Kx[2 * h], Kx[2 * h + 1]);
      const bool pv0 = 2 * q > g, pv1 = 2 * q + 1 > g;
      const uint32_t PM = (pv0 ? 0x0000FFFFu : 0u) | (pv1 ? 0xFFFF0000u : 0u);
      const float kS = 0.23570226039551584f * 1.4426950408889634f;
      const float sc_lo = c_lo * kS, sc_hi = c_hi * kS;
      float sl[4][2], sh[4][2], ml[4], mh[4];
#pragma unroll
      for (int h = 0; h < 4; h++) {
        sh[h][0] = pv0 ? s1[h][2] : s2[h][2];
        sh[h][1] = pv1 ? s1[h][3] : s2[h][3];
        mh[h] = fmaxf(sh[h][0], sh[h][1]);
        sl[h][0] = pv0 ? (first ? -INFINITY : s0[h][0]) : s1[h][0];
        sl[h][1] = pv1 ? (first ? -INFINITY : s0[h][1]) : s1[h][1];
        ml[h] = fmaxf(sl[h][0], sl[h][1]);
      }
#pragma unroll
      for (int s = 1; s <= 2; s <<= 1) {
        float tl[4], th[4];
#pragma unroll
        for (int h = 0; h < 4; h++) { th[h] = shx(mh[h], s); tl[h] = shx(ml[h], s); }
#pragma unroll
        for (int h = 0; h < 4; h++) { mh[h] = fmaxf(mh[h], th[h]); ml[h] = fmaxf(ml[h], tl[h]); }
      }
      float o[4][3][4], den[4][4];
      uint32_t px[4];
#pragma unroll
      for (int h = 0; h < 4; h++) {
        const float bl = -ml[h] * sc_lo, bh = -mh[h] * sc_hi;
        const uint32_t pl = pack_bf16(ex2(fmaf(sl[h][0], sc_lo, bl)), ex2(fmaf(sl[h][1], sc_lo, bl)));
        const uint32_t ph = pack_bf16(ex2(fmaf(sh[h][0], sc_hi, bh)), ex2(fmaf(sh[h][1], sc_hi, bh)));
        mma8z(den[h], pl, ph, 0x3F803F80u);
        px[h] = pl & PM;
#pragma unroll
        for (int u = 0; u < 3; u++) mma16z(o[h][u], pl & ~PM, ph & PM, 0u, ph & ~PM, Vl[2 * h + u], Vh[2 * h + u]);
      }
#pragma unroll
      for (int h = 0; h < 4; h++)
#pragma unroll
        for (int u = 0; u < 3; u++) mma8(o[h][u], px[h], 0u, Vx[2 * h + u]);
      float il[4], ih[4];
#pragma unroll
      for (int h = 0; h < 4; h++) { il[h] = rcp(den[h][0]); ih[h] = rcp(den[h][2]); }
#pragma unroll
      for (int t = 0; t < 9; t++) {
        const int h = t == 8 ? 3 : t >> 1, u = t == 8 ? 2 : t & 1;
        float v0 = o[h][u][0], v1 = o[h][u][1], v2 = o[h][u][2], v3 = o[h][u][3], kl = il[h], kh = ih[h];
        if (u == 0 && h > 0 && q < h) {
          v0 = o[h - 1][2][0]; v1 = o[h - 1][2][1]; v2 = o[h - 1][2][2]; v3 = o[h - 1][2][3]; kl = il[h - 1]; kh = ih[h - 1];
        }
        stg32(sc + o_o + t * 1024, pack_bf16(v0 * kl, v1 * kl));
        stg32(sc + o_o + t * 1024 + 128, pack_bf16(v2 * kh, v3 * kh));
      }
    }
    CSTAMP(4);
    const uint32_t rbo = ldg_rlx32(sc + (o_o + rboff));
    lane = pin(lane);
    const uint32_t o_x = o_o + (OFF(xbuf) - OFF(obuf)), o_xrb = o_x + rboff;
    const uint32_t o_cf = OFF(cflag) + (ip * 32 + j * 4 + w) * 32 + lane * 4;
    if (L == 1 && first_lane) mbar_arrive(sb + BAR_HDONE + p * 8);
    flag_after(sc + o_cf, rbo, 8 * T + 2 * L, lane < 8);
    STAMPD(asf(rbo), L * 40 + p * 20 + 13);
    uint32_t resid[18];
    mbar_wait(sb + BAR_FULL + 16, 1); mbar_wait(sb + BAR_FULL + 32, 1);
    if (L == 0) {
      const uint32_t ra = sb + SM_A + (2 + p) * 8192 + (w * 16 + (lane & 15)) * 128;
#pragma unroll
      for (int t = 0; t < 9; t++) ldsm2(resid[2 * t], resid[2 * t + 1], ra + ((j + t) >> 3) * 16384 + ((((j + t) ^ lane) & 7) << 4));
      if (first_lane) mbar_arrive(sb + BAR_HDONE + p * 8 + pin0(resid[17]));
    } else {
#pragma unroll
      for (int t = 0; t < 9; t++) { resid[2 * t] = ldg_rlx32(sc + o_x + t * 1024); resid[2 * t + 1] = ldg_rlx32(sc + o_x + t * 1024 + 128); }
    }
    const uint32_t o_st = OFF(stats) + (ip * 4 + w) * 2048;
    const uint32_t o_stw = pin(o_st + j * 256 + (g + 8 * (q & 1)) * 16), o_str = pin(o_st + q * 512 + g * 16);
    const uint32_t o_cand = pin(OFF(cand) + (j * 32 + ip) * (CAND_W * 4) + q * 16);
    const uint32_t o_xc = pin(OFF(xcand) + (ip * 8 + j) * 192 + q * 16);
    float accw[36];
    float wr[18];
#pragma unroll
    for (int t = 0; t < 9; t++) { const uint2 u = lds64(sb + SM_WR + t * 32 + q * 8); wr[2 * t] = asf(u.x); wr[2 * t + 1] = asf(u.y); }
    const uint4 ws4 = lds128(sb + SM_WR + 288);
    const float wsum = asf(pin(asu(asf(ws4.x) + asf(ws4.y) + asf(ws4.z))));
    {
      float ul = 1.f, uh = 1.f, vl = 0.f, vh = 0.f;
      if (L == 1) {
        ul += rs_lo; uh += rs_hi; vl = -m_lo * rs_lo; vh = -m_hi * rs_hi;
        if (sel_lo || sel_hi) {
#pragma unroll
          for (int t = 0; t < 9; t++) {
            const uint32_t z = lds32(sb + SM_X2S + t * 16 + q * 4);
            if (sel_hi) resid[2 * t + 1] = z; else resid[2 * t] = z;
          }
          if (sel_hi) { uh = 1.f; vh = 0.f; } else { ul = 1.f; vl = 0.f; }
        }
        __syncwarp();
      }
#pragma unroll
      for (int t = 0; t < 9; t++) {
        accw[4 * t] = fmaf(bf_lo(resid[2 * t]), ul, vl); accw[4 * t + 1] = fmaf(bf_hi(resid[2 * t]), ul, vl);
        accw[4 * t + 2] = fmaf(bf_lo(resid[2 * t + 1]), uh, vh); accw[4 * t + 3] = fmaf(bf_hi(resid[2 * t + 1]), uh, vh);
      }
    }
    fence_regs<36>(accw);
    mbar_wait(sb + BAR_FULL, 1); mbar_wait(sb + BAR_FULL + 8, 1); mbar_wait(sb + BAR_FULL + 24, 1); mbar_wait(sb + BAR_FULL + 40, 1);
    {
      uint32_t wf = sb + BAR_WFULL + p * 72;
      uint32_t bl = DLO(sb + SM_B, 128);
      uint32_t half = p;
      mbar_wait(wf, L);
      CSTAMP(5);
#pragma unroll 1
      for (int c3 = 0; c3 < 3; c3++) {
        const uint32_t al = DLO(sb + SM_A, 1024) + half * 512;
        const uint32_t ae = sb + BAR_AEMPTY + half * 24;
#pragma unroll
        for (int cc = 0; cc < 3; cc++) {
          TSTAMP(36 + (c3 * 3 + cc) * 2);
          wg_fence();
          wgmma_ss_72(accw, al + cc * 1024, DHI(128, 0), bl + cc * 576, DHI(256, 0));
          wgmma_ss_72(accw, al + cc * 1024 + 128, DHI(128, 0), bl + cc * 576 + 144, DHI(256, 0));
          const uint32_t ok = mbar_test(wf + cc * 8 + 8, L);
          wgmma_ss_72(accw, al + cc * 1024 + 256, DHI(128, 0), bl + cc * 576 + 288, DHI(256, 0));
          wgmma_ss_72(accw, al + cc * 1024 + 384, DHI(128, 0), bl + cc * 576 + 432, DHI(256, 0));
          wg_commit();
          wg_wait<1>();
          if (cc > 0) { if (first_lane) { mbar_arrive(ae + cc * 8 - 8); if (cc == 2) mbar_arrive(sb + BAR_EMPTY + c3 * 16); } }
          else if (first_lane && c3 > 0) { mbar_arrive(sb + BAR_AEMPTY + 40 - half * 24); mbar_arrive(sb + BAR_EMPTY + c3 * 16 - 8); }
          if (!ok && (cc < 2 || c3 < 2)) mbar_wait(wf + cc * 8 + 8, L);
        }
        wf += 24; bl += 1728; half ^= 1;
      }
    }
    wg_wait<0>();
    fence_regs<36>(accw);
    if (first_lane) { mbar_arrive(sb + BAR_AEMPTY + (2 + 3 * p) * 8); mbar_arrive(sb + BAR_EMPTY + 40); }
    CSTAMP(6);
    uint32_t xw[18];
    uint32_t rb = 0;
    if (L == 0 && p == 0) {
#pragma unroll
      for (int t = 0; t < 9; t++) {
        stg32(sc + o_x + t * 1024, pack_bf16(accw[4 * t], accw[4 * t + 1]));
        stg32(sc + o_x + t * 1024 + 128, pack_bf16(accw[4 * t + 2], accw[4 * t + 3]));
      }
      rb = ldg_rlx32(sc + o_xrb);
      fence_regs<36>(accw);
    }
    {
      float a0[2] = {0.f, 0.f}, a1[2] = {0.f, 0.f}, a2[2] = {0.f, 0.f}, b0[2] = {0.f, 0.f}, b1[2] = {0.f, 0.f}, b2[2] = {0.f, 0.f};
#pragma unroll
      for (int t = 0; t < 9; t++) {
#pragma unroll
        for (int e = 0; e < 2; e++) {
          const float x = accw[4 * t + e], y = accw[4 * t + 2 + e];
          a0[e] += x; a1[e] = fmaf(x, x, a1[e]); a2[e] = fmaf(x, wr[2 * t + e], a2[e]);
          b0[e] += y; b1[e] = fmaf(y, y, b1[e]); b2[e] = fmaf(y, wr[2 * t + e], b2[e]);
        }
      }
      const bool od = q & 1;
      const float A0 = a0[0] + a0[1], A1 = a1[0] + a1[1], A2 = a2[0] + a2[1], B0 = b0[0] + b0[1], B1 = b1[0] + b1[1], B2 = b2[0] + b2[1];
      float k0 = od ? B0 : A0, k1 = od ? B1 : A1, k2 = od ? B2 : A2;
      k0 += shx(od ? A0 : B0, 1); k1 += shx(od ? A1 : B1, 1); k2 += shx(od ? A2 : B2, 1);
      k0 += shx(k0, 2); k1 += shx(k1, 2); k2 += shx(k2, 2);
      if (q < 2) stg128(sc + o_stw, asu(k0), asu(k1), asu(k2), tg);
      STAMPD(k0, L * 40 + p * 20 + 14);
    }
#pragma unroll
    for (int t = 0; t < 9; t++) {
      xw[2 * t] = pack_bf16(accw[4 * t], accw[4 * t + 1]);
      xw[2 * t + 1] = pack_bf16(accw[4 * t + 2], accw[4 * t + 3]);
    }
    float r_lo, r_hi;
    {
      uint4 u0 = ldg_rlx128(sc + o_str), u1 = ldg_rlx128(sc + o_str + 256), u2 = ldg_rlx128(sc + o_str + 128), u3 = ldg_rlx128(sc + o_str + 384);
      flag_after(sc + o_cf, rb, 8 * T + 1, lane < 8 && L == 0 && p == 0);
      STAMPD(asf(u3.w), L * 40 + p * 20 + 15);
      int n = 0;
#pragma unroll 1
      while (__any_sync(0xffffffffu, orx(orx(orx(orx(0, u0.w, tg), u1.w, tg), u2.w, tg), u3.w, tg) != 0)) {
        rld128(u0, sc + o_str); rld128(u1, sc + o_str + 256); rld128(u2, sc + o_str + 128); rld128(u3, sc + o_str + 384);
        if (++n > SPIN) TIMEOUT(__LINE__)
      }
      float a0 = asf(u0.x) + asf(u1.x), a1 = asf(u0.y) + asf(u1.y), a2 = asf(u0.z) + asf(u1.z);
      float b0 = asf(u2.x) + asf(u3.x), b1 = asf(u2.y) + asf(u3.y), b2 = asf(u2.z) + asf(u3.z);
#pragma unroll
      for (int s = 1; s <= 2; s <<= 1) {
        const float t0 = shx(a0, s), t1 = shx(a1, s), t2 = shx(a2, s), t3 = shx(b0, s), t4 = shx(b1, s), t5 = shx(b2, s);
        a0 += t0; a1 += t1; a2 += t2; b0 += t3; b1 += t4; b2 += t5;
      }
      m_lo = a0 * (1.f / 576.f); m_hi = b0 * (1.f / 576.f);
      rs_lo = rsq(fmaxf(a1 * (1.f / 576.f) - m_lo * m_lo, 0.f) + EPS);
      rs_hi = rsq(fmaxf(b1 * (1.f / 576.f) - m_hi * m_hi, 0.f) + EPS);
      r_lo = (a2 - m_lo * wsum) * rs_lo; r_hi = (b2 - m_hi * wsum) * rs_hi;
    }
    CSTAMP(7);
    if (ST_HOLD && L == 0 && p == ST_P && w == 0 && first_lane) mbar_arrive(sb + BAR_ST + pin0(asu(r_lo)));
    if (LATE_Q1 == 3 && L == 0 && p == 1 && w == 0 && first_lane) mbar_arrive(sb + BAR_ST + pin0(asu(r_lo)));
    int candrow = -1;
    {
      const uint32_t kl = fkey(r_lo), kh = fkey(r_hi);
      const bool hi = kh > kl;
      const uint32_t kb = hi ? kh : kl;
      const uint32_t mx = __reduce_max_sync(0xffffffffu, kb);
      if (first_lane) sts32(sb + SM_BEST + p * 16 + w * 4, mx);
      const uint32_t bal = __ballot_sync(0xffffffffu, kb == mx);
      const bool mine = (bal & ((1u << (lane & 28)) - 1u)) == 0u && kb == mx;
      const uint32_t x0 = hi ? xw[1] : xw[0], x1 = hi ? xw[3] : xw[2], x2 = hi ? xw[5] : xw[4], x3 = hi ? xw[7] : xw[6], x4 = hi ? xw[9] : xw[8];
      const uint32_t x5 = hi ? xw[11] : xw[10], x6 = hi ? xw[13] : xw[12], x7 = hi ? xw[15] : xw[14], x8 = hi ? xw[17] : xw[16];
      nb_sync(NB_WG + p, 128);
      const uint4 bs = lds128(sb + SM_BEST + p * 16);
      const bool best = (w > 0 ? bs.x < mx : true) && (w > 1 ? bs.y < mx : bs.y <= mx) && (w > 2 ? bs.z < mx : bs.z <= mx) && bs.w <= mx;
      if (best && mine) {
        if (q < 2) stg128(sc + o_cand, asu(hi ? r_hi : r_lo), (tg << 6) + (uint32_t)(w * 16 + g + (hi ? 8 : 0)), asu(hi ? m_hi : m_lo), asu(hi ? rs_hi : rs_lo));
        stg128(sc + o_xc, x0, x1, x2, tg);
        stg128(sc + o_xc + 64, x3, x4, x5, tg);
        stg128(sc + o_xc + 128, x6, x7, x8, tg);
      }
      candrow = __reduce_max_sync(0xffffffffu, best && mine ? g + (hi ? 8 : 0) : -1);
    }
    if (L == 0 && p == 1) {
#pragma unroll
      for (int t = 0; t < 9; t++) { stg32(sc + o_x + t * 1024, xw[2 * t]); stg32(sc + o_x + t * 1024 + 128, xw[2 * t + 1]); }
      rb = ldg_rlx32(sc + o_xrb);
    }
    const uint32_t stg = sb + SM_B + p * 13824 + w * 2304;
    unsigned char* obase = (unsigned char*)P.out + ((128 * i + 32 * w + p) * 1152 + 144 * j);
    if (L == 1) {
      const float ul = 1.f + rs_lo, uh = 1.f + rs_hi, vl = -m_lo * rs_lo, vh = -m_hi * rs_hi;
#pragma unroll
      for (int t = 0; t < 9; t++) {
        xw[2 * t] = pack_bf16(fmaf(accw[4 * t], ul, vl), fmaf(accw[4 * t + 1], ul, vl));
        xw[2 * t + 1] = pack_bf16(fmaf(accw[4 * t + 2], uh, vh), fmaf(accw[4 * t + 3], uh, vh));
      }
      mbar_wait(sb + BAR_EMPTY + p * 8, 1);
      const uint32_t sa = stg + (lane & 15) * 144;
#pragma unroll
      for (int t = 0; t < 8; t += 2) stsm4(sa + (lane >> 4) * 16 + t * 16, xw[2 * t], xw[2 * t + 1], xw[2 * t + 2], xw[2 * t + 3]);
      stsm2(sa + 128, xw[16], xw[17]);
      __syncwarp();
      if (p == 0 || !OUT_LATE) store_rows(stg, obase, candrow, lane);
    }
    CSTAMP(8);
    lane = pin(lane);
    const unsigned char* cp = sc + (OFF(cand) + (j * 32 + lane) * (CAND_W * 4));
    if (p == 0) {
      if (L == 1 && candrow >= 0) {
        const Winner wn = poll_winner(cp, ldg_rlx128(cp), tg);
        if (lane < 9 && wn.ci != ip) *(uint4*)(obase + (candrow * 2304 + lane * 16)) = lds128(stg + candrow * 144 + lane * 16);
      }
    } else {
      const uint32_t gr = w * 144 + (lane & 7) + (lane >> 4) * 8, gm = sb + SM_G + ((lane >> 3) & 1) * 46080;
      const uint32_t ga = gm + gr * 64 + (((lane >> 1) & 3) << 4), gl = gm + 36864 + gr * 16;
#define GADDR(s, u) ((u) < 4 ? (ga ^ ((u) << 4)) + (s) * 1024 : gl + (s) * 256)
      uint32_t wf[NPRE][5][4];
      mbar_wait(sb + BAR_GU, 0);
#pragma unroll
      for (int s = 0; s < NPRE - 2; s++)
#pragma unroll
        for (int u = 0; u < 5; u++) ldsm4t(wf[s][u], GADDR(s, u));
      const uint4 c0 = ldg_rlx128(cp);
#pragma unroll
      for (int s = NPRE - 2; s < NPRE; s++)
#pragma unroll
        for (int u = 0; u < 5; u++) ldsm4t(wf[s][u], GADDR(s, u));
      flag_after(sc + o_cf, rb, 8 * T + 1, lane < 8 && L == 0);
      const Winner wn = poll_winner(cp, c0, tg);
      if (w == 0 && first_lane) sts128(sb + SM_WIN, asu(wn.r), asu(wn.m), asu(wn.rstd), (uint32_t)(wn.ci * 64 + wn.rr));
      if (LATE_Q1 == 2 && L == 0 && w == 0 && first_lane) mbar_arrive(sb + BAR_ST + pin0(wn.ci));
      CSTAMP(9);
      if (!OUT_LATE && L == 1 && candrow >= 0 && lane < 9 && wn.ci != ip) *(uint4*)(obase + (candrow * 2304 + lane * 16)) = lds128(stg + candrow * 144 + lane * 16);
      {
        uint32_t hb[18];
        const unsigned char* xc = sc + (OFF(xcand) + wn.ci * 1536 + q * 16);
        const int fp = min(cx.cta / 3, 23);
        uint4 u[7];
        int n = 0;
#pragma unroll 1
        while (true) {
          uint32_t d = 0;
#pragma unroll
          for (int e = 0; e < 7; e++) u[e] = ldg_rlx128(xc + (e < 6 ? w * 384 + e * 64 : fp * 64));
#pragma unroll
          for (int e = 0; e < 7; e++) d = orx(d, u[e].w, tg);
          if (__all_sync(0xffffffffu, d == 0)) break;
          if (++n > SPIN) TIMEOUT(__LINE__)
        }
        if (LATE_Q1 == 1 && L == 0 && w == 0 && first_lane) mbar_arrive(sb + BAR_ST + pin0(u[0].x));
        if (OUT_LATE == 3 && L == 1) store_rows(stg, obase, wn.ci == ip ? candrow : -1, lane);
#pragma unroll
        for (int e = 0; e < 6; e++) { hb[3 * e] = u[e].x; hb[3 * e + 1] = u[e].y; hb[3 * e + 2] = u[e].z; }
        if (w == 0) sts128(sb + SM_XW + q * 16, u[6].x, u[6].y, u[6].z, u[6].w);
        const float nb = -wn.m * wn.rstd;
#pragma unroll
        for (int b = 0; b < 18; b++) hb[b] = pack_bf16(fmaf(bf_lo(hb[b]), wn.rstd, nb), fmaf(bf_hi(hb[b]), wn.rstd, nb));
        CSTAMP(10);
        float d[5][4];
#pragma unroll
        for (int u = 0; u < 5; u++) d[u][0] = d[u][1] = d[u][2] = d[u][3] = 0.f;
#pragma unroll
        for (int s = 0; s < 9; s++) {
#pragma unroll
          for (int u = 0; u < 5; u++) {
            uint32_t* f = wf[s % NPRE][u];
            mma16(d[u], f[0], f[1], f[2], f[3], hb[2 * s], hb[2 * s + 1]);
            if (s + NPRE < 9) ldsm4t(f, GADDR(s + NPRE, u));
          }
        }
        if (q == 0) {
#pragma unroll
          for (int u = 0; u < 5; u++) sts64(sb + R_FPART + w * 320 + (u * 8 + g) * 8, asu(d[u][0]), asu(d[u][2]));
        }
        nb_arrive(NB_FFN, 224);
        CSTAMP(11);
      }
      if (OUT_LATE == 1 && L == 1) store_rows(stg, obase, wn.ci == ip ? candrow : -1, lane);
    }
  }
  STAMPIF(w == 0 && lane == 0, 40 + p * 20 + 12);
  PROF_DUMP();
#undef g
#undef q
#undef first_lane
}

__device__ __forceinline__ void load_wo_a(const Ctx& cx, const Params& P, const uint32_t T, const int L, const int p, const int lane) {
  const unsigned char* src = P.sc->obuf[cx.i * 2 + p];
#pragma unroll
  for (int c = 0; c < 9; c++) w_expect(sb + BAR_WFULL + (9 * p + c) * 8, 8192);
  mbar_wait(sb + BAR_HDONE + p * 8, L);
  wait_flags<32>(P.sc->cflag[cx.i * 2 + p], 8 * T + 2 * L, lane);
  fence_async_glob();
  STAMP(100 + L * 2 + p);
#pragma unroll
  for (int c = 0; c < 9; c++) {
    const int e = 9 * p + c, s = e % 6;
    if (e == 3) mbar_wait(sb + BAR_HDONE + 8, L);
    if (e >= 6) mbar_wait(sb + BAR_AEMPTY + s * 8, (L ^ (e / 6) ^ 1) & 1);
    w_bulk(sb + SM_A + (2 * (s % 3) + s / 3) * 8192, src + c * 8192, 8192, sb + BAR_WFULL + e * 8);
    PSTAMP(48 + L * 36 + 18 + e);
  }
}

__device__ __forceinline__ void finalize_row(const Params& P, const Winner& wn, const uint32_t T, const int L, const int grp, const int a, const int lane) {
  const unsigned char* yp = (const unsigned char*)P.sc->ypart[grp] + (a * 32 + lane) * 16;
  const uint32_t par = L ^ 1;
  uint4 u0 = ldg_rlx128(yp), u1 = ldg_rlx128(yp + 1536), u2 = make_uint4(par, 0, 0, 0);
  if (a < 2) rld128(u2, yp + 3072);
  const int col = lane & 7;
  const uint32_t xw = lds32(sb + SM_XW + (col >> 1) * 16 + (grp % 3) * 4);
  const float xsel = (col & 1) ? bf_hi(xw) : bf_lo(xw);
  const float sg = rbf(rcp(1.f + ex2(-1.4426950408889634f * rbf(wn.r))));
  const float h = rbf((xsel - wn.m) * wn.rstd);
  unsigned char* dst = L == 0 ? (unsigned char*)P.sc->xsel + (((lane >> 3) & 1) * 576 + grp * 8 + col) * 4
                              : (unsigned char*)P.out + ((128 * (wn.ci >> 1) + 2 * wn.rr + (wn.ci & 1)) * 576 + grp * 8 + col) * 2;
  int n = 0;
#pragma unroll 1
  while (__any_sync(0xffffffffu, orx(orx(orx(0, u0.x, par), u1.x, par), u2.x, par) & 1)) {
    rld128(u0, yp); rld128(u1, yp + 1536);
    if (a < 2) rld128(u2, yp + 3072);
    if (++n > SPIN) TIMEOUT(__LINE__)
  }
  const float s0 = asf(u0.x) + asf(u1.x) + asf(u2.x), s1 = asf(u0.y) + asf(u1.y) + asf(u2.y);
  const float s2 = asf(u0.z) + asf(u1.z) + asf(u2.z), s3 = asf(u0.w) + asf(u1.w) + asf(u2.w);
  const float k0 = self(lane & 2, s2, s0) + shx(self(lane & 2, s0, s2), 2), k1 = self(lane & 2, s3, s1) + shx(self(lane & 2, s1, s3), 2);
  float k = self(lane & 4, k1, k0) + shx(self(lane & 4, k0, k1), 4);
  k += shx(k, 8); k += shx(k, 16);
  if (lane < 8) stsf(sb + SM_YRED + ((lane & 1) * 4 + (lane & 2) + (lane >> 2)) * 16 + a * 4, k);
  nb_sync(NB_AUX, 96);
  if (a == 0) {
    const uint4 yy = lds128(sb + SM_YRED + col * 16);
    const float xn = rbf(xsel + rbf(h + rbf(rbf(asf(yy.x) + asf(yy.y) + asf(yy.z)) * sg)));
    if (L == 0) { if (lane < 16) stg32(dst, ftag(lane < 8 ? xn : xn - xsel, T & 1)); }
    else if (lane < 8) *(unsigned short*)dst = (unsigned short)(asu(xn) >> 16);
  }
}

__device__ __forceinline__ void aux_role(const Ctx& cx, const Params& P, const int a, const int lane_) {
  int lane = lane_;
#define t (a * 32 + lane)
#define g (lane >> 2)
#define q (lane & 3)
  const int i = cx.i, j = cx.j, cta = cx.cta;
  unsigned char* const sc = (unsigned char*)P.sc;
  const int rk = 36 * i + 12 * a;
  const uint32_t o_bf = OFF(bflag) + (j * 48 + i * 3 + a) * 32 + (lane & 7) * 4;
  uint32_t T;
  {
    const int k0 = lane & 7, tt = min(lane >> 3, 2), col = (9 * j + tt) * 16;
    const unsigned char* src = (const unsigned char*)P.wqkv + ((i * 8 + k0) * 3456 + a * 1152 + col);
    const Unit b0 = unit_load(src), b1 = unit_load(src + 128 * 3456);
    T = ldg_rlx32(sc + o_bf);
    nb_arrive(NB_ORD, 352);
    STAMPIF(1, 96);
    const uint32_t d2 = tt == 2 ? (22 - 7 * a) * 512 : 3072;
    const uint32_t o = OFF(wq) + (j * 18 + (i >> 2)) * 13824 + ((i & 3) * 8 + k0) * 16 + (a * 8 + tt) * 512;
    const uint32_t r0 = unit_store(sc, b0, lane, o, o + 1536, o + d2);
    STAMPIF(1, 80);
    const uint32_t r1 = unit_store(sc, b1, lane, o + 55296, o + 55296 + 1536, o + 55296 + d2);
    T = __shfl_sync(0xffffffffu, (T >> 3) + 1, 0);
    flag_after(sc + o_bf, r0 ^ r1, 8 * T + 1, lane < 8);
    STAMPIF(1, 98);
    const Unit b2 = unit_load(src + 256 * 3456), b3 = unit_load(src + 384 * 3456);
    const bool qkv = k0 < 4;
    const int q0 = rk + k0 - 4, q1 = rk + 4 + k0;
    const Unit u0 = unit_load(qkv ? (const unsigned char*)P.wqkv + ((512 + 4 * i + k0) * 3456 + a * 1152 + col) : (const unsigned char*)P.wo + (q0 * 1152 + col));
    const Unit u1 = unit_load((const unsigned char*)P.wo + (q1 * 1152 + col));
    const uint32_t r2 = unit_store(sc, b2, lane, o + 2 * 55296, o + 2 * 55296 + 1536, o + 2 * 55296 + d2);
    const uint32_t r3 = unit_store(sc, b3, lane, o + 3 * 55296, o + 3 * 55296 + 1536, o + 3 * 55296 + d2);
    float cs[3][8];
#pragma unroll
    for (int m = 0; m < 3; m++) {
      const uint32_t* w0 = &b0.v[m].x; const uint32_t* w1 = &b1.v[m].x; const uint32_t* w2 = &b2.v[m].x; const uint32_t* w3 = &b3.v[m].x; const uint32_t* w4 = &u0.v[m].x;
#pragma unroll
      for (int e = 0; e < 4; e++) {
        const uint32_t z = qkv ? w4[e] : 0u;
        cs[m][2 * e] = (bf_lo(w0[e]) + bf_lo(w1[e])) + (bf_lo(w2[e]) + bf_lo(w3[e])) + bf_lo(z);
        cs[m][2 * e + 1] = (bf_hi(w0[e]) + bf_hi(w1[e])) + (bf_hi(w2[e]) + bf_hi(w3[e])) + bf_hi(z);
      }
    }
    flag_after(sc + o_bf, r2 ^ r3, 8 * T + 3, lane < 8);
    STAMPIF(1, 82);
#pragma unroll
    for (int st = 4; st >= 1; st >>= 1) {
      const bool up = lane & st;
#pragma unroll
      for (int m = 0; m < 3; m++)
#pragma unroll
        for (int e = 0; e < st; e++) cs[m][e] = (up ? cs[m][e + st] : cs[m][e]) + shx(up ? cs[m][e] : cs[m][e + st], st);
    }
    {
      const uint32_t oz = OFF(zpart) + j * 13824 + i * 864 + (a * 8 + tt) * 32 + k0 * 4;
      stg32(sc + oz, ftag(cs[0][0], 1)); stg32(sc + (oz + 96), ftag(cs[1][0], 1)); stg32(sc + (oz + (d2 >> 4)), ftag(cs[2][0], 1));
    }
    STAMPIF(1, 81);
    nb_sync(NB_GO, 128);
    mbar_wait(sb + BAR_FULL + LATE_WAIT * 8, 0);
    const uint32_t ow = OFF(wo) + j * 82944 + tt * 256;
    const uint32_t oa = qkv ? OFF(wq) + (j * 18 + 16 + (i >> 3)) * 13824 + (4 * (i & 7) + k0) * 16 + (a * 8 + tt) * 512 : ow + (q0 >> 4) * 2304 + (q0 & 15) * 16;
    const uint32_t ob = ow + (q1 >> 4) * 2304 + (q1 & 15) * 16;
    const uint32_t ra = unit_store(sc, u0, lane, oa, oa + (qkv ? 1536 : 768), oa + (qkv ? d2 : 1536));
    const uint32_t rb = unit_store(sc, u1, lane, ob, ob + 768, ob + 1536);
    STAMPIF(1, 113);
#pragma unroll
    for (int S = 0; S < 3; S++) stg64(sc + (OFF(ypart) + (a * 24 + g) * 4096 + cta * 32 + q * 8) + S * 32768, 0u, 0u);
    if (cta < 72 && t < 16) stg32(sc + (OFF(xsel) + (lane >> 3) * 2304 + cta * 32 + (lane & 7) * 4), (T & 1) ^ 1);
    uint4 sv, sw;
    int n = 0;
#pragma unroll 1
    while (true) {
      sv = ldg_rlx128(sc + (OFF(st0) + i * 2048 + t * 16)); sw = ldg_rlx128(sc + (OFF(st0) + i * 2048 + 1536 + lane * 16));
      if (__all_sync(0xffffffffu, ((sv.z ^ T) | (sw.z ^ T)) == 0)) break;
      if (++n > SPIN) TIMEOUT(__LINE__)
    }
    flag_after(sc + o_bf, ra ^ rb, 8 * T + 4, lane < 8);
    sts64(sb + SM_R + t * 8, sv.x, sv.y);
    sts64(sb + SM_R + 768 + lane * 8, sw.x, sw.y);
    STAMPIF(1, 94);
  }
  asm volatile("setmaxnreg.inc.sync.aligned.u32 %0;" ::"n"(REG_AUX));
  Winner wn;
  bool owner = false;
  uint32_t wd[5][3][8];
  auto load_wd = [&](uint32_t (*d)[8], const unsigned char* sk) {
#pragma unroll
    for (int S = 0; S < 3; S++) {
      const uint4 v0 = ldg_wd128(sk + S * 128), v1 = ldg_wd128(sk + S * 128 + 1152);
      d[S][0] = v0.x; d[S][1] = v1.x; d[S][2] = v0.y; d[S][3] = v1.y; d[S][4] = v0.z; d[S][5] = v1.z; d[S][6] = v0.w; d[S][7] = v1.w;
    }
  };
  auto perm_wd = [&](uint32_t (*d)[8]) {
#pragma unroll
    for (int S = 0; S < 3; S++)
#pragma unroll
      for (int u = 0; u < 4; u++) {
        const uint32_t x = d[S][2 * u], y = d[S][2 * u + 1];
        asm volatile("prmt.b32 %0, %2, %3, 0x5410;\nprmt.b32 %1, %2, %3, 0x7632;" : "=&r"(d[S][2 * u]), "=r"(d[S][2 * u + 1]) : "r"(x), "r"(y));
      }
  };
#pragma unroll
  for (int kb = 0; kb < 3; kb++)
#pragma unroll
    for (int S = 0; S < 3; S++)
#pragma unroll
      for (int e = 0; e < 8; e++) wd[kb][S][e] = 0u;
#pragma unroll 1
  for (int L = 0; L < 2; L++) {
    lane = pin(lane);
    const uint32_t o_part = OFF(zpart) + j * 13824, par = L ^ 1;
    const int pk = a * 18 + min(lane, 17);
    if (L == 1) {
      if (cta < 72) finalize_row(P, wn, T, 0, cta, a, lane);
      const int gi = min(lane, 26);
      uint4 wv[12];
      {
        const int pc = gi < 24 ? gi >> 3 : gi - 24, tc = gi < 24 ? gi & 7 : 8;
        const unsigned char* se = (const unsigned char*)P.wqkv + (rk * 3456 + pc * 1152 + (9 * j + tc) * 16);
#pragma unroll
        for (int r = 0; r < 12; r++) wv[r] = ldg_nc128(se + r * 3456);
      }
      STAMPIF(1, 85);
      nb_sync(NB_AUX, 96);
      uint4 xq[3];
      {
        const unsigned char* dp = sc + (OFF(xsel) + 2304 + rk * 4);
        int n = 0;
#pragma unroll 1
        while (true) {
#pragma unroll
          for (int e = 0; e < 3; e++) xq[e] = ldg_rlx128(dp + e * 16);
          if (__all_sync(0xffffffffu, (orx(orx(orx(0, xq[0].x, T), xq[1].x, T), xq[2].x, T) & 1) == 0)) break;
          if (++n > SPIN) TIMEOUT(__LINE__)
        }
        if (t == 0) {
          sts32(sb + SM_SEL, owner ? (wn.ci & 1) * 64 + wn.rr : 0x7FFFFFFFu);
          if (wn.ci != 2 * i) mbar_arrive(sb + BAR_FIX);
          if (wn.ci != 2 * i + 1) mbar_arrive(sb + BAR_FIX + 8);
        }
        STAMPIF(1, 88);
      }
      float s[8];
#pragma unroll
      for (int e = 0; e < 8; e++) s[e] = 0.f;
#pragma unroll
      for (int r = 0; r < 12; r++) {
        const float x = asf((&xq[0].x)[r]);
        s[0] = fmaf(x, bf_lo(wv[r].x), s[0]); s[1] = fmaf(x, bf_hi(wv[r].x), s[1]);
        s[2] = fmaf(x, bf_lo(wv[r].y), s[2]); s[3] = fmaf(x, bf_hi(wv[r].y), s[3]);
        s[4] = fmaf(x, bf_lo(wv[r].z), s[4]); s[5] = fmaf(x, bf_hi(wv[r].z), s[5]);
        s[6] = fmaf(x, bf_lo(wv[r].w), s[6]); s[7] = fmaf(x, bf_hi(wv[r].w), s[7]);
      }
      sts128(sb + SM_R + a * 864 + gi * 32, asu(s[0]), asu(s[1]), asu(s[2]), asu(s[3]));
      sts128(sb + SM_R + a * 864 + gi * 32 + 16, asu(s[4]), asu(s[5]), asu(s[6]), asu(s[7]));
      nb_sync(NB_AUX, 96);
      const uint32_t ad = sb + SM_R + pk * 16;
      const uint4 u0 = lds128(ad), u1 = lds128(ad + 864), u2 = lds128(ad + 1728);
      stg128(sc + (o_part + i * 864 + pk * 16), ftag(asf(u0.x) + asf(u1.x) + asf(u2.x), par), ftag(asf(u0.y) + asf(u1.y) + asf(u2.y), par),
             ftag(asf(u0.z) + asf(u1.z) + asf(u2.z), par), ftag(asf(u0.w) + asf(u1.w) + asf(u2.w), par));
      STAMPIF(1, 86);
    }
    if (owner) {
      uint2 u[3];
      int n = 0;
#pragma unroll 1
      while (true) {
#pragma unroll
        for (int m = 0; m < 3; m++) u[m] = ldg_rlx64(sc + (OFF(xsel) + t * 8) + m * 768);
        if (__all_sync(0xffffffffu, (orx(orx(orx(0, u[0].x, T), u[1].x, T), u[2].x, T) & 1) == 0)) break;
        if (++n > SPIN) TIMEOUT(__LINE__)
      }
      STAMPIF(1, 109);
      float s1 = 0.f, s2 = 0.f;
#pragma unroll
      for (int m = 0; m < 3; m++) {
        const float x0 = asf(u[m].x), x1 = asf(u[m].y);
        s1 += x0 + x1; s2 = fmaf(x0, x0, fmaf(x1, x1, s2));
        const unsigned cc = 96 * m + t - 36 * j;
        if (cc < 36u) sts32(sb + SM_X2S + cc * 4, __byte_perm(u[m].x, u[m].y, 0x7632));
      }
      wn.m = s1; wn.rstd = s2;
    }
    if (L == 0 || owner) {
      uint4 u[16];
      int n = 0;
#pragma unroll 1
      while (true) {
        uint32_t d0 = 0, d1 = 0;
#pragma unroll
        for (int e = 0; e < 16; e++) u[e] = ldg_rlx128(sc + (o_part + pk * 16) + e * 864);
        if (L == 1 && n == 0) {
#pragma unroll
          for (int s = 1; s < 32; s <<= 1) { wn.m += shx(wn.m, s); wn.rstd += shx(wn.rstd, s); }
          if (lane == 0) sts64(sb + SM_RED2 + a * 8, asu(wn.m), asu(wn.rstd));
        }
#pragma unroll
        for (int e = 0; e < 8; e++) { d0 = orx(d0, u[e].x, par); d1 = orx(d1, u[8 + e].x, par); }
        if (__all_sync(0xffffffffu, ((d0 | d1) & 1) == 0)) break;
        if (++n > SPIN) TIMEOUT(__LINE__)
      }
      STAMPIF(1, 118 + L);
      float4 z = make_float4(0.f, 0.f, 0.f, 0.f);
#pragma unroll
      for (int e = 0; e < 16; e++) { z.x += asf(u[e].x); z.y += asf(u[e].y); z.z += asf(u[e].z); z.w += asf(u[e].w); }
      const uint32_t h0 = pack_bf16(z.x, z.y), h1 = pack_bf16(z.z, z.w);
      const uint32_t l0 = pack_bf16(z.x - bf_lo(h0), z.y - bf_hi(h0)), l1 = pack_bf16(z.z - bf_lo(h1), z.w - bf_hi(h1));
      const uint32_t ad = sb + SM_BEXT + (pk >> 1) * 128 + (pk & 1) * 8;
      if (L == 0) {
        sts64(ad, h0, h1);
#pragma unroll
        for (int r = 3; r < 8; r++) sts64(ad + r * 16, 0u, 0u);
      }
      sts64(ad + 16 + L * 48, h0, h1); sts64(ad + 32 + L * 48, l0, l1);
      fence_async_smem();
      nb_sync(NB_AUX, 96);
      if (t == 0) {
        if (L == 1) {
          const uint4 ra = lds128(sb + SM_RED2);
          const uint2 rb = lds64(sb + SM_RED2 + 16);
          const float m2 = (asf(ra.x) + asf(ra.z) + asf(rb.x)) * (1.f / 576.f);
          const float rs2 = rsq(fmaxf((asf(ra.y) + asf(ra.w) + asf(rb.y)) * (1.f / 576.f) - m2 * m2, 0.f) + EPS);
          sts64(sb + SM_SEL + 8, asu(m2), asu(rs2));
          mbar_arrive(sb + BAR_FIX + (wn.ci & 1) * 8);
        } else {
          mbar_arrive(sb + BAR_FIX); mbar_arrive(sb + BAR_FIX + 8);
        }
        STAMP(83 + L * 4);
      }
    }
    lane = pin(lane);
    const unsigned char* const wsrc = (const unsigned char*)P.wd + ((ffn_c32(cta) + 2 * q) * 1152 + a * 384 + g * 16);
    if (L == 0) {
#pragma unroll
      for (int kb = 0; kb < 3; kb++) { load_wd(wd[kb], wsrc + (kb * 9216 + (kb ? pin0(wd[kb - 1][2][7]) : 0u))); perm_wd(wd[kb]); }
    }
    if (L == 0)
    {
    load_wd(wd[3], wsrc + 3 * 9216);
    load_wd(wd[4], wsrc + ((cta & 1) ? (ffn_c8(cta) - ffn_c32(cta)) * 1152 : 24 * 1152));
    perm_wd(wd[3]); perm_wd(wd[4]);
    }
    const uint32_t o_y = pin(OFF(ypart) + (a * 24 + g) * 4096 + cta * 32 + q * 8 + pin0(wd[4][2][7]));
    STAMPIF(1, 89 + L);
    if (a == 2) load_wo_a(cx, P, T, L, 1, lane);
    nb_sync(NB_FFN, 224);
    {
      const uint32_t ad = sb + R_FPART + min(lane, 19) * 16;
      const uint4 u0 = lds128(ad), u1 = lds128(ad + 320), u2 = lds128(ad + 640), u3 = lds128(ad + 960);
      const uint4 wv = lds128(sb + SM_WIN);
      const float g0 = rbf((asf(u0.x) + asf(u1.x)) + (asf(u2.x) + asf(u3.x))), g1 = rbf((asf(u0.z) + asf(u1.z)) + (asf(u2.z) + asf(u3.z)));
      const float v0 = rbf((asf(u0.y) + asf(u1.y)) + (asf(u2.y) + asf(u3.y))), v1 = rbf((asf(u0.w) + asf(u1.w)) + (asf(u2.w) + asf(u3.w)));
      const float s0 = rbf(g0 * rcp(1.f + ex2(-1.4426950408889634f * g0))), s1 = rbf(g1 * rcp(1.f + ex2(-1.4426950408889634f * g1)));
      const uint32_t act = lane < 16 + (cta & 1) * 4 ? pack_bf16(s0 * v0, s1 * v1) : 0u;
      uint32_t b[5];
#pragma unroll
      for (int kb = 0; kb < 5; kb++) b[kb] = __shfl_sync(0xffffffffu, act, 4 * kb + q);
#pragma unroll
      for (int S = 0; S < 3; S++) {
        float y[4][4];
#pragma unroll
        for (int u = 0; u < 4; u++) mma8z(y[u], wd[2][S][2 * u], wd[2][S][2 * u + 1], b[2]);
#pragma unroll
        for (int u = 0; u < 4; u++) mma16(y[u], wd[0][S][2 * u], wd[0][S][2 * u + 1], wd[1][S][2 * u], wd[1][S][2 * u + 1], b[0], b[1]);
#pragma unroll
        for (int u = 0; u < 4; u++) mma16(y[u], wd[3][S][2 * u], wd[3][S][2 * u + 1], wd[4][S][2 * u], wd[4][S][2 * u + 1], b[3], b[4]);
        const float y0 = self(lane & 2, self(lane & 1, y[3][0], y[2][0]), self(lane & 1, y[1][0], y[0][0]));
        const float y1 = self(lane & 2, self(lane & 1, y[3][2], y[2][2]), self(lane & 1, y[1][2], y[0][2]));
        stg64(sc + o_y + S * 32768, ftag(y0, par), ftag(y1, par));
      }
      if (L == 0) nb_arrive(NB_FFN2, Q1_BOTH ? 352 : 224);
      wn.r = asf(wv.x); wn.m = asf(wv.y); wn.rstd = asf(wv.z); wn.ci = wv.w >> 6; wn.rr = wv.w & 63;
    }
    STAMPIF(1, 84 + L * 8);
    owner = (wn.ci >> 1) == i;
  }
  if (cta < 72) finalize_row(P, wn, T, 1, cta, a, lane);
  STAMPIF(1, 93);
  PROF_END();
#undef t
#undef g
#undef q
}

__device__ __forceinline__ int sched_box(const uint32_t at, const int a) {
  int r = -1;
#pragma unroll
  for (int b = 0; b < 6; b++) if (((at >> (4 * b)) & 15) != 15) r = a == (int)((at >> (4 * b)) & 15) ? b : r;
  return r;
}
__host__ __device__ constexpr int sched_first(const uint32_t at) { int b = 0; while (b < 6 && ((at >> (4 * b)) & 15) != 15) b++; return b; }
__host__ __device__ constexpr int sched_last(const uint32_t at) { int b = 5; while (b >= 0 && ((at >> (4 * b)) & 15) != 15) b--; return b; }
__device__ __forceinline__ void producer_role(const Ctx& cx, const Params& P, const int lane) {
  const int i = cx.i, j = cx.j;
  if (elect_one()) asm volatile("prefetch.tensormap [%0];" ::"l"(&P.mx) : "memory");
  const uint32_t T = __shfl_sync(0xffffffffu, (ldg_rlx32(P.sc->cflag[i * 2][j * 4]) >> 3) + 1, 0);
  const unsigned char* const wq = P.sc->wq[j][0];
  nb_sync(NB_START, 288);
#pragma unroll
  for (int s = 0; s < 2 * NA0; s++) w_tma3d(sb + SM_A + s * 8192, &P.mx, (s >> 1) * 64, s & 1, i * 64, sb + BAR_FULL + (s >> 1) * 16);
#pragma unroll
  for (int h = 0; h < 6; h++) w_expect(sb + BAR_FULL + h * 8, h & 1 ? 13824 : 13824 + 16384);
  STAMP(97);
  wait_flags<48>(P.sc->bflag[j], 8 * T + 1, lane);
  fence_async_glob();
  STAMP(120);
#pragma unroll
  for (int h = 0; h < 6; h++) {
    w_bulk(sb + SM_B + h * 13824, wq + h * 13824, 13824, sb + BAR_FULL + h * 8);
    if (!(h & 1) && h >= 2 * NA0) {
      w_tma3d(sb + SM_A + h * 8192, &P.mx, h * 32, 0, i * 64, sb + BAR_FULL + h * 8);
      w_tma3d(sb + SM_A + h * 8192 + 8192, &P.mx, h * 32, 1, i * 64, sb + BAR_FULL + h * 8);
    }
  }
  PSTAMP(0);
  asm volatile("setmaxnreg.inc.sync.aligned.u32 %0;" ::"n"(REG_AUX));
  nb_arrive(NB_GO, 128);
  mbar_wait(sb + BAR_FULL + PF_WAIT * 8, 0);
  w_prefetch((const unsigned char*)P.wd + cx.cta * 41472, 10368);
  const unsigned char* const xb = P.sc->xbuf[i * 2];
  const unsigned char* const fp = (const unsigned char*)P.sc->bflag[j] + lane * 32;
  uint32_t f0 = 0, f1 = 0;
#pragma unroll 1
  for (int L = 0; L < 2; L++) {
    if (L == 1 && !LATE_Q1) {
#pragma unroll 1
      for (int p = 0; p < 2; p++) {
        mbar_wait(sb + BAR_AEMPTY + (2 + 3 * p) * 8, 0);
        wait_flags<32>(P.sc->cflag[i * 2 + p], 8 * T + 1, lane);
        fence_async_glob();
        STAMP(104 + p);
#pragma unroll
        for (int a = 0; a < 3; a++) {
          const int s = 2 * a + p;
          w_expect(sb + BAR_AFULL + s * 8, 8192);
          w_bulk(sb + SM_A + s * 8192, xb + (p * 73728 + a * 8192), 8192, sb + BAR_AFULL + s * 8);
          PSTAMP(48 + 36 + 3 * p + a);
        }
      }
    }
#pragma unroll 1
    for (int a = 3; a < 15; a++) {
      if (a == 12) {
        load_wo_a(cx, P, T, L, 0, lane);
        if (L == 1) break;
        if (LATE_Q1) {
#pragma unroll 1
          for (int b = LATE_G0; b < 6; b++) {
            if (LATE_GGAP) { const int c0 = clock(); while ((int)(clock() - c0) < LATE_GGAP) {} }
            load_gu(P, cx.cta, 0, b, sb + BAR_GU);
          }
#pragma unroll 1
          for (int p = 0; p < 2; p++) {
            mbar_wait(sb + BAR_AEMPTY + (2 + 3 * p) * 8, 0);
            wait_flags<32>(P.sc->cflag[i * 2 + p], 8 * T + 1, lane);
            STAMP(104 + p);
          }
          fence_async_glob();
          mbar_wait(sb + BAR_ST, 0);
#pragma unroll 1
          for (int s = 0; s < 3; s++) {
            const uint32_t fb = sb + BAR_FULL + s * 16, ab = sb + BAR_AFULL + s * 16, db = sb + SM_B + s * 27648, da = sb + SM_A + s * 16384;
            mbar_wait(sb + BAR_EMPTY + s * 16, 1);
            w_expect(fb, 13824);
            w_bulk(db, wq + s * 27648, 13824, fb);
            w_expect(ab, 8192);
            w_bulk(da, xb + s * 8192, 8192, ab);
            w_expect(ab + 8, 8192);
            w_bulk(da + 8192, xb + (73728 + s * 8192), 8192, ab + 8);
            mbar_wait(sb + BAR_EMPTY + s * 16 + 8, 1);
            w_expect(fb + 8, 13824);
            w_bulk(db + 13824, wq + (s * 27648 + 13824), 13824, fb + 8);
          }
          break;
        }
      }
      const int r = (a * 11) >> 5, s = a - 3 * r;
      const uint32_t fb = sb + BAR_FULL + s * 16, da = sb + SM_A + s * 16384, db = sb + SM_B + s * 27648;
      const unsigned char* bsrc = wq + (a < 9 ? a : a < 12 ? 72 - 6 * j + s : s) * 27648;
      const unsigned char* asrc = xb + a * 8192;
      const int kc = (a < 9 ? a : j + a - 10) * 64;
      const int amode = a == 9 || a > 11 ? 0 : L == 0 ? 1 : a < 9 ? 2 : 0;
      mbar_wait(sb + BAR_EMPTY + s * 16, (r & 1) ^ 1);
      if (ST_HOLD && a == ST_HOLD) mbar_wait(sb + BAR_ST, 0);
      if (L == 0) {
        if (a == 4 || a == 8) {
          const uint32_t need = 8 * T + (a == 4 ? 3 : 4);
          if (__any_sync(0xffffffffu, (int)((f0 - need) | (f1 - need)) < 0)) wait_flags<48>(P.sc->bflag[j], need, lane);
          fence_async_glob();
          STAMP(120 + (a >> 1));
        }
        if (a == 3 || a == 7) { f0 = ldg_rlx32(fp); f1 = ldg_rlx32(fp + (lane < 16 ? 1024 : 0)); }
      }
      w_bulk(db, bsrc, 13824, fb);
      if (amode == 2) {
        w_bulk(da, asrc, 4096, fb);
        w_bulk(da + 8192, asrc + 73728, 4096, fb);
      }
      w_expect(fb, amode == 1 ? 13824 + 16384 : amode == 2 ? 13824 + 8192 : 13824);
      mbar_wait(sb + BAR_EMPTY + s * 16 + 8, (r & 1) ^ 1);
      if (amode == 1) {
        w_tma3d(da, &P.mx, kc, 0, i * 64, fb);
        w_tma3d(da + 8192, &P.mx, kc, 1, i * 64, fb);
      }
      w_bulk(db + 13824, bsrc + 13824, 13824, fb + 8);
      if (amode == 2) {
        w_bulk(da + 4096, asrc + 4096, 4096, fb + 8);
        w_bulk(da + 8192 + 4096, asrc + 73728 + 4096, 4096, fb + 8);
      }
      w_expect(fb + 8, amode == 2 ? 13824 + 8192 : 13824);
      PSTAMP(a < 12 ? L * 24 + a : 12 + a);
      if (L == 0) {
        {
          if (a >= WD_PF && a < WD_PF + 3) w_prefetch((const unsigned char*)P.wd + (cx.cta * 4 + a - WD_PF + 1) * 10368, 10368);
          if (a >= PG_0 && a < PG_0 + 6) w_prefetch((const unsigned char*)P.wg + ((a - PG_0) * 128 + cx.cta) * 6912, 6912);
        }
        if (a == 3) w_expect(sb + BAR_GU, 12 * (6144 + (cx.cta & 1) * 1536));
        {
          const int bu = sched_box(U_AT, a), bg = sched_box(G_AT, a);
          if (bu >= 0) load_gu(P, cx.cta, 1, bu, sb + BAR_GU);
          if (bg >= 0) load_gu(P, cx.cta, 0, bg, sb + BAR_GU);
          if (a == U_WIN) {
#pragma unroll 1
            for (int b = sched_first(U_AT); b <= sched_last(U_AT); b++) {
              const int c0 = clock();
              while ((int)(clock() - c0) < U_GAP) {}
              load_gu(P, cx.cta, 1, b, sb + BAR_GU);
            }
          }
          if (a == G_WIN) {
#pragma unroll 1
            for (int b = sched_first(G_AT); b <= sched_last(G_AT); b++) {
              const int c0 = clock();
              while ((int)(clock() - c0) < G_GAP) {}
              load_gu(P, cx.cta, 0, b, sb + BAR_GU);
            }
          }
        }
      }
    }
  }
}

template <bool BY_SMID>
__global__ void __launch_bounds__(384, 1) fused_kernel(const __grid_constant__ Params P) {
  extern __shared__ __align__(1024) unsigned char smem[];
  Ctx cx;
  STAMPIF(threadIdx.x == 64, 125);
  unsigned id;
  if (BY_SMID) asm volatile("mov.u32 %0, %%smid;" : "=r"(id)); else id = blockIdx.x;
  const int work = __shfl_sync(0xffffffffu, (int)P.work[min(id, 131u)], 0);
  const int warp = __shfl_sync(0xffffffffu, (int)(threadIdx.x >> 5), 0), lane = threadIdx.x & 31;
  if (work < 0) {
    if (warp == 0) {
      const int sp = -1 - work;
      if (lane == 0) { mbar_init(sb, 1); fence_async_smem(); }
      __syncwarp();
      __nanosleep(SPARE_DELAY);
#pragma unroll 1
      for (int k = 32 + sp; k < 72; k += 4) w_prefetch((const unsigned char*)P.wqkv + k * 27648, 27648);
#pragma unroll 1
      for (int k = sp; k < 24; k += 4) w_prefetch((const unsigned char*)P.wo + k * 27648, 27648);
#pragma unroll 1
      for (int k = sp; k < X_NU; k += 4) w_prefetch((const unsigned char*)P.wu + k * 27648, 27648);
      w_expect(sb, 16);
      w_bulk(sb + 128, P.wr, 16, sb);
      mbar_wait(sb, 0);
    }
    return;
  }
  cx.cta = work; cx.i = work >> 3; cx.j = work & 7;
  STAMPIF(threadIdx.x == 32, 95);
  if (warp < 8) {
    asm volatile("setmaxnreg.dec.sync.aligned.u32 %0;" ::"n"(REG_CONS));
    if (warp == 0) {
      if (elect_one()) {
        if ((uint32_t)__cvta_generic_to_shared(smem) != sb) __trap();
#pragma unroll
        for (int b = 0; b < 48; b++) mbar_init(sb + SM_BAR + b * 8, b < 34 ? 1 : b < 42 ? 4 : 8);
        fence_async_smem();
      }
      __syncwarp();
    }
    consumer_role(cx, P, smem, warp >> 2, warp & 3, lane);
  } else {
    if (warp < 11) aux_role(cx, P, warp - 8, lane);
    else producer_role(cx, P, lane);
  }
}

int work_of_smid(int smid) {
  const int t = smid >> 1;
  if (t == 60 || t == 61) return -1 - ((t - 60) * 2 + (smid & 1));
  const int gpc = t < 32 ? t & 7 : t < 60 ? 1 + (t - 32) % 7 : 0;
  const int x = 2 * (t < 32 ? t >> 3 : t < 60 ? 4 + (t - 32) / 7 : t - 58) + (smid & 1);
  const int blk[8] = {6, 0, 2, 3, 4, 7, 5, 1}, b = blk[gpc];
  return ((b >> 1) * 4 + (x & 1) + (x >> 3) * 2) * 8 + (b & 1) * 4 + ((x >> 1) & 3);
}

typedef CUresult (*EncodeFn)(CUtensorMap*, CUtensorMapDataType, cuuint32_t, void*, const cuuint64_t*, const cuuint64_t*,
                             const cuuint32_t*, const cuuint32_t*, CUtensorMapInterleave, CUtensorMapSwizzle,
                             CUtensorMapL2promotion, CUtensorMapFloatOOBfill);

void make_map(EncodeFn enc, CUtensorMap* m, const void* base, int rank, const cuuint64_t* dims, const cuuint64_t* strides,
              const cuuint32_t* box, CUtensorMapSwizzle sw, CUtensorMapL2promotion promo = CU_TENSOR_MAP_L2_PROMOTION_L2_128B) {
  const cuuint32_t es[3] = {1, 1, 1};
  enc(m, CU_TENSOR_MAP_DATA_TYPE_BFLOAT16, rank, const_cast<void*>(base), dims, strides, box, es, CU_TENSOR_MAP_INTERLEAVE_NONE, sw,
      promo, CU_TENSOR_MAP_FLOAT_OOB_FILL_NONE);
}

}

extern "C" void kernel_launch(void* const* d_in, const int* in_sizes, int n_in, void* d_out, int out_size) {
  (void)in_sizes; (void)n_in; (void)out_size;
  static EncodeFn enc = nullptr;
  static int nsm = 0;
  static void* scr = nullptr;
  if (!enc) {
    void* f = nullptr;
    cudaDriverEntryPointQueryResult qr;
    cudaGetDriverEntryPoint("cuTensorMapEncodeTiled", &f, cudaEnableDefault, &qr);
    enc = (EncodeFn)f;
    cudaGetSymbolAddress(&scr, g_scratch);
    int dev = 0;
    cudaGetDevice(&dev);
    cudaDeviceGetAttribute(&nsm, cudaDevAttrMultiProcessorCount, dev);
    cudaFuncSetAttribute(fused_kernel<true>, cudaFuncAttributeMaxDynamicSharedMemorySize, SM_TOTAL);
    cudaFuncSetAttribute(fused_kernel<false>, cudaFuncAttributeMaxDynamicSharedMemorySize, SM_TOTAL);
  }
  Params P;
  P.x = (const __nv_bfloat16*)d_in[0];
  P.wqkv = (const __nv_bfloat16*)d_in[1];
  P.wo = (const __nv_bfloat16*)d_in[2];
  P.wr = (const __nv_bfloat16*)d_in[4];
  P.wg = (const __nv_bfloat16*)d_in[5];
  P.wu = (const __nv_bfloat16*)d_in[6];
  P.wd = (const __nv_bfloat16*)d_in[7];
  P.out = (__nv_bfloat16*)d_out;
  P.sc = (Scratch*)scr;
  for (int k = 0; k < 136; k++) P.work[k] = (signed char)(nsm == 132 ? (k < 132 ? work_of_smid(k) : -1) : (k < 128 ? k : k < 132 ? 127 - k : -1));
  {
    const cuuint64_t dims[3] = {576, 2, 1024}, str[2] = {1152, 2304};
    const cuuint32_t box[3] = {64, 1, 64};
    make_map(enc, &P.mx, P.x, 3, dims, str, box, CU_TENSOR_MAP_SWIZZLE_128B);
  }
  {
    const cuuint64_t dims[2] = {4608, 576}, str[1] = {9216};
    const cuuint32_t box[2] = {32, 96}, box8[2] = {8, 96};
    make_map(enc, &P.mg, d_in[5], 2, dims, str, box, CU_TENSOR_MAP_SWIZZLE_64B);
    make_map(enc, &P.mu, d_in[6], 2, dims, str, box, CU_TENSOR_MAP_SWIZZLE_64B);
    make_map(enc, &P.mg8, d_in[5], 2, dims, str, box8, CU_TENSOR_MAP_SWIZZLE_NONE);
    make_map(enc, &P.mu8, d_in[6], 2, dims, str, box8, CU_TENSOR_MAP_SWIZZLE_NONE);
  }
  if (nsm == 132) fused_kernel<true><<<132, 384, SM_TOTAL>>>(P);
  else fused_kernel<false><<<132, 384, SM_TOTAL>>>(P);
}
```

```cpp
#include <cuda_runtime.h>
#include <cuda.h>
#include <cuda_bf16.h>
#include <stdint.h>
#include <stddef.h>

namespace {

#define NPRE_ 4
constexpr int NPRE = NPRE_;
#define X_NU 192
#define CAND_W 8
#define HALO_V 0
#define X_DELAY 200
#define X_STEP 100
#define HOLD_C 13
#define NA0 3
#define B2_AT 0
#define LATE_WAIT 1
#define OUT_LATE 0
#define U_AT 0xFFFF75
#define G_AT 0xEEEEEB
#define PG_0 6
#define WD_PF 3
#define U_WIN 11
#define G_WIN 11
#define G_GAP 300
#define U_GAP 400
#define ST_HOLD 0
#define ST_P 1
#define LATE_Q1 1
#define LATE_U0 6
#define LATE_G0 1
#define LATE_GGAP 600
#define Q1_BOTH 1
#define A32 1
#define WD_RES 1
#define REG_AUX 200
#define REG_CONS 152
#define REG_AT 1
#define WD_TRIG 0
#define HOIST 0
#define X_TOUCH 0
#define XROW_MERGE 1
#define D_STATS 400
#define D_Y0 500
#define D_Y1 0
#define P_FROM 1
#define P_GAP 0
#define PF_WAIT 0
#define POLL_GAP 100
#define SPARE_DELAY 400
constexpr float EPS = 1e-5f;
constexpr int SPIN = 1 << 22;
#define TIMEOUT(line) __trap();

struct __align__(128) Scratch {
  uint32_t bflag[8][48][8];
  uint32_t cflag[32][32][8];
  uint32_t halo[32][8][672];
  uint32_t stats[32][4][8][64];
  uint32_t cand[8][32][CAND_W];
  uint32_t xcand[32][8][48];
  uint32_t ypart[72][128][8];
  uint32_t zpart[8][16][216];
  uint32_t st0[2048][4];
  uint32_t xsel[2][576];
  unsigned char wq[8][9][27648];
  unsigned char wo[8][3][27648];
  unsigned char obuf[32][73728];
  unsigned char xbuf[32][73728];
};
__device__ Scratch g_scratch;
#define OFF(f) ((uint32_t)offsetof(Scratch, f))
#define STAMPD(v, k) do {} while (0)
#define STAMPIF(c, k) do {} while (0)
#define STAMP(k) do {} while (0)

constexpr uint32_t sb = 1024;
constexpr uint32_t SM_A = 0;
constexpr uint32_t SM_B = 49152;
constexpr uint32_t SM_G = 132096;
constexpr uint32_t SM_BEXT = 224256;

constexpr uint32_t SM_WIN = 227712;
constexpr uint32_t SM_XW = 228320;
constexpr uint32_t SM_YRED = 228448;
constexpr uint32_t SM_X2S = 228576;
constexpr uint32_t SM_RED2 = 228736;
constexpr uint32_t SM_WR = 228864;
constexpr uint32_t SM_R = 229168;
constexpr uint32_t SM_BEST = 231760;
constexpr uint32_t SM_SEL = 231824;
constexpr uint32_t SM_BAR = 231840;
constexpr uint32_t SM_TOTAL = 232448;
constexpr uint32_t R_FPART = SM_R;
constexpr uint32_t BAR_FULL = SM_BAR  , BAR_AFULL = SM_BAR + 48  , BAR_WFULL = SM_BAR + 96  , BAR_ST = SM_BAR + 240, BAR_GU = SM_BAR + 248,
                   BAR_FIX = SM_BAR + 256  , BAR_AEMPTY = SM_BAR + 272  , BAR_HDONE = SM_BAR + 320  ,
                   BAR_EMPTY = SM_BAR + 336  ;
enum { NB_WG = 1  , NB_STAG = 3, NB_AUX = 4, NB_FFN2 = 5, NB_FFN = 8, NB_START = 9, NB_GO = 6, NB_ORD = 7 };

struct Params {
  const __nv_bfloat16 *wqkv, *x, *wr, *wo;
  Scratch* sc;
  const __nv_bfloat16 *wd, *wg, *wu;
  __nv_bfloat16* out;
  signed char work[136];
  CUtensorMap mx, mg, mu, mg8, mu8;
};

__device__ __forceinline__ void mbar_init(uint32_t bar, int cnt) { asm volatile("mbarrier.init.shared::cta.b64 [%0], %1;" ::"r"(bar), "r"(cnt) : "memory"); }
__device__ __forceinline__ void mbar_arrive(uint32_t bar) { asm volatile("mbarrier.arrive.shared::cta.b64 _, [%0];" ::"r"(bar) : "memory"); }
__device__ __forceinline__ void mbar_wait(uint32_t bar, uint32_t par) {
  asm volatile("{\n.reg .pred p;\nLOOP:\nmbarrier.try_wait.parity.shared::cta.b64 p, [%0], %1;\n@!p bra.uni LOOP;\n}\n" ::"r"(bar), "r"(par) : "memory");
}
__device__ __forceinline__ uint32_t mbar_test(uint32_t bar, uint32_t par) {
  uint32_t ok;
  asm volatile("{\n.reg .pred p;\nmbarrier.test_wait.parity.shared::cta.b64 p, [%1], %2;\nselp.u32 %0,1,0,p;\n}" : "=r"(ok) : "r"(bar), "r"(par) : "memory");
  return ok;
}
__device__ __forceinline__ bool elect_one() {
  uint32_t ok;
  asm volatile("{\n.reg .pred p;\nelect.sync _|p, 0xffffffff;\nselp.u32 %0, 1, 0, p;\n}" : "=r"(ok));
  return ok;
}
__device__ __forceinline__ float ex2(float x) { float r; asm("ex2.approx.ftz.f32 %0, %1;" : "=f"(r) : "f"(x)); return r; }
__device__ __forceinline__ float rsq(float x) { float r; asm("rsqrt.approx.ftz.f32 %0, %1;" : "=f"(r) : "f"(x)); return r; }
__device__ __forceinline__ float rcp(float x) { float r; asm("rcp.approx.ftz.f32 %0, %1;" : "=f"(r) : "f"(x)); return r; }
__device__ __forceinline__ void w_expect(uint32_t bar, uint32_t bytes) {
  asm volatile("{\n.reg .pred p;\nelect.sync _|p, 0xffffffff;\n@p mbarrier.arrive.expect_tx.shared::cta.b64 _, [%0], %1;\n}" ::"r"(bar), "r"(bytes) : "memory");
}
__device__ __forceinline__ void w_bulk(uint32_t dst, const void* src, uint32_t bytes, uint32_t bar) {
  asm volatile("{\n.reg .pred p;\nelect.sync _|p, 0xffffffff;\n@p cp.async.bulk.shared::cluster.global.mbarrier::complete_tx::bytes [%0], [%1], %2, [%3];\n}" ::"r"(dst), "l"(src), "r"(bytes), "r"(bar) : "memory");
}
__device__ __forceinline__ void w_tma2d(uint32_t dst, const CUtensorMap* m, int c0, int c1, uint32_t bar) {
  asm volatile("{\n.reg .pred p;\nelect.sync _|p, 0xffffffff;\n@p cp.async.bulk.tensor.2d.shared::cluster.global.mbarrier::complete_tx::bytes [%0], [%1, {%3, %4}], [%2];\n}" ::"r"(dst), "l"(m), "r"(bar), "r"(c0), "r"(c1) : "memory");
}
__device__ __forceinline__ void w_tma3d(uint32_t dst, const CUtensorMap* m, int c0, int c1, int c2, uint32_t bar) {
  asm volatile("{\n.reg .pred p;\nelect.sync _|p, 0xffffffff;\n@p cp.async.bulk.tensor.3d.shared::cluster.global.mbarrier::complete_tx::bytes [%0], [%1, {%3, %4, %5}], [%2];\n}" ::"r"(dst), "l"(m), "r"(bar), "r"(c0), "r"(c1), "r"(c2) : "memory");
}
__device__ __forceinline__ void w_prefetch(const void* src, uint32_t bytes) {
  asm volatile("{\n.reg .pred p;\nelect.sync _|p, 0xffffffff;\n@p cp.async.bulk.prefetch.L2.global [%0], %1;\n}" ::"l"(src), "r"(bytes) : "memory");
}
__device__ __forceinline__ void nb_sync(int id, int n) { asm volatile("bar.sync %0, %1;" ::"r"(id), "r"(n) : "memory"); }
__device__ __forceinline__ void nb_arrive(int id, int n) { asm volatile("bar.arrive %0, %1;" ::"r"(id), "r"(n) : "memory"); }
__device__ __forceinline__ void fence_async_smem() { asm volatile("fence.proxy.async.shared::cta;" ::: "memory"); }
__device__ __forceinline__ void fence_async_glob() { asm volatile("fence.proxy.async.global;" ::: "memory"); }
__device__ __forceinline__ void flag_after(void* p, uint32_t readback, uint32_t T, bool writer) {
  asm volatile("{\n.reg .pred p;\n.reg .u32 v;\nsetp.ne.u32 p, %3, 0;\nor.b32 v, %1, %2;\nmin.u32 v, v, %2;\n@p st.relaxed.gpu.global.u32 [%0], v;\n}"
               ::"l"(p), "r"(readback), "r"(T), "r"((uint32_t)writer) : "memory");
}
__device__ __forceinline__ uint4 ldg_rlx128(const void* p) { uint4 v; asm volatile("ld.relaxed.gpu.global.v4.b32 {%0,%1,%2,%3}, [%4];" : "=r"(v.x), "=r"(v.y), "=r"(v.z), "=r"(v.w) : "l"(p) : "memory"); return v; }
__device__ __forceinline__ uint2 ldg_rlx64(const void* p) { uint2 v; asm volatile("ld.relaxed.gpu.global.v2.b32 {%0,%1}, [%2];" : "=r"(v.x), "=r"(v.y) : "l"(p) : "memory"); return v; }
__device__ __forceinline__ void rld128(uint4& v, const void* p) { asm volatile("ld.relaxed.gpu.global.v4.b32 {%0,%1,%2,%3}, [%4];" : "+r"(v.x), "+r"(v.y), "+r"(v.z), "+r"(v.w) : "l"(p) : "memory"); }
__device__ __forceinline__ uint32_t ldg_rlx32(const void* p) { uint32_t v; asm volatile("ld.relaxed.gpu.global.b32 %0, [%1];" : "=r"(v) : "l"(p) : "memory"); return v; }
#define NC_HINT ""
__device__ __forceinline__ uint4 ldg_nc128(const void* p) { uint4 v; asm volatile("ld.global.nc" NC_HINT ".v4.b32 {%0,%1,%2,%3}, [%4];" : "=r"(v.x), "=r"(v.y), "=r"(v.z), "=r"(v.w) : "l"(p)); return v; }
#define WD_HINT ".nc.L1::no_allocate"
__device__ __forceinline__ uint4 ldg_wd128(const void* p) { uint4 v; asm volatile("ld.global" WD_HINT ".v4.b32 {%0,%1,%2,%3}, [%4];" : "=r"(v.x), "=r"(v.y), "=r"(v.z), "=r"(v.w) : "l"(p)); return v; }
__device__ __forceinline__ uint32_t ldg_nc32(const void* p) { uint32_t v; asm volatile("ld.global.nc.L1::no_allocate.b32 %0, [%1];" : "=r"(v) : "l"(p)); return v; }
__device__ __forceinline__ void stg128(void* p, uint32_t a, uint32_t b, uint32_t c, uint32_t d) { asm volatile("st.relaxed.gpu.global.v4.b32 [%0], {%1,%2,%3,%4};" ::"l"(p), "r"(a), "r"(b), "r"(c), "r"(d) : "memory"); }
__device__ __forceinline__ void stg64(void* p, uint32_t a, uint32_t b) { asm volatile("st.relaxed.gpu.global.v2.b32 [%0], {%1,%2};" ::"l"(p), "r"(a), "r"(b) : "memory"); }
__device__ __forceinline__ void stg32(void* p, uint32_t a) { asm volatile("st.relaxed.gpu.global.b32 [%0], %1;" ::"l"(p), "r"(a) : "memory"); }
__device__ __forceinline__ void sts128(uint32_t a, uint32_t x, uint32_t y, uint32_t z, uint32_t w) { asm volatile("st.shared.v4.b32 [%0], {%1,%2,%3,%4};" ::"r"(a), "r"(x), "r"(y), "r"(z), "r"(w) : "memory"); }
__device__ __forceinline__ void sts64(uint32_t a, uint32_t x, uint32_t y) { asm volatile("st.shared.v2.b32 [%0], {%1,%2};" ::"r"(a), "r"(x), "r"(y) : "memory"); }
__device__ __forceinline__ void sts32(uint32_t a, uint32_t x) { asm volatile("st.shared.b32 [%0], %1;" ::"r"(a), "r"(x) : "memory"); }
__device__ __forceinline__ void stsf(uint32_t a, float x) { sts32(a, __float_as_uint(x)); }
__device__ __forceinline__ uint4 lds128(uint32_t a) { uint4 v; asm volatile("ld.shared.v4.b32 {%0,%1,%2,%3}, [%4];" : "=r"(v.x), "=r"(v.y), "=r"(v.z), "=r"(v.w) : "r"(a) : "memory"); return v; }
__device__ __forceinline__ uint2 lds64(uint32_t a) { uint2 v; asm volatile("ld.shared.v2.b32 {%0,%1}, [%2];" : "=r"(v.x), "=r"(v.y) : "r"(a) : "memory"); return v; }
__device__ __forceinline__ uint32_t lds32(uint32_t a) { uint32_t v; asm volatile("ld.shared.b32 %0, [%1];" : "=r"(v) : "r"(a) : "memory"); return v; }
__device__ __forceinline__ uint32_t pack_bf16(float lo, float hi) { uint32_t r; asm("cvt.rn.bf16x2.f32 %0, %1, %2;" : "=r"(r) : "f"(hi), "f"(lo)); return r; }
__device__ __forceinline__ float bf_lo(uint32_t w) { return __uint_as_float(w << 16); }
__device__ __forceinline__ float bf_hi(uint32_t w) { return __uint_as_float(w & 0xFFFF0000u); }
__device__ __forceinline__ float rbf(float x) { return bf_lo(pack_bf16(x, 0.f)); }
__device__ __forceinline__ float asf(uint32_t u) { return __uint_as_float(u); }
__device__ __forceinline__ uint32_t asu(float f) { return __float_as_uint(f); }
__device__ __forceinline__ float shx(float v, int m) { return __shfl_xor_sync(0xffffffffu, v, m); }
__device__ __forceinline__ uint32_t movm(uint32_t a) { uint32_t o; asm volatile("movmatrix.sync.aligned.m8n8.trans.b16 %0, %1;" : "=r"(o) : "r"(a)); return o; }
__device__ __forceinline__ void ldsm2(uint32_t& a, uint32_t& b, uint32_t addr) { asm volatile("ldmatrix.sync.aligned.m8n8.x2.shared.b16 {%0,%1}, [%2];" : "=r"(a), "=r"(b) : "r"(addr) : "memory"); }
__device__ __forceinline__ void ldsm4t(uint32_t* r, uint32_t addr) { asm volatile("ldmatrix.sync.aligned.m8n8.x4.trans.shared.b16 {%0,%1,%2,%3}, [%4];" : "=r"(r[0]), "=r"(r[1]), "=r"(r[2]), "=r"(r[3]) : "r"(addr) : "memory"); }
__device__ __forceinline__ void stsm4(uint32_t addr, uint32_t a, uint32_t b, uint32_t c, uint32_t d) { asm volatile("stmatrix.sync.aligned.m8n8.x4.shared.b16 [%0], {%1,%2,%3,%4};" ::"r"(addr), "r"(a), "r"(b), "r"(c), "r"(d) : "memory"); }
__device__ __forceinline__ void stsm2(uint32_t addr, uint32_t a, uint32_t b) { asm volatile("stmatrix.sync.aligned.m8n8.x2.shared.b16 [%0], {%1,%2};" ::"r"(addr), "r"(a), "r"(b) : "memory"); }
__device__ __forceinline__ void mma16(float* d, uint32_t a0, uint32_t a1, uint32_t a2, uint32_t a3, uint32_t b0, uint32_t b1) {
  asm volatile("mma.sync.aligned.m16n8k16.row.col.f32.bf16.bf16.f32 {%0,%1,%2,%3},{%4,%5,%6,%7},{%8,%9},{%0,%1,%2,%3};"
               : "+f"(d[0]), "+f"(d[1]), "+f"(d[2]), "+f"(d[3]) : "r"(a0), "r"(a1), "r"(a2), "r"(a3), "r"(b0), "r"(b1));
}
__device__ __forceinline__ void mma16z(float* d, uint32_t a0, uint32_t a1, uint32_t a2, uint32_t a3, uint32_t b0, uint32_t b1) {
  asm volatile("mma.sync.aligned.m16n8k16.row.col.f32.bf16.bf16.f32 {%0,%1,%2,%3},{%4,%5,%6,%7},{%8,%9},{%10,%10,%10,%10};"
               : "=f"(d[0]), "=f"(d[1]), "=f"(d[2]), "=f"(d[3]) : "r"(a0), "r"(a1), "r"(a2), "r"(a3), "r"(b0), "r"(b1), "f"(0.f));
}
__device__ __forceinline__ void mma8(float* d, uint32_t a0, uint32_t a1, uint32_t b0) {
  asm volatile("mma.sync.aligned.m16n8k8.row.col.f32.bf16.bf16.f32 {%0,%1,%2,%3},{%4,%5},{%6},{%0,%1,%2,%3};"
               : "+f"(d[0]), "+f"(d[1]), "+f"(d[2]), "+f"(d[3]) : "r"(a0), "r"(a1), "r"(b0));
}
__device__ __forceinline__ uint32_t pin(uint32_t v) { uint32_t r; asm volatile("shfl.sync.bfly.b32 %0, %1, 0, 31, 0xffffffff;" : "=r"(r) : "r"(v)); return r; }
__device__ __forceinline__ uint32_t pin0(uint32_t v) { uint32_t r; asm volatile("{\n.reg .u32 t;\nor.b32 t, %1, 1;\nbfind.shiftamt.u32 %0, t;\nshr.u32 %0, %0, 5;\n}" : "=r"(r) : "r"(v)); return r; }
__device__ __forceinline__ void mma8z(float* d, uint32_t a0, uint32_t a1, uint32_t b0) {
  asm volatile("mma.sync.aligned.m16n8k8.row.col.f32.bf16.bf16.f32 {%0,%1,%2,%3},{%4,%5},{%6},{%7,%7,%7,%7};"
               : "=f"(d[0]), "=f"(d[1]), "=f"(d[2]), "=f"(d[3]) : "r"(a0), "r"(a1), "r"(b0), "f"(0.f));
}
__device__ __forceinline__ void wg_fence() { asm volatile("wgmma.fence.sync.aligned;" ::: "memory"); }
__device__ __forceinline__ void wg_commit() { asm volatile("wgmma.commit_group.sync.aligned;" ::: "memory"); }
template <int N> __device__ __forceinline__ void wg_wait() { asm volatile("wgmma.wait_group.sync.aligned %0;" ::"n"(N) : "memory"); }
template <int N> __device__ __forceinline__ void fence_regs(float* d) {
#pragma unroll
  for (int k = 0; k < N; k++) asm volatile("" : "+f"(d[k])::"memory");
}
__host__ __device__ constexpr uint32_t DLO(uint32_t addr, uint32_t lbo) { return (addr >> 4) | ((lbo >> 4) << 16); }
__host__ __device__ constexpr uint32_t DHI(uint32_t sbo, uint32_t swz) { return (sbo >> 4) | (swz << 30); }
template <int N>
__device__ __forceinline__ void wait_flags(const void* base, const uint32_t V, const int lane) {
  const unsigned char* p = (const unsigned char*)base + lane * 32;
  const unsigned char* p2 = p + (lane < N - 32 ? 1024 : 0);
  uint32_t a0 = ldg_rlx32(p), a1 = N > 32 ? ldg_rlx32(p2) : V;
  __nanosleep(POLL_GAP);
  int n = 0;
#pragma unroll 1
  while (true) {
    const uint32_t b0 = ldg_rlx32(p), b1 = N > 32 ? ldg_rlx32(p2) : V;
    if (__all_sync(0xffffffffu, (int)((a0 - V) | (a1 - V)) >= 0)) break;
    a0 = ldg_rlx32(p); a1 = N > 32 ? ldg_rlx32(p2) : V;
    if (__all_sync(0xffffffffu, (int)((b0 - V) | (b1 - V)) >= 0)) break;
    if (++n > SPIN) TIMEOUT(__LINE__)
  }
}
__device__ __forceinline__ uint32_t ftag(float v, uint32_t par) { return (asu(v) & ~1u) | par; }
__device__ __forceinline__ uint32_t selu(uint32_t c, uint32_t a, uint32_t b) { uint32_t r; asm("{\n.reg .pred p;\nsetp.ne.u32 p, %1, 0;\nselp.b32 %0, %2, %3, p;\n}" : "=r"(r) : "r"(c), "r"(a), "r"(b)); return r; }
__device__ __forceinline__ float self(uint32_t c, float a, float b) { return asf(selu(c, asu(a), asu(b))); }
__device__ __forceinline__ uint32_t orx(uint32_t acc, uint32_t a, uint32_t ref) { uint32_t r; asm("lop3.b32 %0, %1, %2, %3, 0xF6;" : "=r"(r) : "r"(acc), "r"(a), "r"(ref)); return r; }
__device__ __forceinline__ uint32_t fkey(float r) {
  uint32_t u = asu(r);
  u = (u & 0x80000000u) ? ~u : (u | 0x80000000u);
  return (r == r) ? u : 0u;
}
__host__ __device__ constexpr int GI(int part, int t) { return t < 8 ? part * 8 + t : 24 + part; }

__device__ __forceinline__ void wgmma_ss_216(float* d, uint32_t al, uint32_t ah, uint32_t bl, uint32_t bh) {
  asm volatile("{\n.reg .b64 da, db;\nmov.b64 da, {%108, %109};\nmov.b64 db, {%110, %111};\n"
      "wgmma.mma_async.sync.aligned.m64n216k16.f32.bf16.bf16 {"
      "%0,%1,%2,%3,%4,%5,%6,%7,%8,%9,%10,%11,%12,%13,%14,%15,%16,%17,%18,%19,%20,%21,%22,%23,%24,%25,%26,"
      "%27,%28,%29,%30,%31,%32,%33,%34,%35,%36,%37,%38,%39,%40,%41,%42,%43,%44,%45,%46,%47,%48,%49,%50,%51,%52,%53,"
      "%54,%55,%56,%57,%58,%59,%60,%61,%62,%63,%64,%65,%66,%67,%68,%69,%70,%71,%72,%73,%74,%75,%76,%77,%78,%79,%80,"
      "%81,%82,%83,%84,%85,%86,%87,%88,%89,%90,%91,%92,%93,%94,%95,%96,%97,%98,%99,%100,%101,%102,%103,%104,%105,%106,%107"
      "}, da, db, 1, 1, 1, 0, 1;\n}\n"
      : "+f"(d[0]), "+f"(d[1]), "+f"(d[2]), "+f"(d[3]), "+f"(d[4]), "+f"(d[5]), "+f"(d[6]), "+f"(d[7]), "+f"(d[8]),
        "+f"(d[9]), "+f"(d[10]), "+f"(d[11]), "+f"(d[12]), "+f"(d[13]), "+f"(d[14]), "+f"(d[15]), "+f"(d[16]), "+f"(d[17]),
        "+f"(d[18]), "+f"(d[19]), "+f"(d[20]), "+f"(d[21]), "+f"(d[22]), "+f"(d[23]), "+f"(d[24]), "+f"(d[25]), "+f"(d[26]),
        "+f"(d[27]), "+f"(d[28]), "+f"(d[29]), "+f"(d[30]), "+f"(d[31]), "+f"(d[32]), "+f"(d[33]), "+f"(d[34]), "+f"(d[35]),
        "+f"(d[36]), "+f"(d[37]), "+f"(d[38]), "+f"(d[39]), "+f"(d[40]), "+f"(d[41]), "+f"(d[42]), "+f"(d[43]), "+f"(d[44]),
        "+f"(d[45]), "+f"(d[46]), "+f"(d[47]), "+f"(d[48]), "+f"(d[49]), "+f"(d[50]), "+f"(d[51]), "+f"(d[52]), "+f"(d[53]),
        "+f"(d[54]), "+f"(d[55]), "+f"(d[56]), "+f"(d[57]), "+f"(d[58]), "+f"(d[59]), "+f"(d[60]), "+f"(d[61]), "+f"(d[62]),
        "+f"(d[63]), "+f"(d[64]), "+f"(d[65]), "+f"(d[66]), "+f"(d[67]), "+f"(d[68]), "+f"(d[69]), "+f"(d[70]), "+f"(d[71]),
        "+f"(d[72]), "+f"(d[73]), "+f"(d[74]), "+f"(d[75]), "+f"(d[76]), "+f"(d[77]), "+f"(d[78]), "+f"(d[79]), "+f"(d[80]),
        "+f"(d[81]), "+f"(d[82]), "+f"(d[83]), "+f"(d[84]), "+f"(d[85]), "+f"(d[86]), "+f"(d[87]), "+f"(d[88]), "+f"(d[89]),
        "+f"(d[90]), "+f"(d[91]), "+f"(d[92]), "+f"(d[93]), "+f"(d[94]), "+f"(d[95]), "+f"(d[96]), "+f"(d[97]), "+f"(d[98]),
        "+f"(d[99]), "+f"(d[100]), "+f"(d[101]), "+f"(d[102]), "+f"(d[103]), "+f"(d[104]), "+f"(d[105]), "+f"(d[106]), "+f"(d[107])
      : "r"(al), "r"(ah), "r"(bl), "r"(bh));
}
__device__ __forceinline__ void wgmma_ss_72(float* d, uint32_t al, uint32_t ah, uint32_t bl, uint32_t bh) {
  asm volatile("{\n.reg .b64 da, db;\nmov.b64 da, {%36, %37};\nmov.b64 db, {%38, %39};\n"
      "wgmma.mma_async.sync.aligned.m64n72k16.f32.bf16.bf16 {"
      "%0,%1,%2,%3,%4,%5,%6,%7,%8,%9,%10,%11,%12,%13,%14,%15,%16,%17,%18,%19,%20,%21,%22,%23,%24,%25,%26,"
      "%27,%28,%29,%30,%31,%32,%33,%34,%35"
      "}, da, db, 1, 1, 1, 0, 1;\n}\n"
      : "+f"(d[0]), "+f"(d[1]), "+f"(d[2]), "+f"(d[3]), "+f"(d[4]), "+f"(d[5]), "+f"(d[6]), "+f"(d[7]), "+f"(d[8]),
        "+f"(d[9]), "+f"(d[10]), "+f"(d[11]), "+f"(d[12]), "+f"(d[13]), "+f"(d[14]), "+f"(d[15]), "+f"(d[16]), "+f"(d[17]),
        "+f"(d[18]), "+f"(d[19]), "+f"(d[20]), "+f"(d[21]), "+f"(d[22]), "+f"(d[23]), "+f"(d[24]), "+f"(d[25]), "+f"(d[26]),
        "+f"(d[27]), "+f"(d[28]), "+f"(d[29]), "+f"(d[30]), "+f"(d[31]), "+f"(d[32]), "+f"(d[33]), "+f"(d[34]), "+f"(d[35])
      : "r"(al), "r"(ah), "r"(bl), "r"(bh));
}
template <uint32_t BH>
__device__ __forceinline__ void wgmma_rs_216(float* d, uint32_t a0, uint32_t a1, uint32_t a2, uint32_t a3, uint32_t bl) {
  asm volatile("{\n.reg .b64 db;\nmov.b64 db, {%112, %113};\n"
      "wgmma.mma_async.sync.aligned.m64n216k16.f32.bf16.bf16 {"
      "%0,%1,%2,%3,%4,%5,%6,%7,%8,%9,%10,%11,%12,%13,%14,%15,%16,%17,%18,%19,%20,%21,%22,%23,%24,%25,%26,"
      "%27,%28,%29,%30,%31,%32,%33,%34,%35,%36,%37,%38,%39,%40,%41,%42,%43,%44,%45,%46,%47,%48,%49,%50,%51,%52,%53,"
      "%54,%55,%56,%57,%58,%59,%60,%61,%62,%63,%64,%65,%66,%67,%68,%69,%70,%71,%72,%73,%74,%75,%76,%77,%78,%79,%80,"
      "%81,%82,%83,%84,%85,%86,%87,%88,%89,%90,%91,%92,%93,%94,%95,%96,%97,%98,%99,%100,%101,%102,%103,%104,%105,%106,%107"
      "}, {%108,%109,%110,%111}, db, 1, 1, 1, 1;\n}\n"
      : "+f"(d[0]), "+f"(d[1]), "+f"(d[2]), "+f"(d[3]), "+f"(d[4]), "+f"(d[5]), "+f"(d[6]), "+f"(d[7]), "+f"(d[8]),
        "+f"(d[9]), "+f"(d[10]), "+f"(d[11]), "+f"(d[12]), "+f"(d[13]), "+f"(d[14]), "+f"(d[15]), "+f"(d[16]), "+f"(d[17]),
        "+f"(d[18]), "+f"(d[19]), "+f"(d[20]), "+f"(d[21]), "+f"(d[22]), "+f"(d[23]), "+f"(d[24]), "+f"(d[25]), "+f"(d[26]),
        "+f"(d[27]), "+f"(d[28]), "+f"(d[29]), "+f"(d[30]), "+f"(d[31]), "+f"(d[32]), "+f"(d[33]), "+f"(d[34]), "+f"(d[35]),
        "+f"(d[36]), "+f"(d[37]), "+f"(d[38]), "+f"(d[39]), "+f"(d[40]), "+f"(d[41]), "+f"(d[42]), "+f"(d[43]), "+f"(d[44]),
        "+f"(d[45]), "+f"(d[46]), "+f"(d[47]), "+f"(d[48]), "+f"(d[49]), "+f"(d[50]), "+f"(d[51]), "+f"(d[52]), "+f"(d[53]),
        "+f"(d[54]), "+f"(d[55]), "+f"(d[56]), "+f"(d[57]), "+f"(d[58]), "+f"(d[59]), "+f"(d[60]), "+f"(d[61]), "+f"(d[62]),
        "+f"(d[63]), "+f"(d[64]), "+f"(d[65]), "+f"(d[66]), "+f"(d[67]), "+f"(d[68]), "+f"(d[69]), "+f"(d[70]), "+f"(d[71]),
        "+f"(d[72]), "+f"(d[73]), "+f"(d[74]), "+f"(d[75]), "+f"(d[76]), "+f"(d[77]), "+f"(d[78]), "+f"(d[79]), "+f"(d[80]),
        "+f"(d[81]), "+f"(d[82]), "+f"(d[83]), "+f"(d[84]), "+f"(d[85]), "+f"(d[86]), "+f"(d[87]), "+f"(d[88]), "+f"(d[89]),
        "+f"(d[90]), "+f"(d[91]), "+f"(d[92]), "+f"(d[93]), "+f"(d[94]), "+f"(d[95]), "+f"(d[96]), "+f"(d[97]), "+f"(d[98]),
        "+f"(d[99]), "+f"(d[100]), "+f"(d[101]), "+f"(d[102]), "+f"(d[103]), "+f"(d[104]), "+f"(d[105]), "+f"(d[106]), "+f"(d[107])
      : "r"(a0), "r"(a1), "r"(a2), "r"(a3), "r"(bl), "n"(BH));
}

struct Ctx {
  int i, j, cta;
};
#define TSTAMP(k) do {} while (0)
#define PSTAMP(k) do {} while (0)
#define PROF_DUMP() do {} while (0)
#define PROF_END() do {} while (0)
#define GSTAMP(k) do {} while (0)
#define CSTAMP(k) STAMPIF(1, L * 40 + p * 20 + (k))

__device__ __forceinline__ int ffn_c32(int cta) { return 32 * cta; }
__device__ __forceinline__ int ffn_c8(int cta) { return 4096 + 8 * (cta >> 1); }
__device__ __forceinline__ void load_gu(const Params& P, const int cta_, const int mat, const int b, const uint32_t bar) {
  const int cta = cta_;
  w_tma2d(sb + SM_G + mat * 46080 + b * 6144, &P.mg + mat, ffn_c32(cta), b * 96, bar);
  if (cta & 1) w_tma2d(sb + SM_G + mat * 46080 + 36864 + b * 1536, &P.mg8 + mat, ffn_c8(cta), b * 96, bar);
}

struct Winner { float r, m, rstd; int ci, rr; };

__device__ __forceinline__ Winner poll_winner(const void* p, uint4 v, const uint32_t tg) {
  int n = 0;
#pragma unroll 1
  while (!__all_sync(0xffffffffu, ((v.y ^ (tg << 6)) >> 6) == 0)) {
    rld128(v, p);
    if (++n > SPIN) TIMEOUT(__LINE__)
  }
  uint32_t key = fkey(asf(v.x));
  uint32_t mx = __reduce_max_sync(0xffffffffu, key);
  int src = __ffs(__ballot_sync(0xffffffffu, key == mx)) - 1;
  Winner w;
  w.ci = src;
  w.r = asf(__shfl_sync(0xffffffffu, v.x, src));
  w.rr = (int)__shfl_sync(0xffffffffu, v.y, src) & 63;
  w.m = asf(__shfl_sync(0xffffffffu, v.z, src));
  w.rstd = asf(__shfl_sync(0xffffffffu, v.w, src));
  return w;
}

__device__ __forceinline__ float2 row_stats(const Params& P, const int r, const int lane) {
  const unsigned char* src = (const unsigned char*)P.x + (((r & ~127) + 2 * (r & 63) + ((r >> 6) & 1)) * 1152 + (lane & 15) * 16);
  uint4 v[4];
#pragma unroll
  for (int m = 0; m < 4; m++) v[m] = ldg_nc128(src + m * 256);
  uint2 v4;
  asm volatile("ld.global.nc.v2.b32 {%0,%1}, [%2];" : "=r"(v4.x), "=r"(v4.y) : "l"(src + (1024 - (lane & 15) * 8)));
  nb_arrive(NB_START, 288 + pin0(v4.x));
  const float sft = __shfl_sync(0xffffffffu, bf_lo(v[0].x), lane & 16);
  float s1 = 0.f, s2 = 0.f, s3 = 0.f;
#pragma unroll
  for (int e = 0; e < 18; e++) {
    const uint32_t u = e < 16 ? (&v[0].x)[e] : (&v4.x)[e - 16];
    const float d0 = bf_lo(u) - sft, d1 = bf_hi(u) - sft;
    s1 += d0 + d1; s2 = fmaf(d0, d0, s2); s3 = fmaf(d1, d1, s3);
  }
  s2 += s3;
#pragma unroll
  for (int o = 1; o < 16; o <<= 1) { s1 += shx(s1, o); s2 += shx(s2, o); }
  s1 *= (1.f / 576.f);
  return make_float2(s1 + sft, rsq(fmaxf(s2 * (1.f / 576.f) - s1 * s1, 0.f) + EPS));
}

struct Unit { uint4 v[3]; };
__device__ __forceinline__ Unit unit_load(const unsigned char* src) {
  Unit u;
#pragma unroll
  for (int m = 0; m < 3; m++) u.v[m] = ldg_nc128(src + m * 48);
  return u;
}
__device__ __forceinline__ uint32_t unit_store(unsigned char* sc, const Unit& u, const int lane, const uint32_t o0, const uint32_t o1, const uint32_t o2) {
  stg128(sc + o0, u.v[0].x, u.v[0].y, u.v[0].z, u.v[0].w);
  stg128(sc + o1, u.v[1].x, u.v[1].y, u.v[1].z, u.v[1].w);
  stg128(sc + o2, u.v[2].x, u.v[2].y, u.v[2].z, u.v[2].w);
  return ldg_rlx32(sc + ((lane & 3) == 0 ? o0 : (lane & 3) == 1 ? o1 : o2));
}

__device__ __forceinline__ void store_rows(const uint32_t stg, unsigned char* obase, const int skip, const int lane) {
#pragma unroll
  for (int m = 0; m < 5; m++) {
    const int e = lane + 32 * m, r = (e * 57) >> 9;
    const uint4 v = lds128(stg + min(e, 143) * 16);
    if (e < 144 && r != skip) *(uint4*)(obase + (r * (2304 - 144) + e * 16)) = v;
  }
}

__device__ __forceinline__ void consumer_role(const Ctx& cx, const Params& P, const unsigned char* smem, const int p, const int w, const int lane_) {
  int lane = lane_;
#define g (lane >> 2)
#define q (lane & 3)
#define first_lane (lane == 0)
  const int i = cx.i, j = cx.j, ip = i * 2 + p;
  unsigned char* const sc = (unsigned char*)P.sc;
  float m_lo = 0.f, m_hi = 0.f, rs_lo = 0.f, rs_hi = 0.f;
  uint32_t T = ldg_rlx32(P.sc->cflag[ip][j * 4 + w]);
  nb_sync(NB_ORD, 352);
  if (X_DELAY) { const int c0 = clock(); while ((int)(clock() - c0) < X_DELAY + (p * 4 + w) * X_STEP) {} }
  {
    const int t = min(w * 32 + lane, 95);
    uint32_t u0 = 0, u1 = 0, u2 = 0, u = 0;
    if (p == 0) {
      u0 = ldg_nc32((const uint32_t*)P.wr + t); u1 = ldg_nc32((const uint32_t*)P.wr + 96 + t); u2 = ldg_nc32((const uint32_t*)P.wr + 192 + t);
      u = ldg_nc32((const uint32_t*)P.wr + 36 * j + min(t, 35));
    }
    const int r = cx.cta * 16 + (p * 4 + w) * 2 + (lane >> 4);
    const float2 st = row_stats(P, r, lane);
    T = __shfl_sync(0xffffffffu, (T >> 3) + 1, 0);
    if ((lane & 15) == 0) stg128(sc + (OFF(st0) + r * 16), asu(st.x), asu(st.y), T, 0u);
    STAMPIF(1, 111);
    if (p == 0) {
      float s = (bf_lo(u0) + bf_hi(u0)) + (bf_lo(u1) + bf_hi(u1)) + (bf_lo(u2) + bf_hi(u2));
#pragma unroll
      for (int o = 1; o < 32; o <<= 1) s += shx(s, o);
      stsf(sb + SM_WR + 288 + w * 4, s);
      sts64(sb + SM_WR + min(t, 35) * 8, u << 16, u & 0xFFFF0000u);
    }
  }
#pragma unroll 1
  for (int L = 0; L < 2; L++) {
    lane = pin(lane);
    const uint32_t tg = 2 * T + L;
    float c_lo = 0.f, c_hi = 0.f;
    bool sel_lo = false, sel_hi = false;
    float acc[108];
#pragma unroll
    for (int k = 0; k < 108; k++) acc[k] = 0.f;
    fence_regs<108>(acc);
    {
      const uint32_t ah = L == 0 ? DHI(1024, 1) : DHI(128, 0);
      const uint32_t astep = L == 0 ? 2 : 128;
      const uint32_t a0 = (L == 0 ? DLO(sb + SM_A, 16) : DLO(sb + SM_A, 1024)) + p * 512;
      constexpr uint32_t bh = DHI(512, 0);
      if (L == 1) {
        const float ul = 1.f + rs_lo, uh = 1.f + rs_hi;
        const float vl = fmaxf(rcp(rs_lo * rs_lo) - EPS, 0.f), vh = fmaxf(rcp(rs_hi * rs_hi) - EPS, 0.f);
        c_lo = ul * rsq(vl * ul * ul + EPS);
        c_hi = uh * rsq(vh * uh * uh + EPS);
      }
      if (L == 1) mbar_wait(sb + BAR_AFULL + p * 8, 0);
      mbar_wait(sb + BAR_FULL, 0);
      if (L == 1 && (p == 1 || Q1_BOTH)) nb_sync(NB_FFN2, Q1_BOTH ? 352 : 224);
      CSTAMP(0); GSTAMP(120 + 2 * L);
      uint32_t e0 = 0, e1 = 0;
      bool prepped = false, gone = false;
      auto prep_ext = [&]() {
        const int row = p * 64 + w * 16 + g;
        if (L == 0) {
          const uint2 u0 = lds64(sb + SM_R + row * 8), u1 = lds64(sb + SM_R + row * 8 + 64);
          m_lo = asf(u0.x); c_lo = asf(u0.y); m_hi = asf(u1.x); c_hi = asf(u1.y);
        } else {
          const uint4 sv = lds128(sb + SM_SEL);
          sel_lo = (int)sv.x == row; sel_hi = (int)sv.x == row + 8;
          if (sel_lo) { m_lo = asf(sv.z); c_lo = asf(sv.w); }
          if (sel_hi) { m_hi = asf(sv.z); c_hi = asf(sv.w); }
        }
        const float hl = rbf(-m_lo), hh = rbf(-m_hi);
        const uint32_t em = selu(lane & 1, 0x0000FFFFu, 0xFFFFFFFFu);
        e0 = selu(lane & 2, selu(sel_lo && !(lane & 1), 0x3F803F80u, 0u), pack_bf16(hl, -m_lo - hl) & em);
        e1 = selu(lane & 2, selu(sel_hi && !(lane & 1), 0x3F803F80u, 0u), pack_bf16(hh, -m_hi - hh) & em);
      };
      bool pend = false;
#pragma unroll 1
      for (int r = 0; r < 3; r++) {
#pragma unroll
        for (int h = 0; h < 6; h++) {
          const uint32_t al = a0 + (h >> 1) * 1024 + (h & 1) * 2 * astep, bl = DLO(sb + SM_B, 128) + h * 864;
          const uint32_t nb = sb + BAR_FULL + ((h + 1) % 6) * 8, np = (r + (h == 5)) & 1;
          TSTAMP((6 * r + h) * 2);
          wg_fence();
          wgmma_ss_216(acc, al, ah, bl, bh);
          wgmma_ss_216(acc, al + astep, ah, bl + 16, bh);
          wg_commit();
          if (h == 5 && r == 2) break;
          const uint32_t ok = mbar_test(nb, np);
          if ((h == 1 || h == 3) && r == 0 && L == 1) mbar_wait(sb + BAR_AFULL + (h + 1 + p) * 8, 0);
          if (h == 0 && r == 1 && L == 0) {
          if (lane < 16) stg128(sc + (OFF(stats) + (ip * 4 + w) * 2048 + j * 256 + lane * 16), 0u, 0u, 0u, 0u);
          if (w == 3 && i < 15 && lane < 28) {
#pragma unroll
            for (int e = 0; e < 6; e++) stg128(sc + (OFF(halo) + ((ip + 2) * 8 + j) * 2688 + lane * 16) + e * 448, 0u, 0u, 0u, 0u);
          }
          if (w == 0 && lane < 2) stg128(sc + (OFF(cand) + (j * 32 + ip) * (CAND_W * 4) + lane * 16), 0u, 0u, 0u, 0u);
          }
          wg_wait<1>();
          if (first_lane && pend) mbar_arrive(sb + BAR_EMPTY + ((h + 5) % 6) * 8);
          pend = true;
          const bool hold = h == HOLD_C % 6 && r == HOLD_C / 6 && p == 1;
          if (hold || (!ok && !mbar_test(nb, np))) {
            wg_wait<0>();
            if (first_lane) mbar_arrive(sb + BAR_EMPTY + h * 8);
            pend = false;
            TSTAMP((6 * r + h) * 2 + 1);
            mbar_wait(nb, np);
            if (hold) {
              if (mbar_test(sb + BAR_FIX + 8, L)) { prep_ext(); prepped = true; }
              nb_sync(NB_STAG, 256);
            }
          }
        }
      }
      if (!prepped) {
        if (p == 0 && !gone && !mbar_test(sb + BAR_FIX, L)) { nb_arrive(NB_STAG, 256); gone = true; }
        mbar_wait(sb + BAR_FIX + p * 8, L);
        prep_ext();
      }
      wg_fence();
      wgmma_rs_216<DHI(128, 0)>(acc, e0, e1, 0u, 0u, DLO(sb + SM_BEXT, 0));
      wg_commit();
      if (p == 0 && !gone) nb_arrive(NB_STAG, 256);
      wg_wait<2>();
      if (first_lane && pend) mbar_arrive(sb + BAR_EMPTY + 32);
    }
    lane = pin(lane);
    const uint32_t fragoff = ip * 73728 + (9 * j) * 1024 + w * 256 + lane * 4;
    const uint32_t rboff = (min(lane, 17) >> 1) * 1024 + (lane < 18 ? lane & 1 : 0) * 128;
    const uint32_t hl16 = (lane < 4 ? lane : lane - 4) * 16;
    const uint32_t o_halo = pin(OFF(halo) + ((ip + (w == 3 ? 2 : 0)) * 8 + j) * 2688 + hl16);
    const uint32_t o_o = pin(OFF(obuf) + fragoff);
    nb_sync(NB_WG + p, 128);
    if ((o_halo | o_o) == 0xFFFFFFFFu) __trap();
    wg_wait<0>();
    fence_regs<108>(acc);
    if (first_lane) mbar_arrive(sb + BAR_EMPTY + 40);
    CSTAMP(1); GSTAMP(121 + 2 * L);
    {
      uint32_t Kh[9], Vh[9], Kl[9], Vl[9], Kx[9], Vx[9], Ql[9], Qh[9];
#pragma unroll
      for (int t = 0; t < 9; t++) {
        Kh[t] = pack_bf16(acc[4 * GI(1, t) + 2] * c_hi, acc[4 * GI(1, t) + 3] * c_hi);
        Vh[t] = pack_bf16(acc[4 * GI(2, t) + 2] * c_hi, acc[4 * GI(2, t) + 3] * c_hi);
        Ql[t] = pack_bf16(acc[4 * GI(0, t)], acc[4 * GI(0, t) + 1]);
        Qh[t] = pack_bf16(acc[4 * GI(0, t) + 2], acc[4 * GI(0, t) + 3]);
      }
      const uint32_t hbuf = sb + SM_A + p * 8192 + w * 2688 + hl16;
      if (w < 3) {
        if (lane >= 4) {
#pragma unroll
          for (int e = 0; e < 4; e++) sts128(hbuf + e * 448, Kh[2 * e], Kh[2 * e + 1], Vh[e], tg);
          sts128(hbuf + 4 * 448, Kh[8], Vh[4], Vh[5], tg);
          sts128(hbuf + 5 * 448, Vh[6], Vh[7], Vh[8], tg);
        }
      } else if (i < 15 && lane >= 4) {
#pragma unroll
        for (int e = 0; e < 4; e++) stg128(sc + o_halo + e * 448, Kh[2 * e], Kh[2 * e + 1], Vh[e], tg);
        stg128(sc + o_halo + 4 * 448, Kh[8], Vh[4], Vh[5], tg);
        stg128(sc + o_halo + 5 * 448, Vh[6], Vh[7], Vh[8], tg);
      }
      nb_sync(NB_WG + p, 128);
#pragma unroll
      for (int t = 0; t < 9; t++) {
        Kl[t] = pack_bf16(acc[4 * GI(1, t)] * c_lo, acc[4 * GI(1, t) + 1] * c_lo);
      }
#pragma unroll
      for (int t = 0; t < HALO_V; t++) Vl[t] = pack_bf16(acc[4 * GI(2, t)] * c_lo, acc[4 * GI(2, t) + 1] * c_lo);
      uint32_t dep = (Kl[0] ^ Kl[1] ^ Kl[2]) | (Kl[3] ^ Kl[4] ^ Kl[5]) | (Kl[6] ^ Kl[7] ^ Kl[8]);
#pragma unroll
      for (int t = 0; t < HALO_V; t += 3) dep |= Vl[t] ^ Vl[t + 1] ^ Vl[t + 2];
      const unsigned char* hp = (w > 0 ? smem + (hbuf - 2688 - sb) : sc + o_halo) + pin0(dep);
      uint4 hv[6];
#pragma unroll
      for (int e = 0; e < 6; e++)
        asm volatile("ld.relaxed.gpu.v4.b32 {%0,%1,%2,%3}, [%4];" : "=r"(hv[e].x), "=r"(hv[e].y), "=r"(hv[e].z), "=r"(hv[e].w) : "l"(hp + e * 448) : "memory");
      CSTAMP(2);
#pragma unroll
      for (int t = 0; t < 9; t++) {
        if (t >= HALO_V) Vl[t] = pack_bf16(acc[4 * GI(2, t)] * c_lo, acc[4 * GI(2, t) + 1] * c_lo);
        Vl[t] = movm(Vl[t]);
        Vh[t] = movm(Vh[t]);
      }
      uint32_t qa[4][2], qb[4][2];
      float s1[4][4], s2[4][4];
#pragma unroll
      for (int h = 0; h < 4; h++) {
        qa[h][0] = q >= h ? Ql[2 * h] : 0u; qa[h][1] = q >= h ? Qh[2 * h] : 0u;
        qb[h][0] = q <= h ? Ql[2 * h + 2] : 0u; qb[h][1] = q <= h ? Qh[2 * h + 2] : 0u;
      }
      const bool first = (i == 0 && w == 0);
      if (w == 0 && i > 0) {
        int n = 0;
#pragma unroll 1
        while (__any_sync(0xffffffffu, (orx(orx(orx(0, hv[0].w, tg), hv[1].w, tg), hv[2].w, tg) | orx(orx(orx(0, hv[3].w, tg), hv[4].w, tg), hv[5].w, tg)) != 0)) {
#pragma unroll
          for (int e = 0; e < 6; e++) rld128(hv[e], sc + o_halo + e * 448);
          if (++n > SPIN) TIMEOUT(__LINE__)
        }
      }
#pragma unroll
      for (int e = 0; e < 4; e++) { Kx[2 * e] = hv[e].x; Kx[2 * e + 1] = hv[e].y; Vx[e] = hv[e].z; }
      Kx[8] = hv[4].x; Vx[4] = hv[4].y; Vx[5] = hv[4].z; Vx[6] = hv[5].x; Vx[7] = hv[5].y; Vx[8] = hv[5].z;
      CSTAMP(3);
#pragma unroll
      for (int t = 0; t < 9; t++) Vx[t] = movm(Vx[t]);
#pragma unroll
      for (int h = 0; h < 4; h++) { mma8z(s1[h], qb[h][0], qb[h][1], Kl[2 * h + 2]); mma8z(s2[h], qb[h][0], qb[h][1], Kh[2 * h + 2]); }
#pragma unroll
      for (int h = 0; h < 4; h++) {
        mma16(s1[h], qa[h][0], qa[h][1], Ql[2 * h + 1], Qh[2 * h + 1], Kl[2 * h], Kl[2 * h + 1]);
        mma16(s2[h], qa[h][0], qa[h][1], Ql[2 * h + 1], Qh[2 * h + 1], Kh[2 * h], Kh[2 * h + 1]);
      }
      float s0[4][4];
#pragma unroll
      for (int h = 0; h < 4; h++) mma8z(s0[h], qb[h][0], qb[h][1], Kx[2 * h + 2]);
#pragma unroll
      for (int h = 0; h < 4; h++) mma16(s0[h], qa[h][0], qa[h][1], Ql[2 * h + 1], Qh[2 * h + 1], Kx[2 * h], Kx[2 * h + 1]);
      const bool pv0 = 2 * q > g, pv1 = 2 * q + 1 > g;
      const uint32_t PM = (pv0 ? 0x0000FFFFu : 0u) | (pv1 ? 0xFFFF0000u : 0u);
      const float kS = 0.23570226039551584f * 1.4426950408889634f;
      const float sc_lo = c_lo * kS, sc_hi = c_hi * kS;
      float sl[4][2], sh[4][2], ml[4], mh[4];
#pragma unroll
      for (int h = 0; h < 4; h++) {
        sh[h][0] = pv0 ? s1[h][2] : s2[h][2];
        sh[h][1] = pv1 ? s1[h][3] : s2[h][3];
        mh[h] = fmaxf(sh[h][0], sh[h][1]);
        sl[h][0] = pv0 ? (first ? -INFINITY : s0[h][0]) : s1[h][0];
        sl[h][1] = pv1 ? (first ? -INFINITY : s0[h][1]) : s1[h][1];
        ml[h] = fmaxf(sl[h][0], sl[h][1]);
      }
#pragma unroll
      for (int s = 1; s <= 2; s <<= 1) {
        float tl[4], th[4];
#pragma unroll
        for (int h = 0; h < 4; h++) { th[h] = shx(mh[h], s); tl[h] = shx(ml[h], s); }
#pragma unroll
        for (int h = 0; h < 4; h++) { mh[h] = fmaxf(mh[h], th[h]); ml[h] = fmaxf(ml[h], tl[h]); }
      }
      float o[4][3][4], den[4][4];
      uint32_t px[4];
#pragma unroll
      for (int h = 0; h < 4; h++) {
        const float bl = -ml[h] * sc_lo, bh = -mh[h] * sc_hi;
        const uint32_t pl = pack_bf16(ex2(fmaf(sl[h][0], sc_lo, bl)), ex2(fmaf(sl[h][1], sc_lo, bl)));
        const uint32_t ph = pack_bf16(ex2(fmaf(sh[h][0], sc_hi, bh)), ex2(fmaf(sh[h][1], sc_hi, bh)));
        mma8z(den[h], pl, ph, 0x3F803F80u);
        px[h] = pl & PM;
#pragma unroll
        for (int u = 0; u < 3; u++) mma16z(o[h][u], pl & ~PM, ph & PM, 0u, ph & ~PM, Vl[2 * h + u], Vh[2 * h + u]);
      }
#pragma unroll
      for (int h = 0; h < 4; h++)
#pragma unroll
        for (int u = 0; u < 3; u++) mma8(o[h][u], px[h], 0u, Vx[2 * h + u]);
      float il[4], ih[4];
#pragma unroll
      for (int h = 0; h < 4; h++) { il[h] = rcp(den[h][0]); ih[h] = rcp(den[h][2]); }
#pragma unroll
      for (int t = 0; t < 9; t++) {
        const int h = t == 8 ? 3 : t >> 1, u = t == 8 ? 2 : t & 1;
        float v0 = o[h][u][0], v1 = o[h][u][1], v2 = o[h][u][2], v3 = o[h][u][3], kl = il[h], kh = ih[h];
        if (u == 0 && h > 0 && q < h) {
          v0 = o[h - 1][2][0]; v1 = o[h - 1][2][1]; v2 = o[h - 1][2][2]; v3 = o[h - 1][2][3]; kl = il[h - 1]; kh = ih[h - 1];
        }
        stg32(sc + o_o + t * 1024, pack_bf16(v0 * kl, v1 * kl));
        stg32(sc + o_o + t * 1024 + 128, pack_bf16(v2 * kh, v3 * kh));
      }
    }
    CSTAMP(4);
    const uint32_t rbo = ldg_rlx32(sc + (o_o + rboff));
    lane = pin(lane);
    const uint32_t o_x = o_o + (OFF(xbuf) - OFF(obuf)), o_xrb = o_x + rboff;
    const uint32_t o_cf = OFF(cflag) + (ip * 32 + j * 4 + w) * 32 + lane * 4;
    if (L == 1 && first_lane) mbar_arrive(sb + BAR_HDONE + p * 8);
    flag_after(sc + o_cf, rbo, 8 * T + 2 * L, lane < 8);
    STAMPD(asf(rbo), L * 40 + p * 20 + 13);
    uint32_t resid[18];
    mbar_wait(sb + BAR_FULL + 16, 1); mbar_wait(sb + BAR_FULL + 32, 1);
    if (L == 0) {
      const uint32_t ra = sb + SM_A + (2 + p) * 8192 + (w * 16 + (lane & 15)) * 128;
#pragma unroll
      for (int t = 0; t < 9; t++) ldsm2(resid[2 * t], resid[2 * t + 1], ra + ((j + t) >> 3) * 16384 + ((((j + t) ^ lane) & 7) << 4));
      if (first_lane) mbar_arrive(sb + BAR_HDONE + p * 8 + pin0(resid[17]));
    } else {
#pragma unroll
      for (int t = 0; t < 9; t++) { resid[2 * t] = ldg_rlx32(sc + o_x + t * 1024); resid[2 * t + 1] = ldg_rlx32(sc + o_x + t * 1024 + 128); }
    }
    const uint32_t o_st = OFF(stats) + (ip * 4 + w) * 2048;
    const uint32_t o_stw = pin(o_st + j * 256 + (g + 8 * (q & 1)) * 16), o_str = pin(o_st + q * 512 + g * 16);
    const uint32_t o_cand = pin(OFF(cand) + (j * 32 + ip) * (CAND_W * 4) + q * 16);
    const uint32_t o_xc = pin(OFF(xcand) + (ip * 8 + j) * 192 + q * 16);
    float accw[36];
    float wr[18];
#pragma unroll
    for (int t = 0; t < 9; t++) { const uint2 u = lds64(sb + SM_WR + t * 32 + q * 8); wr[2 * t] = asf(u.x); wr[2 * t + 1] = asf(u.y); }
    const uint4 ws4 = lds128(sb + SM_WR + 288);
    const float wsum = asf(pin(asu(asf(ws4.x) + asf(ws4.y) + asf(ws4.z))));
    {
      float ul = 1.f, uh = 1.f, vl = 0.f, vh = 0.f;
      if (L == 1) {
        ul += rs_lo; uh += rs_hi; vl = -m_lo * rs_lo; vh = -m_hi * rs_hi;
        if (sel_lo || sel_hi) {
#pragma unroll
          for (int t = 0; t < 9; t++) {
            const uint32_t z = lds32(sb + SM_X2S + t * 16 + q * 4);
            if (sel_hi) resid[2 * t + 1] = z; else resid[2 * t] = z;
          }
          if (sel_hi) { uh = 1.f; vh = 0.f; } else { ul = 1.f; vl = 0.f; }
        }
        __syncwarp();
      }
#pragma unroll
      for (int t = 0; t < 9; t++) {
        accw[4 * t] = fmaf(bf_lo(resid[2 * t]), ul, vl); accw[4 * t + 1] = fmaf(bf_hi(resid[2 * t]), ul, vl);
        accw[4 * t + 2] = fmaf(bf_lo(resid[2 * t + 1]), uh, vh); accw[4 * t + 3] = fmaf(bf_hi(resid[2 * t + 1]), uh, vh);
      }
    }
    fence_regs<36>(accw);
    mbar_wait(sb + BAR_FULL, 1); mbar_wait(sb + BAR_FULL + 8, 1); mbar_wait(sb + BAR_FULL + 24, 1); mbar_wait(sb + BAR_FULL + 40, 1);
    {
      uint32_t wf = sb + BAR_WFULL + p * 72;
      uint32_t bl = DLO(sb + SM_B, 128);
      uint32_t half = p;
      mbar_wait(wf, L);
      CSTAMP(5);
#pragma unroll 1
      for (int c3 = 0; c3 < 3; c3++) {
        const uint32_t al = DLO(sb + SM_A, 1024) + half * 512;
        const uint32_t ae = sb + BAR_AEMPTY + half * 24;
#pragma unroll
        for (int cc = 0; cc < 3; cc++) {
          TSTAMP(36 + (c3 * 3 + cc) * 2);
          wg_fence();
          wgmma_ss_72(accw, al + cc * 1024, DHI(128, 0), bl + cc * 576, DHI(256, 0));
          wgmma_ss_72(accw, al + cc * 1024 + 128, DHI(128, 0), bl + cc * 576 + 144, DHI(256, 0));
          const uint32_t ok = mbar_test(wf + cc * 8 + 8, L);
          wgmma_ss_72(accw, al + cc * 1024 + 256, DHI(128, 0), bl + cc * 576 + 288, DHI(256, 0));
          wgmma_ss_72(accw, al + cc * 1024 + 384, DHI(128, 0), bl + cc * 576 + 432, DHI(256, 0));
          wg_commit();
          wg_wait<1>();
          if (cc > 0) { if (first_lane) { mbar_arrive(ae + cc * 8 - 8); if (cc == 2) mbar_arrive(sb + BAR_EMPTY + c3 * 16); } }
          else if (first_lane && c3 > 0) { mbar_arrive(sb + BAR_AEMPTY + 40 - half * 24); mbar_arrive(sb + BAR_EMPTY + c3 * 16 - 8); }
          if (!ok && (cc < 2 || c3 < 2)) mbar_wait(wf + cc * 8 + 8, L);
        }
        wf += 24; bl += 1728; half ^= 1;
      }
    }
    wg_wait<0>();
    fence_regs<36>(accw);
    if (first_lane) { mbar_arrive(sb + BAR_AEMPTY + (2 + 3 * p) * 8); mbar_arrive(sb + BAR_EMPTY + 40); }
    CSTAMP(6);
    uint32_t xw[18];
    uint32_t rb = 0;
    if (L == 0 && p == 0) {
#pragma unroll
      for (int t = 0; t < 9; t++) {
        stg32(sc + o_x + t * 1024, pack_bf16(accw[4 * t], accw[4 * t + 1]));
        stg32(sc + o_x + t * 1024 + 128, pack_bf16(accw[4 * t + 2], accw[4 * t + 3]));
      }
      rb = ldg_rlx32(sc + o_xrb);
      fence_regs<36>(accw);
    }
    {
      float a0[2] = {0.f, 0.f}, a1[2] = {0.f, 0.f}, a2[2] = {0.f, 0.f}, b0[2] = {0.f, 0.f}, b1[2] = {0.f, 0.f}, b2[2] = {0.f, 0.f};
#pragma unroll
      for (int t = 0; t < 9; t++) {
#pragma unroll
        for (int e = 0; e < 2; e++) {
          const float x = accw[4 * t + e], y = accw[4 * t + 2 + e];
          a0[e] += x; a1[e] = fmaf(x, x, a1[e]); a2[e] = fmaf(x, wr[2 * t + e], a2[e]);
          b0[e] += y; b1[e] = fmaf(y, y, b1[e]); b2[e] = fmaf(y, wr[2 * t + e], b2[e]);
        }
      }
      const bool od = q & 1;
      const float A0 = a0[0] + a0[1], A1 = a1[0] + a1[1], A2 = a2[0] + a2[1], B0 = b0[0] + b0[1], B1 = b1[0] + b1[1], B2 = b2[0] + b2[1];
      float k0 = od ? B0 : A0, k1 = od ? B1 : A1, k2 = od ? B2 : A2;
      k0 += shx(od ? A0 : B0, 1); k1 += shx(od ? A1 : B1, 1); k2 += shx(od ? A2 : B2, 1);
      k0 += shx(k0, 2); k1 += shx(k1, 2); k2 += shx(k2, 2);
      if (q < 2) stg128(sc + o_stw, asu(k0), asu(k1), asu(k2), tg);
      STAMPD(k0, L * 40 + p * 20 + 14);
    }
#pragma unroll
    for (int t = 0; t < 9; t++) {
      xw[2 * t] = pack_bf16(accw[4 * t], accw[4 * t + 1]);
      xw[2 * t + 1] = pack_bf16(accw[4 * t + 2], accw[4 * t + 3]);
    }
    float r_lo, r_hi;
    {
      if (D_STATS) { const int c0 = clock(); while ((int)(clock() - c0) < D_STATS) {} }
      uint4 u0 = ldg_rlx128(sc + o_str), u1 = ldg_rlx128(sc + o_str + 256), u2 = ldg_rlx128(sc + o_str + 128), u3 = ldg_rlx128(sc + o_str + 384);
      flag_after(sc + o_cf, rb, 8 * T + 1, lane < 8 && L == 0 && p == 0);
      STAMPD(asf(u3.w), L * 40 + p * 20 + 15);
      int n = 0;
#pragma unroll 1
      while (__any_sync(0xffffffffu, orx(orx(orx(orx(0, u0.w, tg), u1.w, tg), u2.w, tg), u3.w, tg) != 0)) {
        rld128(u0, sc + o_str); rld128(u1, sc + o_str + 256); rld128(u2, sc + o_str + 128); rld128(u3, sc + o_str + 384);
        if (++n > SPIN) TIMEOUT(__LINE__)
      }
      float a0 = asf(u0.x) + asf(u1.x), a1 = asf(u0.y) + asf(u1.y), a2 = asf(u0.z) + asf(u1.z);
      float b0 = asf(u2.x) + asf(u3.x), b1 = asf(u2.y) + asf(u3.y), b2 = asf(u2.z) + asf(u3.z);
#pragma unroll
      for (int s = 1; s <= 2; s <<= 1) {
        const float t0 = shx(a0, s), t1 = shx(a1, s), t2 = shx(a2, s), t3 = shx(b0, s), t4 = shx(b1, s), t5 = shx(b2, s);
        a0 += t0; a1 += t1; a2 += t2; b0 += t3; b1 += t4; b2 += t5;
      }
      m_lo = a0 * (1.f / 576.f); m_hi = b0 * (1.f / 576.f);
      rs_lo = rsq(fmaxf(a1 * (1.f / 576.f) - m_lo * m_lo, 0.f) + EPS);
      rs_hi = rsq(fmaxf(b1 * (1.f / 576.f) - m_hi * m_hi, 0.f) + EPS);
      r_lo = (a2 - m_lo * wsum) * rs_lo; r_hi = (b2 - m_hi * wsum) * rs_hi;
    }
    CSTAMP(7);
    if (ST_HOLD && L == 0 && p == ST_P && w == 0 && first_lane) mbar_arrive(sb + BAR_ST + pin0(asu(r_lo)));
    if (LATE_Q1 == 3 && L == 0 && p == 1 && w == 0 && first_lane) mbar_arrive(sb + BAR_ST + pin0(asu(r_lo)));
    int candrow = -1;
    {
      const uint32_t kl = fkey(r_lo), kh = fkey(r_hi);
      const bool hi = kh > kl;
      const uint32_t kb = hi ? kh : kl;
      const uint32_t mx = __reduce_max_sync(0xffffffffu, kb);
      if (first_lane) sts32(sb + SM_BEST + p * 16 + w * 4, mx);
      const uint32_t bal = __ballot_sync(0xffffffffu, kb == mx);
      const bool mine = (bal & ((1u << (lane & 28)) - 1u)) == 0u && kb == mx;
      const uint32_t x0 = hi ? xw[1] : xw[0], x1 = hi ? xw[3] : xw[2], x2 = hi ? xw[5] : xw[4], x3 = hi ? xw[7] : xw[6], x4 = hi ? xw[9] : xw[8];
      const uint32_t x5 = hi ? xw[11] : xw[10], x6 = hi ? xw[13] : xw[12], x7 = hi ? xw[15] : xw[14], x8 = hi ? xw[17] : xw[16];
      nb_sync(NB_WG + p, 128);
      const uint4 bs = lds128(sb + SM_BEST + p * 16);
      const bool best = (w > 0 ? bs.x < mx : true) && (w > 1 ? bs.y < mx : bs.y <= mx) && (w > 2 ? bs.z < mx : bs.z <= mx) && bs.w <= mx;
      if (best && mine) {
        if (q < 2) stg128(sc + o_cand, asu(hi ? r_hi : r_lo), (tg << 6) + (uint32_t)(w * 16 + g + (hi ? 8 : 0)), asu(hi ? m_hi : m_lo), asu(hi ? rs_hi : rs_lo));
        stg128(sc + o_xc, x0, x1, x2, tg);
        stg128(sc + o_xc + 64, x3, x4, x5, tg);
        stg128(sc + o_xc + 128, x6, x7, x8, tg);
      }
      candrow = __reduce_max_sync(0xffffffffu, best && mine ? g + (hi ? 8 : 0) : -1);
    }
    if (L == 0 && p == 1) {
#pragma unroll
      for (int t = 0; t < 9; t++) { stg32(sc + o_x + t * 1024, xw[2 * t]); stg32(sc + o_x + t * 1024 + 128, xw[2 * t + 1]); }
      rb = ldg_rlx32(sc + o_xrb);
    }
    const uint32_t stg = sb + SM_B + p * 13824 + w * 2304;
    unsigned char* obase = (unsigned char*)P.out + ((128 * i + 32 * w + p) * 1152 + 144 * j);
    if (L == 1) {
      const float ul = 1.f + rs_lo, uh = 1.f + rs_hi, vl = -m_lo * rs_lo, vh = -m_hi * rs_hi;
#pragma unroll
      for (int t = 0; t < 9; t++) {
        xw[2 * t] = pack_bf16(fmaf(accw[4 * t], ul, vl), fmaf(accw[4 * t + 1], ul, vl));
        xw[2 * t + 1] = pack_bf16(fmaf(accw[4 * t + 2], uh, vh), fmaf(accw[4 * t + 3], uh, vh));
      }
      mbar_wait(sb + BAR_EMPTY + p * 8, 1);
      const uint32_t sa = stg + (lane & 15) * 144;
#pragma unroll
      for (int t = 0; t < 8; t += 2) stsm4(sa + (lane >> 4) * 16 + t * 16, xw[2 * t], xw[2 * t + 1], xw[2 * t + 2], xw[2 * t + 3]);
      stsm2(sa + 128, xw[16], xw[17]);
      __syncwarp();
      if (p == 0 || !OUT_LATE) store_rows(stg, obase, candrow, lane);
    }
    CSTAMP(8);
    lane = pin(lane);
    const unsigned char* cp = sc + (OFF(cand) + (j * 32 + lane) * (CAND_W * 4));
    if (p == 0) {
      if (L == 1 && candrow >= 0) {
        const Winner wn = poll_winner(cp, ldg_rlx128(cp), tg);
        if (lane < 9 && wn.ci != ip) *(uint4*)(obase + (candrow * 2304 + lane * 16)) = lds128(stg + candrow * 144 + lane * 16);
      }
    } else {
      const uint32_t gr = w * 144 + (lane & 7) + (lane >> 4) * 8, gm = sb + SM_G + ((lane >> 3) & 1) * 46080;
      const uint32_t ga = gm + gr * 64 + (((lane >> 1) & 3) << 4), gl = gm + 36864 + gr * 16;
#define GADDR(s, u) ((u) < 4 ? (ga ^ ((u) << 4)) + (s) * 1024 : gl + (s) * 256)
      uint32_t wf[NPRE][5][4];
      mbar_wait(sb + BAR_GU, 0);
#pragma unroll
      for (int s = 0; s < NPRE - 2; s++)
#pragma unroll
        for (int u = 0; u < 5; u++) ldsm4t(wf[s][u], GADDR(s, u));
      const uint4 c0 = ldg_rlx128(cp);
#pragma unroll
      for (int s = NPRE - 2; s < NPRE; s++)
#pragma unroll
        for (int u = 0; u < 5; u++) ldsm4t(wf[s][u], GADDR(s, u));
      flag_after(sc + o_cf, rb, 8 * T + 1, lane < 8 && L == 0);
      const Winner wn = poll_winner(cp, c0, tg);
      if (w == 0 && first_lane) sts128(sb + SM_WIN, asu(wn.r), asu(wn.m), asu(wn.rstd), (uint32_t)(wn.ci * 64 + wn.rr));
      if (LATE_Q1 == 2 && L == 0 && w == 0 && first_lane) mbar_arrive(sb + BAR_ST + pin0(wn.ci));
      CSTAMP(9);
      if (!OUT_LATE && L == 1 && candrow >= 0 && lane < 9 && wn.ci != ip) *(uint4*)(obase + (candrow * 2304 + lane * 16)) = lds128(stg + candrow * 144 + lane * 16);
      {
        uint32_t hb[18];
        const unsigned char* xc = sc + (OFF(xcand) + wn.ci * 1536 + q * 16);
        const int fp = min(cx.cta / 3, 23);
        uint4 u[7];
        int n = 0;
#pragma unroll 1
        while (true) {
          uint32_t d = 0;
#pragma unroll
          for (int e = 0; e < 7; e++) u[e] = ldg_rlx128(xc + (e < 6 ? w * 384 + e * 64 : fp * 64));
#pragma unroll
          for (int e = 0; e < 7; e++) d = orx(d, u[e].w, tg);
          if (__all_sync(0xffffffffu, d == 0)) break;
          if (++n > SPIN) TIMEOUT(__LINE__)
        }
        if (LATE_Q1 == 1 && L == 0 && w == 0 && first_lane) mbar_arrive(sb + BAR_ST + pin0(u[0].x));
        if (OUT_LATE == 3 && L == 1) store_rows(stg, obase, wn.ci == ip ? candrow : -1, lane);
#pragma unroll
        for (int e = 0; e < 6; e++) { hb[3 * e] = u[e].x; hb[3 * e + 1] = u[e].y; hb[3 * e + 2] = u[e].z; }
        if (w == 0) sts128(sb + SM_XW + q * 16, u[6].x, u[6].y, u[6].z, u[6].w);
        const float nb = -wn.m * wn.rstd;
#pragma unroll
        for (int b = 0; b < 18; b++) hb[b] = pack_bf16(fmaf(bf_lo(hb[b]), wn.rstd, nb), fmaf(bf_hi(hb[b]), wn.rstd, nb));
        CSTAMP(10);
        float d[5][4];
#pragma unroll
        for (int u = 0; u < 5; u++) d[u][0] = d[u][1] = d[u][2] = d[u][3] = 0.f;
#pragma unroll
        for (int s = 0; s < 9; s++) {
#pragma unroll
          for (int u = 0; u < 5; u++) {
            uint32_t* f = wf[s % NPRE][u];
            mma16(d[u], f[0], f[1], f[2], f[3], hb[2 * s], hb[2 * s + 1]);
            if (s + NPRE < 9) ldsm4t(f, GADDR(s + NPRE, u));
          }
        }
        if (q == 0) {
#pragma unroll
          for (int u = 0; u < 5; u++) sts64(sb + R_FPART + w * 320 + (u * 8 + g) * 8, asu(d[u][0]), asu(d[u][2]));
        }
        nb_arrive(NB_FFN, 224);
        CSTAMP(11);
      }
      if (OUT_LATE == 1 && L == 1) store_rows(stg, obase, wn.ci == ip ? candrow : -1, lane);
    }
  }
  STAMPIF(w == 0 && lane == 0, 40 + p * 20 + 12);
  PROF_DUMP();
#undef g
#undef q
#undef first_lane
}

__device__ __forceinline__ void load_wo_a(const Ctx& cx, const Params& P, const uint32_t T, const int L, const int p, const int lane) {
  const unsigned char* src = P.sc->obuf[cx.i * 2 + p];
#pragma unroll
  for (int c = 0; c < 9; c++) w_expect(sb + BAR_WFULL + (9 * p + c) * 8, 8192);
  mbar_wait(sb + BAR_HDONE + p * 8, L);
  wait_flags<32>(P.sc->cflag[cx.i * 2 + p], 8 * T + 2 * L, lane);
  fence_async_glob();
  STAMP(100 + L * 2 + p);
#pragma unroll
  for (int c = 0; c < 9; c++) {
    const int e = 9 * p + c, s = e % 6;
    if (e == 3) mbar_wait(sb + BAR_HDONE + 8, L);
    if (e >= 6) mbar_wait(sb + BAR_AEMPTY + s * 8, (L ^ (e / 6) ^ 1) & 1);
    w_bulk(sb + SM_A + (2 * (s % 3) + s / 3) * 8192, src + c * 8192, 8192, sb + BAR_WFULL + e * 8);
    PSTAMP(48 + L * 36 + 18 + e);
  }
}

__device__ __forceinline__ void finalize_row(const Params& P, const Winner& wn, const uint32_t T, const int L, const int grp, const int a, const int lane) {
  const unsigned char* yp = (const unsigned char*)P.sc->ypart[grp] + (a * 32 + lane) * 16;
  const uint32_t par = L ^ 1;
  if (L == 0 ? D_Y0 : D_Y1) { const int c0 = clock(); while ((int)(clock() - c0) < (L == 0 ? D_Y0 : D_Y1)) {} }
  uint4 u0 = ldg_rlx128(yp), u1 = ldg_rlx128(yp + 1536), u2 = make_uint4(par, 0, 0, 0);
  if (a < 2) rld128(u2, yp + 3072);
  const int col = lane & 7;
  const uint32_t xw = lds32(sb + SM_XW + (col >> 1) * 16 + (grp % 3) * 4);
  const float xsel = (col & 1) ? bf_hi(xw) : bf_lo(xw);
  const float sg = rbf(rcp(1.f + ex2(-1.4426950408889634f * rbf(wn.r))));
  const float h = rbf((xsel - wn.m) * wn.rstd);
  unsigned char* dst = L == 0 ? (unsigned char*)P.sc->xsel + (((lane >> 3) & 1) * 576 + grp * 8 + col) * 4
                              : (unsigned char*)P.out + ((128 * (wn.ci >> 1) + 2 * wn.rr + (wn.ci & 1)) * 576 + grp * 8 + col) * 2;
  int n = 0;
#pragma unroll 1
  while (__any_sync(0xffffffffu, orx(orx(orx(0, u0.x, par), u1.x, par), u2.x, par) & 1)) {
    rld128(u0, yp); rld128(u1, yp + 1536);
    if (a < 2) rld128(u2, yp + 3072);
    if (++n > SPIN) TIMEOUT(__LINE__)
  }
  const float s0 = asf(u0.x) + asf(u1.x) + asf(u2.x), s1 = asf(u0.y) + asf(u1.y) + asf(u2.y);
  const float s2 = asf(u0.z) + asf(u1.z) + asf(u2.z), s3 = asf(u0.w) + asf(u1.w) + asf(u2.w);
  const float k0 = self(lane & 2, s2, s0) + shx(self(lane & 2, s0, s2), 2), k1 = self(lane & 2, s3, s1) + shx(self(lane & 2, s1, s3), 2);
  float k = self(lane & 4, k1, k0) + shx(self(lane & 4, k0, k1), 4);
  k += shx(k, 8); k += shx(k, 16);
  if (lane < 8) stsf(sb + SM_YRED + ((lane & 1) * 4 + (lane & 2) + (lane >> 2)) * 16 + a * 4, k);
  nb_sync(NB_AUX, 96);
  if (a == 0) {
    const uint4 yy = lds128(sb + SM_YRED + col * 16);
    const float xn = rbf(xsel + rbf(h + rbf(rbf(asf(yy.x) + asf(yy.y) + asf(yy.z)) * sg)));
    if (L == 0) { if (lane < 16) stg32(dst, ftag(lane < 8 ? xn : xn - xsel, T & 1)); }
    else if (lane < 8) *(unsigned short*)dst = (unsigned short)(asu(xn) >> 16);
  }
}

__device__ __forceinline__ void aux_role(const Ctx& cx, const Params& P, const int a, const int lane_, const Unit& h0, const Unit& h1, const uint32_t hT) {
  int lane = lane_;
#define t (a * 32 + lane)
#define g (lane >> 2)
#define q (lane & 3)
  const int i = cx.i, j = cx.j, cta = cx.cta;
  unsigned char* const sc = (unsigned char*)P.sc;
  const int rk = 36 * i + 12 * a;
  const uint32_t o_bf = OFF(bflag) + (j * 48 + i * 3 + a) * 32 + (lane & 7) * 4;
  uint32_t T;
  {
    const int k0 = lane & 7, tt = min(lane >> 3, 2), col = (9 * j + tt) * 16;
    const unsigned char* src = (const unsigned char*)P.wqkv + ((i * 8 + k0) * 3456 + a * 1152 + col);
    const Unit b0 = unit_load(src), b1 = unit_load(src + 128 * 3456);
    T = ldg_rlx32(sc + o_bf);
    nb_arrive(NB_ORD, 352);
    STAMPIF(1, 96);
    const uint32_t d2 = tt == 2 ? (22 - 7 * a) * 512 : 3072;
    const uint32_t o = OFF(wq) + (j * 18 + (i >> 2)) * 13824 + ((i & 3) * 8 + k0) * 16 + (a * 8 + tt) * 512;
    const uint32_t r0 = unit_store(sc, b0, lane, o, o + 1536, o + d2);
    STAMPIF(1, 80);
    const uint32_t r1 = unit_store(sc, b1, lane, o + 55296, o + 55296 + 1536, o + 55296 + d2);
    T = __shfl_sync(0xffffffffu, (T >> 3) + 1, 0);
    flag_after(sc + o_bf, r0 ^ r1, 8 * T + 1, lane < 8);
    STAMPIF(1, 98);
    const Unit b2 = unit_load(src + 256 * 3456), b3 = unit_load(src + 384 * 3456);
    const bool qkv = k0 < 4;
    const int q0 = rk + k0 - 4, q1 = rk + 4 + k0;
    const Unit u0 = unit_load(qkv ? (const unsigned char*)P.wqkv + ((512 + 4 * i + k0) * 3456 + a * 1152 + col) : (const unsigned char*)P.wo + (q0 * 1152 + col));
    const Unit u1 = unit_load((const unsigned char*)P.wo + (q1 * 1152 + col));
    const uint32_t r2 = unit_store(sc, b2, lane, o + 2 * 55296, o + 2 * 55296 + 1536, o + 2 * 55296 + d2);
    const uint32_t r3 = unit_store(sc, b3, lane, o + 3 * 55296, o + 3 * 55296 + 1536, o + 3 * 55296 + d2);
    float cs[3][8];
#pragma unroll
    for (int m = 0; m < 3; m++) {
      const uint32_t* w0 = &b0.v[m].x; const uint32_t* w1 = &b1.v[m].x; const uint32_t* w2 = &b2.v[m].x; const uint32_t* w3 = &b3.v[m].x; const uint32_t* w4 = &u0.v[m].x;
#pragma unroll
      for (int e = 0; e < 4; e++) {
        const uint32_t z = qkv ? w4[e] : 0u;
        cs[m][2 * e] = (bf_lo(w0[e]) + bf_lo(w1[e])) + (bf_lo(w2[e]) + bf_lo(w3[e])) + bf_lo(z);
        cs[m][2 * e + 1] = (bf_hi(w0[e]) + bf_hi(w1[e])) + (bf_hi(w2[e]) + bf_hi(w3[e])) + bf_hi(z);
      }
    }
    flag_after(sc + o_bf, r2 ^ r3, 8 * T + 3, lane < 8);
    STAMPIF(1, 82);
#pragma unroll
    for (int st = 4; st >= 1; st >>= 1) {
      const bool up = lane & st;
#pragma unroll
      for (int m = 0; m < 3; m++)
#pragma unroll
        for (int e = 0; e < st; e++) cs[m][e] = (up ? cs[m][e + st] : cs[m][e]) + shx(up ? cs[m][e] : cs[m][e + st], st);
    }
    {
      const uint32_t oz = OFF(zpart) + j * 13824 + i * 864 + (a * 8 + tt) * 32 + k0 * 4;
      stg32(sc + oz, ftag(cs[0][0], 1)); stg32(sc + (oz + 96), ftag(cs[1][0], 1)); stg32(sc + (oz + (d2 >> 4)), ftag(cs[2][0], 1));
    }
    STAMPIF(1, 81);
    nb_sync(NB_GO, 128);
    mbar_wait(sb + BAR_FULL + LATE_WAIT * 8, 0);
    const uint32_t ow = OFF(wo) + j * 82944 + tt * 256;
    const uint32_t oa = qkv ? OFF(wq) + (j * 18 + 16 + (i >> 3)) * 13824 + (4 * (i & 7) + k0) * 16 + (a * 8 + tt) * 512 : ow + (q0 >> 4) * 2304 + (q0 & 15) * 16;
    const uint32_t ob = ow + (q1 >> 4) * 2304 + (q1 & 15) * 16;
    const uint32_t ra = unit_store(sc, u0, lane, oa, oa + (qkv ? 1536 : 768), oa + (qkv ? d2 : 1536));
    const uint32_t rb = unit_store(sc, u1, lane, ob, ob + 768, ob + 1536);
    STAMPIF(1, 113);
#pragma unroll
    for (int S = 0; S < 3; S++) stg64(sc + (OFF(ypart) + (a * 24 + g) * 4096 + cta * 32 + q * 8) + S * 32768, 0u, 0u);
    if (cta < 72 && t < 16) stg32(sc + (OFF(xsel) + (lane >> 3) * 2304 + cta * 32 + (lane & 7) * 4), (T & 1) ^ 1);
    uint4 sv, sw;
    int n = 0;
#pragma unroll 1
    while (true) {
      sv = ldg_rlx128(sc + (OFF(st0) + i * 2048 + t * 16)); sw = ldg_rlx128(sc + (OFF(st0) + i * 2048 + 1536 + lane * 16));
      if (__all_sync(0xffffffffu, ((sv.z ^ T) | (sw.z ^ T)) == 0)) break;
      if (++n > SPIN) TIMEOUT(__LINE__)
    }
    flag_after(sc + o_bf, ra ^ rb, 8 * T + 4, lane < 8);
    sts64(sb + SM_R + t * 8, sv.x, sv.y);
    sts64(sb + SM_R + 768 + lane * 8, sw.x, sw.y);
    STAMPIF(1, 94);
  }
  asm volatile("setmaxnreg.inc.sync.aligned.u32 %0;" ::"n"(REG_AUX));
  Winner wn;
  bool owner = false;
  uint32_t wd[5][3][8];
  auto load_wd = [&](uint32_t (*d)[8], const unsigned char* sk) {
#pragma unroll
    for (int S = 0; S < 3; S++) {
      const uint4 v0 = ldg_wd128(sk + S * 128), v1 = ldg_wd128(sk + S * 128 + 1152);
      d[S][0] = v0.x; d[S][1] = v1.x; d[S][2] = v0.y; d[S][3] = v1.y; d[S][4] = v0.z; d[S][5] = v1.z; d[S][6] = v0.w; d[S][7] = v1.w;
    }
  };
  auto perm_wd = [&](uint32_t (*d)[8]) {
#pragma unroll
    for (int S = 0; S < 3; S++)
#pragma unroll
      for (int u = 0; u < 4; u++) {
        const uint32_t x = d[S][2 * u], y = d[S][2 * u + 1];
        asm volatile("prmt.b32 %0, %2, %3, 0x5410;\nprmt.b32 %1, %2, %3, 0x7632;" : "=&r"(d[S][2 * u]), "=r"(d[S][2 * u + 1]) : "r"(x), "r"(y));
      }
  };
#pragma unroll
  for (int kb = 0; kb < 3; kb++)
#pragma unroll
    for (int S = 0; S < 3; S++)
#pragma unroll
      for (int e = 0; e < 8; e++) wd[kb][S][e] = 0u;
#pragma unroll 1
  for (int L = 0; L < 2; L++) {
    lane = pin(lane);
    const uint32_t o_part = OFF(zpart) + j * 13824, par = L ^ 1;
    const int pk = a * 18 + min(lane, 17);
    uint2 xu[3] = {make_uint2(0, 0), make_uint2(0, 0), make_uint2(0, 0)};
    if (L == 1) {
      if (cta < 72) finalize_row(P, wn, T, 0, cta, a, lane);
      const int gi = min(lane, 26);
      uint4 wv[12];
      {
        const int pc = gi < 24 ? gi >> 3 : gi - 24, tc = gi < 24 ? gi & 7 : 8;
        const unsigned char* se = (const unsigned char*)P.wqkv + (rk * 3456 + pc * 1152 + (9 * j + tc) * 16);
#pragma unroll
        for (int r = 0; r < 12; r++) wv[r] = ldg_nc128(se + r * 3456);
      }
      STAMPIF(1, 85);
      nb_sync(NB_AUX, 96);
      uint4 xq[3];
      {
        const unsigned char* dp = sc + (OFF(xsel) + 2304 + rk * 4);
        int n = 0;
#pragma unroll 1
        while (true) {
#pragma unroll
          for (int e = 0; e < 3; e++) xq[e] = ldg_rlx128(dp + e * 16);
          uint32_t d = orx(orx(orx(0, xq[0].x, T), xq[1].x, T), xq[2].x, T);
          if (owner) {
#pragma unroll
            for (int m = 0; m < 3; m++) xu[m] = ldg_rlx64(sc + (OFF(xsel) + t * 8) + m * 768);
            d = orx(orx(orx(d, xu[0].x, T), xu[1].x, T), xu[2].x, T);
          }
          if (__all_sync(0xffffffffu, (d & 1) == 0)) break;
          if (++n > SPIN) TIMEOUT(__LINE__)
        }
        if (t == 0) {
          sts32(sb + SM_SEL, owner ? (wn.ci & 1) * 64 + wn.rr : 0x7FFFFFFFu);
          if (wn.ci != 2 * i) mbar_arrive(sb + BAR_FIX);
          if (wn.ci != 2 * i + 1) mbar_arrive(sb + BAR_FIX + 8);
        }
        STAMPIF(1, 88);
      }
      float s[8];
#pragma unroll
      for (int e = 0; e < 8; e++) s[e] = 0.f;
#pragma unroll
      for (int r = 0; r < 12; r++) {
        const float x = asf((&xq[0].x)[r]);
        s[0] = fmaf(x, bf_lo(wv[r].x), s[0]); s[1] = fmaf(x, bf_hi(wv[r].x), s[1]);
        s[2] = fmaf(x, bf_lo(wv[r].y), s[2]); s[3] = fmaf(x, bf_hi(wv[r].y), s[3]);
        s[4] = fmaf(x, bf_lo(wv[r].z), s[4]); s[5] = fmaf(x, bf_hi(wv[r].z), s[5]);
        s[6] = fmaf(x, bf_lo(wv[r].w), s[6]); s[7] = fmaf(x, bf_hi(wv[r].w), s[7]);
      }
      sts128(sb + SM_R + a * 864 + gi * 32, asu(s[0]), asu(s[1]), asu(s[2]), asu(s[3]));
      sts128(sb + SM_R + a * 864 + gi * 32 + 16, asu(s[4]), asu(s[5]), asu(s[6]), asu(s[7]));
      nb_sync(NB_AUX, 96);
      const uint32_t ad = sb + SM_R + pk * 16;
      const uint4 u0 = lds128(ad), u1 = lds128(ad + 864), u2 = lds128(ad + 1728);
      stg128(sc + (o_part + i * 864 + pk * 16), ftag(asf(u0.x) + asf(u1.x) + asf(u2.x), par), ftag(asf(u0.y) + asf(u1.y) + asf(u2.y), par),
             ftag(asf(u0.z) + asf(u1.z) + asf(u2.z), par), ftag(asf(u0.w) + asf(u1.w) + asf(u2.w), par));
      STAMPIF(1, 86);
    }
    if (owner) {
      const uint2* u = xu;
      STAMPIF(1, 109);
      float s1 = 0.f, s2 = 0.f;
#pragma unroll
      for (int m = 0; m < 3; m++) {
        const float x0 = asf(u[m].x), x1 = asf(u[m].y);
        s1 += x0 + x1; s2 = fmaf(x0, x0, fmaf(x1, x1, s2));
        const unsigned cc = 96 * m + t - 36 * j;
        if (cc < 36u) sts32(sb + SM_X2S + cc * 4, __byte_perm(u[m].x, u[m].y, 0x7632));
      }
      wn.m = s1; wn.rstd = s2;
    }
    if (L == 0 || owner) {
      uint4 u[16];
      int n = 0;
#pragma unroll 1
      while (true) {
        uint32_t d0 = 0, d1 = 0;
#pragma unroll
        for (int e = 0; e < 16; e++) u[e] = ldg_rlx128(sc + (o_part + pk * 16) + e * 864);
        if (L == 1 && n == 0) {
#pragma unroll
          for (int s = 1; s < 32; s <<= 1) { wn.m += shx(wn.m, s); wn.rstd += shx(wn.rstd, s); }
          if (lane == 0) sts64(sb + SM_RED2 + a * 8, asu(wn.m), asu(wn.rstd));
        }
#pragma unroll
        for (int e = 0; e < 8; e++) { d0 = orx(d0, u[e].x, par); d1 = orx(d1, u[8 + e].x, par); }
        if (__all_sync(0xffffffffu, ((d0 | d1) & 1) == 0)) break;
        if (++n > SPIN) TIMEOUT(__LINE__)
      }
      STAMPIF(1, 118 + L);
      float4 z = make_float4(0.f, 0.f, 0.f, 0.f);
#pragma unroll
      for (int e = 0; e < 16; e++) { z.x += asf(u[e].x); z.y += asf(u[e].y); z.z += asf(u[e].z); z.w += asf(u[e].w); }
      const uint32_t h0 = pack_bf16(z.x, z.y), h1 = pack_bf16(z.z, z.w);
      const uint32_t l0 = pack_bf16(z.x - bf_lo(h0), z.y - bf_hi(h0)), l1 = pack_bf16(z.z - bf_lo(h1), z.w - bf_hi(h1));
      const uint32_t ad = sb + SM_BEXT + (pk >> 1) * 128 + (pk & 1) * 8;
      if (L == 0) {
        sts64(ad, h0, h1);
#pragma unroll
        for (int r = 3; r < 8; r++) sts64(ad + r * 16, 0u, 0u);
      }
      sts64(ad + 16 + L * 48, h0, h1); sts64(ad + 32 + L * 48, l0, l1);
      fence_async_smem();
      nb_sync(NB_AUX, 96);
      if (t == 0) {
        if (L == 1) {
          const uint4 ra = lds128(sb + SM_RED2);
          const uint2 rb = lds64(sb + SM_RED2 + 16);
          const float m2 = (asf(ra.x) + asf(ra.z) + asf(rb.x)) * (1.f / 576.f);
          const float rs2 = rsq(fmaxf((asf(ra.y) + asf(ra.w) + asf(rb.y)) * (1.f / 576.f) - m2 * m2, 0.f) + EPS);
          sts64(sb + SM_SEL + 8, asu(m2), asu(rs2));
          mbar_arrive(sb + BAR_FIX + (wn.ci & 1) * 8);
        } else {
          mbar_arrive(sb + BAR_FIX); mbar_arrive(sb + BAR_FIX + 8);
        }
        STAMP(83 + L * 4);
      }
    }
    lane = pin(lane);
    const unsigned char* const wsrc = (const unsigned char*)P.wd + ((ffn_c32(cta) + 2 * q) * 1152 + a * 384 + g * 16);
    if (L == 0) {
#pragma unroll
      for (int kb = 0; kb < 3; kb++) { load_wd(wd[kb], wsrc + (kb * 9216 + (kb ? pin0(wd[kb - 1][2][7]) : 0u))); perm_wd(wd[kb]); }
    }
    if (L == 0)
    {
    load_wd(wd[3], wsrc + 3 * 9216);
    load_wd(wd[4], wsrc + ((cta & 1) ? (ffn_c8(cta) - ffn_c32(cta)) * 1152 : 24 * 1152));
    perm_wd(wd[3]); perm_wd(wd[4]);
    }
    const uint32_t o_y = pin(OFF(ypart) + (a * 24 + g) * 4096 + cta * 32 + q * 8 + pin0(wd[4][2][7]));
    STAMPIF(1, 89 + L);
    if (a == 2) load_wo_a(cx, P, T, L, 1, lane);
    nb_sync(NB_FFN, 224);
    {
      const uint32_t ad = sb + R_FPART + min(lane, 19) * 16;
      const uint4 u0 = lds128(ad), u1 = lds128(ad + 320), u2 = lds128(ad + 640), u3 = lds128(ad + 960);
      const uint4 wv = lds128(sb + SM_WIN);
      const float g0 = rbf((asf(u0.x) + asf(u1.x)) + (asf(u2.x) + asf(u3.x))), g1 = rbf((asf(u0.z) + asf(u1.z)) + (asf(u2.z) + asf(u3.z)));
      const float v0 = rbf((asf(u0.y) + asf(u1.y)) + (asf(u2.y) + asf(u3.y))), v1 = rbf((asf(u0.w) + asf(u1.w)) + (asf(u2.w) + asf(u3.w)));
      const float s0 = rbf(g0 * rcp(1.f + ex2(-1.4426950408889634f * g0))), s1 = rbf(g1 * rcp(1.f + ex2(-1.4426950408889634f * g1)));
      const uint32_t act = lane < 16 + (cta & 1) * 4 ? pack_bf16(s0 * v0, s1 * v1) : 0u;
      uint32_t b[5];
#pragma unroll
      for (int kb = 0; kb < 5; kb++) b[kb] = __shfl_sync(0xffffffffu, act, 4 * kb + q);
#pragma unroll
      for (int S = 0; S < 3; S++) {
        float y[4][4];
#pragma unroll
        for (int u = 0; u < 4; u++) mma8z(y[u], wd[2][S][2 * u], wd[2][S][2 * u + 1], b[2]);
#pragma unroll
        for (int u = 0; u < 4; u++) mma16(y[u], wd[0][S][2 * u], wd[0][S][2 * u + 1], wd[1][S][2 * u], wd[1][S][2 * u + 1], b[0], b[1]);
#pragma unroll
        for (int u = 0; u < 4; u++) mma16(y[u], wd[3][S][2 * u], wd[3][S][2 * u + 1], wd[4][S][2 * u], wd[4][S][2 * u + 1], b[3], b[4]);
        const float y0 = self(lane & 2, self(lane & 1, y[3][0], y[2][0]), self(lane & 1, y[1][0], y[0][0]));
        const float y1 = self(lane & 2, self(lane & 1, y[3][2], y[2][2]), self(lane & 1, y[1][2], y[0][2]));
        stg64(sc + o_y + S * 32768, ftag(y0, par), ftag(y1, par));
      }
      if (L == 0) nb_arrive(NB_FFN2, Q1_BOTH ? 352 : 224);
      wn.r = asf(wv.x); wn.m = asf(wv.y); wn.rstd = asf(wv.z); wn.ci = wv.w >> 6; wn.rr = wv.w & 63;
    }
    STAMPIF(1, 84 + L * 8);
    owner = (wn.ci >> 1) == i;
  }
  if (cta < 72) finalize_row(P, wn, T, 1, cta, a, lane);
  STAMPIF(1, 93);
  PROF_END();
#undef t
#undef g
#undef q
}

__device__ __forceinline__ int sched_box(const uint32_t at, const int a) {
  int r = -1;
#pragma unroll
  for (int b = 0; b < 6; b++) if (((at >> (4 * b)) & 15) != 15) r = a == (int)((at >> (4 * b)) & 15) ? b : r;
  return r;
}
__host__ __device__ constexpr int sched_first(const uint32_t at) { int b = 0; while (b < 6 && ((at >> (4 * b)) & 15) != 15) b++; return b; }
__host__ __device__ constexpr int sched_last(const uint32_t at) { int b = 5; while (b >= 0 && ((at >> (4 * b)) & 15) != 15) b--; return b; }
__device__ __forceinline__ void producer_role(const Ctx& cx, const Params& P, const int lane) {
  const int i = cx.i, j = cx.j;
  if (elect_one()) asm volatile("prefetch.tensormap [%0];" ::"l"(&P.mx) : "memory");
  const uint32_t T = __shfl_sync(0xffffffffu, (ldg_rlx32(P.sc->cflag[i * 2][j * 4]) >> 3) + 1, 0);
  const unsigned char* const wq = P.sc->wq[j][0];
  nb_sync(NB_START, 288);
#pragma unroll
  for (int s = 0; s < 2 * NA0; s++) w_tma3d(sb + SM_A + s * 8192, &P.mx, (s >> 1) * 64, s & 1, i * 64, sb + BAR_FULL + (s >> 1) * 16);
#pragma unroll
  for (int h = 0; h < 6; h++) w_expect(sb + BAR_FULL + h * 8, h & 1 ? 13824 : 13824 + 16384);
  STAMP(97);
  wait_flags<48>(P.sc->bflag[j], 8 * T + 1, lane);
  fence_async_glob();
  STAMP(120);
#pragma unroll
  for (int h = 0; h < 6; h++) {
    if (h >= P_FROM && P_GAP) { const int c0 = clock(); while ((int)(clock() - c0) < P_GAP) {} }
    w_bulk(sb + SM_B + h * 13824, wq + h * 13824, 13824, sb + BAR_FULL + h * 8);
    if (!(h & 1) && h >= 2 * NA0) {
      w_tma3d(sb + SM_A + h * 8192, &P.mx, h * 32, 0, i * 64, sb + BAR_FULL + h * 8);
      w_tma3d(sb + SM_A + h * 8192 + 8192, &P.mx, h * 32, 1, i * 64, sb + BAR_FULL + h * 8);
    }
  }
  PSTAMP(0);
  asm volatile("setmaxnreg.inc.sync.aligned.u32 %0;" ::"n"(REG_AUX));
  nb_arrive(NB_GO, 128);
  mbar_wait(sb + BAR_FULL + PF_WAIT * 8, 0);
  w_prefetch((const unsigned char*)P.wd + cx.cta * 41472, 10368);
  const unsigned char* const xb = P.sc->xbuf[i * 2];
  const unsigned char* const fp = (const unsigned char*)P.sc->bflag[j] + lane * 32;
  uint32_t f0 = 0, f1 = 0;
#pragma unroll 1
  for (int L = 0; L < 2; L++) {
    if (L == 1 && !LATE_Q1) {
#pragma unroll 1
      for (int p = 0; p < 2; p++) {
        mbar_wait(sb + BAR_AEMPTY + (2 + 3 * p) * 8, 0);
        wait_flags<32>(P.sc->cflag[i * 2 + p], 8 * T + 1, lane);
        fence_async_glob();
        STAMP(104 + p);
#pragma unroll
        for (int a = 0; a < 3; a++) {
          const int s = 2 * a + p;
          w_expect(sb + BAR_AFULL + s * 8, 8192);
          w_bulk(sb + SM_A + s * 8192, xb + (p * 73728 + a * 8192), 8192, sb + BAR_AFULL + s * 8);
          PSTAMP(48 + 36 + 3 * p + a);
        }
      }
    }
#pragma unroll 1
    for (int a = 3; a < 15; a++) {
      if (a == 12) {
        load_wo_a(cx, P, T, L, 0, lane);
        if (L == 1) break;
        if (LATE_Q1) {
#pragma unroll 1
          for (int b = LATE_U0; b < 6; b++) {
            if (LATE_GGAP) { const int c0 = clock(); while ((int)(clock() - c0) < LATE_GGAP) {} }
            load_gu(P, cx.cta, 1, b, sb + BAR_GU);
          }
#pragma unroll 1
          for (int b = LATE_G0; b < 6; b++) {
            if (LATE_GGAP) { const int c0 = clock(); while ((int)(clock() - c0) < LATE_GGAP) {} }
            load_gu(P, cx.cta, 0, b, sb + BAR_GU);
          }
#pragma unroll 1
          for (int p = 0; p < 2; p++) {
            mbar_wait(sb + BAR_AEMPTY + (2 + 3 * p) * 8, 0);
            wait_flags<32>(P.sc->cflag[i * 2 + p], 8 * T + 1, lane);
            STAMP(104 + p);
          }
          fence_async_glob();
          mbar_wait(sb + BAR_ST, 0);
#pragma unroll 1
          for (int s = 0; s < 3; s++) {
            const uint32_t fb = sb + BAR_FULL + s * 16, ab = sb + BAR_AFULL + s * 16, db = sb + SM_B + s * 27648, da = sb + SM_A + s * 16384;
            mbar_wait(sb + BAR_EMPTY + s * 16, 1);
            w_expect(fb, 13824);
            w_bulk(db, wq + s * 27648, 13824, fb);
            w_expect(ab, 8192);
            w_bulk(da, xb + s * 8192, 8192, ab);
            w_expect(ab + 8, 8192);
            w_bulk(da + 8192, xb + (73728 + s * 8192), 8192, ab + 8);
            mbar_wait(sb + BAR_EMPTY + s * 16 + 8, 1);
            w_expect(fb + 8, 13824);
            w_bulk(db + 13824, wq + (s * 27648 + 13824), 13824, fb + 8);
          }
          break;
        }
      }
      const int r = (a * 11) >> 5, s = a - 3 * r;
      const uint32_t fb = sb + BAR_FULL + s * 16, da = sb + SM_A + s * 16384, db = sb + SM_B + s * 27648;
      const unsigned char* bsrc = wq + (a < 9 ? a : a < 12 ? 72 - 6 * j + s : s) * 27648;
      const unsigned char* asrc = xb + a * 8192;
      const int kc = (a < 9 ? a : j + a - 10) * 64;
      const int amode = a == 9 || a > 11 ? 0 : L == 0 ? 1 : a < 9 ? 2 : 0;
      mbar_wait(sb + BAR_EMPTY + s * 16, (r & 1) ^ 1);
      if (ST_HOLD && a == ST_HOLD) mbar_wait(sb + BAR_ST, 0);
      if (L == 0) {
        if (a == 4 || a == 8) {
          const uint32_t need = 8 * T + (a == 4 ? 3 : 4);
          if (__any_sync(0xffffffffu, (int)((f0 - need) | (f1 - need)) < 0)) wait_flags<48>(P.sc->bflag[j], need, lane);
          fence_async_glob();
          STAMP(120 + (a >> 1));
        }
        if (a == 3 || a == 7) { f0 = ldg_rlx32(fp); f1 = ldg_rlx32(fp + (lane < 16 ? 1024 : 0)); }
      }
      w_bulk(db, bsrc, 13824, fb);
      if (amode == 2) {
        w_bulk(da, asrc, 4096, fb);
        w_bulk(da + 8192, asrc + 73728, 4096, fb);
      }
      w_expect(fb, amode == 1 ? 13824 + 16384 : amode == 2 ? 13824 + 8192 : 13824);
      mbar_wait(sb + BAR_EMPTY + s * 16 + 8, (r & 1) ^ 1);
      if (amode == 1) {
        w_tma3d(da, &P.mx, kc, 0, i * 64, fb);
        w_tma3d(da + 8192, &P.mx, kc, 1, i * 64, fb);
      }
      w_bulk(db + 13824, bsrc + 13824, 13824, fb + 8);
      if (amode == 2) {
        w_bulk(da + 4096, asrc + 4096, 4096, fb + 8);
        w_bulk(da + 8192 + 4096, asrc + 73728 + 4096, 4096, fb + 8);
      }
      w_expect(fb + 8, amode == 2 ? 13824 + 8192 : 13824);
      PSTAMP(a < 12 ? L * 24 + a : 12 + a);
      if (L == 0) {
        {
          if (a >= WD_PF && a < WD_PF + 3) w_prefetch((const unsigned char*)P.wd + (cx.cta * 4 + a - WD_PF + 1) * 10368, 10368);
          if (a >= PG_0 && a < PG_0 + 6) w_prefetch((const unsigned char*)P.wg + ((a - PG_0) * 128 + cx.cta) * 6912, 6912);
        }
        if (a == 3) w_expect(sb + BAR_GU, 12 * (6144 + (cx.cta & 1) * 1536));
        {
          const int bu = sched_box(U_AT, a), bg = sched_box(G_AT, a);
          if (bu >= 0) load_gu(P, cx.cta, 1, bu, sb + BAR_GU);
          if (bg >= 0) load_gu(P, cx.cta, 0, bg, sb + BAR_GU);
          if (a == U_WIN) {
#pragma unroll 1
            for (int b = sched_first(U_AT); b <= sched_last(U_AT); b++) {
              const int c0 = clock();
              while ((int)(clock() - c0) < U_GAP) {}
              load_gu(P, cx.cta, 1, b, sb + BAR_GU);
            }
          }
          if (a == G_WIN) {
#pragma unroll 1
            for (int b = sched_first(G_AT); b <= sched_last(G_AT); b++) {
              const int c0 = clock();
              while ((int)(clock() - c0) < G_GAP) {}
              load_gu(P, cx.cta, 0, b, sb + BAR_GU);
            }
          }
        }
      }
    }
  }
}

template <bool BY_SMID>
__global__ void __launch_bounds__(384, 1) fused_kernel(const __grid_constant__ Params P) {
  extern __shared__ __align__(1024) unsigned char smem[];
  Ctx cx;
  STAMPIF(threadIdx.x == 64, 125);
  unsigned id;
  if (BY_SMID) asm volatile("mov.u32 %0, %%smid;" : "=r"(id)); else id = blockIdx.x;
  const int work = __shfl_sync(0xffffffffu, (int)P.work[min(id, 131u)], 0);
  const int warp = __shfl_sync(0xffffffffu, (int)(threadIdx.x >> 5), 0), lane = threadIdx.x & 31;
  if (work < 0) {
    if (warp == 0) {
      const int sp = -1 - work;
      if (lane == 0) { mbar_init(sb, 1); fence_async_smem(); }
      __syncwarp();
      __nanosleep(SPARE_DELAY);
#pragma unroll 1
      for (int k = 32 + sp; k < 72; k += 4) w_prefetch((const unsigned char*)P.wqkv + k * 27648, 27648);
#pragma unroll 1
      for (int k = sp; k < 24; k += 4) w_prefetch((const unsigned char*)P.wo + k * 27648, 27648);
#pragma unroll 1
      for (int k = sp; k < X_NU; k += 4) w_prefetch((const unsigned char*)P.wu + k * 27648, 27648);
      w_expect(sb, 16);
      w_bulk(sb + 128, P.wr, 16, sb);
      mbar_wait(sb, 0);
    }
    return;
  }
  cx.cta = work; cx.i = work >> 3; cx.j = work & 7;
  STAMPIF(threadIdx.x == 32, 95);
  Unit h0, h1;
  uint32_t hT = 0;
  if (warp < 8) {
    asm volatile("setmaxnreg.dec.sync.aligned.u32 %0;" ::"n"(REG_CONS));
    if (warp == 0) {
      if (elect_one()) {
        if ((uint32_t)__cvta_generic_to_shared(smem) != sb) __trap();
#pragma unroll
        for (int b = 0; b < 48; b++) mbar_init(sb + SM_BAR + b * 8, b < 34 ? 1 : b < 42 ? 4 : 8);
        fence_async_smem();
      }
      __syncwarp();
    }
    consumer_role(cx, P, smem, warp >> 2, warp & 3, lane);
  } else {
    if (warp < 11) aux_role(cx, P, warp - 8, lane, h0, h1, hT);
    else producer_role(cx, P, lane);
  }
}

int work_of_smid(int smid) {
  const int t = smid >> 1;
  if (t == 60 || t == 61) return -1 - ((t - 60) * 2 + (smid & 1));
  const int gpc = t < 32 ? t & 7 : t < 60 ? 1 + (t - 32) % 7 : 0;
  const int x = 2 * (t < 32 ? t >> 3 : t < 60 ? 4 + (t - 32) / 7 : t - 58) + (smid & 1);
  const int blk[8] = {6, 0, 2, 3, 4, 7, 5, 1}, b = blk[gpc];
  return ((b >> 1) * 4 + (x & 1) + (x >> 3) * 2) * 8 + (b & 1) * 4 + ((x >> 1) & 3);
}

typedef CUresult (*EncodeFn)(CUtensorMap*, CUtensorMapDataType, cuuint32_t, void*, const cuuint64_t*, const cuuint64_t*,
                             const cuuint32_t*, const cuuint32_t*, CUtensorMapInterleave, CUtensorMapSwizzle,
                             CUtensorMapL2promotion, CUtensorMapFloatOOBfill);

void make_map(EncodeFn enc, CUtensorMap* m, const void* base, int rank, const cuuint64_t* dims, const cuuint64_t* strides,
              const cuuint32_t* box, CUtensorMapSwizzle sw, CUtensorMapL2promotion promo = CU_TENSOR_MAP_L2_PROMOTION_L2_128B) {
  const cuuint32_t es[3] = {1, 1, 1};
  enc(m, CU_TENSOR_MAP_DATA_TYPE_BFLOAT16, rank, const_cast<void*>(base), dims, strides, box, es, CU_TENSOR_MAP_INTERLEAVE_NONE, sw,
      promo, CU_TENSOR_MAP_FLOAT_OOB_FILL_NONE);
}

}

extern "C" void kernel_launch(void* const* d_in, const int* in_sizes, int n_in, void* d_out, int out_size) {
  (void)in_sizes; (void)n_in; (void)out_size;
  static EncodeFn enc = nullptr;
  static int nsm = 0;
  static void* scr = nullptr;
  if (!enc) {
    void* f = nullptr;
    cudaDriverEntryPointQueryResult qr;
    cudaGetDriverEntryPoint("cuTensorMapEncodeTiled", &f, cudaEnableDefault, &qr);
    enc = (EncodeFn)f;
    cudaGetSymbolAddress(&scr, g_scratch);
    int dev = 0;
    cudaGetDevice(&dev);
    cudaDeviceGetAttribute(&nsm, cudaDevAttrMultiProcessorCount, dev);
    cudaFuncSetAttribute(fused_kernel<true>, cudaFuncAttributeMaxDynamicSharedMemorySize, SM_TOTAL);
    cudaFuncSetAttribute(fused_kernel<false>, cudaFuncAttributeMaxDynamicSharedMemorySize, SM_TOTAL);
  }
  Params P;
  P.x = (const __nv_bfloat16*)d_in[0];
  P.wqkv = (const __nv_bfloat16*)d_in[1];
  P.wo = (const __nv_bfloat16*)d_in[2];
  P.wr = (const __nv_bfloat16*)d_in[4];
  P.wg = (const __nv_bfloat16*)d_in[5];
  P.wu = (const __nv_bfloat16*)d_in[6];
  P.wd = (const __nv_bfloat16*)d_in[7];
  P.out = (__nv_bfloat16*)d_out;
  P.sc = (Scratch*)scr;
  for (int k = 0; k < 136; k++) P.work[k] = (signed char)(nsm == 132 ? (k < 132 ? work_of_smid(k) : -1) : (k < 128 ? k : k < 132 ? 127 - k : -1));
  {
    const cuuint64_t dims[3] = {576, 2, 1024}, str[2] = {1152, 2304};
    const cuuint32_t box[3] = {64, 1, 64};
    make_map(enc, &P.mx, P.x, 3, dims, str, box, CU_TENSOR_MAP_SWIZZLE_128B);
  }
  {
    const cuuint64_t dims[2] = {4608, 576}, str[1] = {9216};
    const cuuint32_t box[2] = {32, 96}, box8[2] = {8, 96};
    make_map(enc, &P.mg, d_in[5], 2, dims, str, box, CU_TENSOR_MAP_SWIZZLE_64B);
    make_map(enc, &P.mu, d_in[6], 2, dims, str, box, CU_TENSOR_MAP_SWIZZLE_64B);
    make_map(enc, &P.mg8, d_in[5], 2, dims, str, box8, CU_TENSOR_MAP_SWIZZLE_NONE);
    make_map(enc, &P.mu8, d_in[6], 2, dims, str, box8, CU_TENSOR_MAP_SWIZZLE_NONE);
  }
  if (nsm == 132) fused_kernel<true><<<132, 384, SM_TOTAL>>>(P);
  else fused_kernel<false><<<132, 384, SM_TOTAL>>>(P);
}
```

```cpp
#include <cuda_runtime.h>
#include <cuda.h>
#include <cuda_bf16.h>
#include <stdint.h>
#include <stddef.h>

namespace {

#define NPRE_ 4
constexpr int NPRE = NPRE_;
#define X_NU 192
#define CAND_W 8
#define HALO_V 0
#define X_DELAY 200
#define X_STEP 100
#define HOLD_C 13
#define NA0 3
#define B2_AT 0
#define LATE_WAIT 1
#define OUT_LATE 0
#define U_AT 0xFFFF75
#define G_AT 0xEEEEEB
#define PG_0 6
#define WD_PF 3
#define U_WIN 11
#define G_WIN 11
#define G_GAP 300
#define U_GAP 400
#define ST_HOLD 0
#define ST_P 1
#define LATE_Q1 1
#define LATE_U0 6
#define LATE_G0 1
#define LATE_GGAP 600
#define Q1_BOTH 1
#define A32 1
#define WD_RES 1
#define REG_AUX 200
#define REG_CONS 152
#define REG_AT 1
#define WD_TRIG 0
#define HOIST 1
#define X_TOUCH 0
#define XROW_MERGE 1
#define D_STATS 400
#define D_Y0 500
#define D_Y1 0
#define P_FROM 1
#define P_GAP 0
#define T_LATE 2
#define XPF_DELAY 600
#define B_FIRST 0
#define PF_WAIT 0
#define POLL_GAP 100
#define SPARE_DELAY 400
constexpr float EPS = 1e-5f;
constexpr int SPIN = 1 << 22;
#define TIMEOUT(line) __trap();

struct __align__(128) Scratch {
  uint32_t bflag[8][48][8];
  uint32_t cflag[32][32][8];
  uint32_t halo[32][8][672];
  uint32_t stats[32][4][8][64];
  uint32_t cand[8][32][CAND_W];
  uint32_t xcand[32][8][48];
  uint32_t ypart[72][128][8];
  uint32_t zpart[8][16][216];
  uint32_t st0[2048][4];
  uint32_t xsel[2][576];
  unsigned char wq[8][9][27648];
  unsigned char wo[8][3][27648];
  unsigned char obuf[32][73728];
  unsigned char xbuf[32][73728];
};
__device__ Scratch g_scratch;
#define OFF(f) ((uint32_t)offsetof(Scratch, f))
#define STAMPD(v, k) do {} while (0)
#define STAMPIF(c, k) do {} while (0)
#define STAMP(k) do {} while (0)

constexpr uint32_t sb = 1024;
constexpr uint32_t SM_A = 0;
constexpr uint32_t SM_B = 49152;
constexpr uint32_t SM_G = 132096;
constexpr uint32_t SM_BEXT = 224256;

constexpr uint32_t SM_WIN = 227712;
constexpr uint32_t SM_XW = 228320;
constexpr uint32_t SM_YRED = 228448;
constexpr uint32_t SM_X2S = 228576;
constexpr uint32_t SM_RED2 = 228736;
constexpr uint32_t SM_WR = 228864;
constexpr uint32_t SM_R = 229168;
constexpr uint32_t SM_BEST = 231760;
constexpr uint32_t SM_SEL = 231824;
constexpr uint32_t SM_BAR = 231840;
constexpr uint32_t SM_TOTAL = 232448;
constexpr uint32_t R_FPART = SM_R;
constexpr uint32_t BAR_FULL = SM_BAR  , BAR_AFULL = SM_BAR + 48  , BAR_WFULL = SM_BAR + 96  , BAR_ST = SM_BAR + 240, BAR_GU = SM_BAR + 248,
                   BAR_FIX = SM_BAR + 256  , BAR_AEMPTY = SM_BAR + 272  , BAR_HDONE = SM_BAR + 320  ,
                   BAR_EMPTY = SM_BAR + 336  ;
enum { NB_WG = 1  , NB_STAG = 3, NB_AUX = 4, NB_FFN2 = 5, NB_FFN = 8, NB_START = 9, NB_GO = 6, NB_ORD = 7, NB_PF = 11, NB_INIT = 12 };

struct Params {
  const __nv_bfloat16 *wqkv, *x, *wr, *wo;
  Scratch* sc;
  const __nv_bfloat16 *wd, *wg, *wu;
  __nv_bfloat16* out;
  signed char work[136];
  CUtensorMap mx, mg, mu, mg8, mu8;
};

__device__ __forceinline__ void mbar_init(uint32_t bar, int cnt) { asm volatile("mbarrier.init.shared::cta.b64 [%0], %1;" ::"r"(bar), "r"(cnt) : "memory"); }
__device__ __forceinline__ void mbar_arrive(uint32_t bar) { asm volatile("mbarrier.arrive.shared::cta.b64 _, [%0];" ::"r"(bar) : "memory"); }
__device__ __forceinline__ void mbar_wait(uint32_t bar, uint32_t par) {
  asm volatile("{\n.reg .pred p;\nLOOP:\nmbarrier.try_wait.parity.shared::cta.b64 p, [%0], %1;\n@!p bra.uni LOOP;\n}\n" ::"r"(bar), "r"(par) : "memory");
}
__device__ __forceinline__ uint32_t mbar_test(uint32_t bar, uint32_t par) {
  uint32_t ok;
  asm volatile("{\n.reg .pred p;\nmbarrier.test_wait.parity.shared::cta.b64 p, [%1], %2;\nselp.u32 %0,1,0,p;\n}" : "=r"(ok) : "r"(bar), "r"(par) : "memory");
  return ok;
}
__device__ __forceinline__ bool elect_one() {
  uint32_t ok;
  asm volatile("{\n.reg .pred p;\nelect.sync _|p, 0xffffffff;\nselp.u32 %0, 1, 0, p;\n}" : "=r"(ok));
  return ok;
}
__device__ __forceinline__ float ex2(float x) { float r; asm("ex2.approx.ftz.f32 %0, %1;" : "=f"(r) : "f"(x)); return r; }
__device__ __forceinline__ float rsq(float x) { float r; asm("rsqrt.approx.ftz.f32 %0, %1;" : "=f"(r) : "f"(x)); return r; }
__device__ __forceinline__ float rcp(float x) { float r; asm("rcp.approx.ftz.f32 %0, %1;" : "=f"(r) : "f"(x)); return r; }
__device__ __forceinline__ void w_expect(uint32_t bar, uint32_t bytes) {
  asm volatile("{\n.reg .pred p;\nelect.sync _|p, 0xffffffff;\n@p mbarrier.arrive.expect_tx.shared::cta.b64 _, [%0], %1;\n}" ::"r"(bar), "r"(bytes) : "memory");
}
__device__ __forceinline__ void w_bulk(uint32_t dst, const void* src, uint32_t bytes, uint32_t bar) {
  asm volatile("{\n.reg .pred p;\nelect.sync _|p, 0xffffffff;\n@p cp.async.bulk.shared::cluster.global.mbarrier::complete_tx::bytes [%0], [%1], %2, [%3];\n}" ::"r"(dst), "l"(src), "r"(bytes), "r"(bar) : "memory");
}
__device__ __forceinline__ void w_tma2d(uint32_t dst, const CUtensorMap* m, int c0, int c1, uint32_t bar) {
  asm volatile("{\n.reg .pred p;\nelect.sync _|p, 0xffffffff;\n@p cp.async.bulk.tensor.2d.shared::cluster.global.mbarrier::complete_tx::bytes [%0], [%1, {%3, %4}], [%2];\n}" ::"r"(dst), "l"(m), "r"(bar), "r"(c0), "r"(c1) : "memory");
}
__device__ __forceinline__ void w_tma3d(uint32_t dst, const CUtensorMap* m, int c0, int c1, int c2, uint32_t bar) {
  asm volatile("{\n.reg .pred p;\nelect.sync _|p, 0xffffffff;\n@p cp.async.bulk.tensor.3d.shared::cluster.global.mbarrier::complete_tx::bytes [%0], [%1, {%3, %4, %5}], [%2];\n}" ::"r"(dst), "l"(m), "r"(bar), "r"(c0), "r"(c1), "r"(c2) : "memory");
}
__device__ __forceinline__ void w_prefetch(const void* src, uint32_t bytes) {
  asm volatile("{\n.reg .pred p;\nelect.sync _|p, 0xffffffff;\n@p cp.async.bulk.prefetch.L2.global [%0], %1;\n}" ::"l"(src), "r"(bytes) : "memory");
}
__device__ __forceinline__ void nb_sync(int id, int n) { asm volatile("bar.sync %0, %1;" ::"r"(id), "r"(n) : "memory"); }
__device__ __forceinline__ void nb_arrive(int id, int n) { asm volatile("bar.arrive %0, %1;" ::"r"(id), "r"(n) : "memory"); }
__device__ __forceinline__ void fence_async_smem() { asm volatile("fence.proxy.async.shared::cta;" ::: "memory"); }
__device__ __forceinline__ void fence_async_glob() { asm volatile("fence.proxy.async.global;" ::: "memory"); }
__device__ __forceinline__ void flag_after(void* p, uint32_t readback, uint32_t T, bool writer) {
  asm volatile("{\n.reg .pred p;\n.reg .u32 v;\nsetp.ne.u32 p, %3, 0;\nor.b32 v, %1, %2;\nmin.u32 v, v, %2;\n@p st.relaxed.gpu.global.u32 [%0], v;\n}"
               ::"l"(p), "r"(readback), "r"(T), "r"((uint32_t)writer) : "memory");
}
__device__ __forceinline__ uint4 ldg_rlx128(const void* p) { uint4 v; asm volatile("ld.relaxed.gpu.global.v4.b32 {%0,%1,%2,%3}, [%4];" : "=r"(v.x), "=r"(v.y), "=r"(v.z), "=r"(v.w) : "l"(p) : "memory"); return v; }
__device__ __forceinline__ uint2 ldg_rlx64(const void* p) { uint2 v; asm volatile("ld.relaxed.gpu.global.v2.b32 {%0,%1}, [%2];" : "=r"(v.x), "=r"(v.y) : "l"(p) : "memory"); return v; }
__device__ __forceinline__ void rld128(uint4& v, const void* p) { asm volatile("ld.relaxed.gpu.global.v4.b32 {%0,%1,%2,%3}, [%4];" : "+r"(v.x), "+r"(v.y), "+r"(v.z), "+r"(v.w) : "l"(p) : "memory"); }
__device__ __forceinline__ uint32_t ldg_rlx32(const void* p) { uint32_t v; asm volatile("ld.relaxed.gpu.global.b32 %0, [%1];" : "=r"(v) : "l"(p) : "memory"); return v; }
#define NC_HINT ""
__device__ __forceinline__ uint4 ldg_nc128(const void* p) { uint4 v; asm volatile("ld.global.nc" NC_HINT ".v4.b32 {%0,%1,%2,%3}, [%4];" : "=r"(v.x), "=r"(v.y), "=r"(v.z), "=r"(v.w) : "l"(p)); return v; }
#define WD_HINT ".nc.L1::no_allocate"
__device__ __forceinline__ uint4 ldg_wd128(const void* p) { uint4 v; asm volatile("ld.global" WD_HINT ".v4.b32 {%0,%1,%2,%3}, [%4];" : "=r"(v.x), "=r"(v.y), "=r"(v.z), "=r"(v.w) : "l"(p)); return v; }
__device__ __forceinline__ uint32_t ldg_nc32(const void* p) { uint32_t v; asm volatile("ld.global.nc.L1::no_allocate.b32 %0, [%1];" : "=r"(v) : "l"(p)); return v; }
__device__ __forceinline__ void stg128(void* p, uint32_t a, uint32_t b, uint32_t c, uint32_t d) { asm volatile("st.relaxed.gpu.global.v4.b32 [%0], {%1,%2,%3,%4};" ::"l"(p), "r"(a), "r"(b), "r"(c), "r"(d) : "memory"); }
__device__ __forceinline__ void stg64(void* p, uint32_t a, uint32_t b) { asm volatile("st.relaxed.gpu.global.v2.b32 [%0], {%1,%2};" ::"l"(p), "r"(a), "r"(b) : "memory"); }
__device__ __forceinline__ void stg32(void* p, uint32_t a) { asm volatile("st.relaxed.gpu.global.b32 [%0], %1;" ::"l"(p), "r"(a) : "memory"); }
__device__ __forceinline__ void sts128(uint32_t a, uint32_t x, uint32_t y, uint32_t z, uint32_t w) { asm volatile("st.shared.v4.b32 [%0], {%1,%2,%3,%4};" ::"r"(a), "r"(x), "r"(y), "r"(z), "r"(w) : "memory"); }
__device__ __forceinline__ void sts64(uint32_t a, uint32_t x, uint32_t y) { asm volatile("st.shared.v2.b32 [%0], {%1,%2};" ::"r"(a), "r"(x), "r"(y) : "memory"); }
__device__ __forceinline__ void sts32(uint32_t a, uint32_t x) { asm volatile("st.shared.b32 [%0], %1;" ::"r"(a), "r"(x) : "memory"); }
__device__ __forceinline__ void stsf(uint32_t a, float x) { sts32(a, __float_as_uint(x)); }
__device__ __forceinline__ uint4 lds128(uint32_t a) { uint4 v; asm volatile("ld.shared.v4.b32 {%0,%1,%2,%3}, [%4];" : "=r"(v.x), "=r"(v.y), "=r"(v.z), "=r"(v.w) : "r"(a) : "memory"); return v; }
__device__ __forceinline__ uint2 lds64(uint32_t a) { uint2 v; asm volatile("ld.shared.v2.b32 {%0,%1}, [%2];" : "=r"(v.x), "=r"(v.y) : "r"(a) : "memory"); return v; }
__device__ __forceinline__ uint32_t lds32(uint32_t a) { uint32_t v; asm volatile("ld.shared.b32 %0, [%1];" : "=r"(v) : "r"(a) : "memory"); return v; }
__device__ __forceinline__ uint32_t pack_bf16(float lo, float hi) { uint32_t r; asm("cvt.rn.bf16x2.f32 %0, %1, %2;" : "=r"(r) : "f"(hi), "f"(lo)); return r; }
__device__ __forceinline__ float bf_lo(uint32_t w) { return __uint_as_float(w << 16); }
__device__ __forceinline__ float bf_hi(uint32_t w) { return __uint_as_float(w & 0xFFFF0000u); }
__device__ __forceinline__ float rbf(float x) { return bf_lo(pack_bf16(x, 0.f)); }
__device__ __forceinline__ float asf(uint32_t u) { return __uint_as_float(u); }
__device__ __forceinline__ uint32_t asu(float f) { return __float_as_uint(f); }
__device__ __forceinline__ float shx(float v, int m) { return __shfl_xor_sync(0xffffffffu, v, m); }
__device__ __forceinline__ uint32_t movm(uint32_t a) { uint32_t o; asm volatile("movmatrix.sync.aligned.m8n8.trans.b16 %0, %1;" : "=r"(o) : "r"(a)); return o; }
__device__ __forceinline__ void ldsm2(uint32_t& a, uint32_t& b, uint32_t addr) { asm volatile("ldmatrix.sync.aligned.m8n8.x2.shared.b16 {%0,%1}, [%2];" : "=r"(a), "=r"(b) : "r"(addr) : "memory"); }
__device__ __forceinline__ void ldsm4t(uint32_t* r, uint32_t addr) { asm volatile("ldmatrix.sync.aligned.m8n8.x4.trans.shared.b16 {%0,%1,%2,%3}, [%4];" : "=r"(r[0]), "=r"(r[1]), "=r"(r[2]), "=r"(r[3]) : "r"(addr) : "memory"); }
__device__ __forceinline__ void stsm4(uint32_t addr, uint32_t a, uint32_t b, uint32_t c, uint32_t d) { asm volatile("stmatrix.sync.aligned.m8n8.x4.shared.b16 [%0], {%1,%2,%3,%4};" ::"r"(addr), "r"(a), "r"(b), "r"(c), "r"(d) : "memory"); }
__device__ __forceinline__ void stsm2(uint32_t addr, uint32_t a, uint32_t b) { asm volatile("stmatrix.sync.aligned.m8n8.x2.shared.b16 [%0], {%1,%2};" ::"r"(addr), "r"(a), "r"(b) : "memory"); }
__device__ __forceinline__ void mma16(float* d, uint32_t a0, uint32_t a1, uint32_t a2, uint32_t a3, uint32_t b0, uint32_t b1) {
  asm volatile("mma.sync.aligned.m16n8k16.row.col.f32.bf16.bf16.f32 {%0,%1,%2,%3},{%4,%5,%6,%7},{%8,%9},{%0,%1,%2,%3};"
               : "+f"(d[0]), "+f"(d[1]), "+f"(d[2]), "+f"(d[3]) : "r"(a0), "r"(a1), "r"(a2), "r"(a3), "r"(b0), "r"(b1));
}
__device__ __forceinline__ void mma16z(float* d, uint32_t a0, uint32_t a1, uint32_t a2, uint32_t a3, uint32_t b0, uint32_t b1) {
  asm volatile("mma.sync.aligned.m16n8k16.row.col.f32.bf16.bf16.f32 {%0,%1,%2,%3},{%4,%5,%6,%7},{%8,%9},{%10,%10,%10,%10};"
               : "=f"(d[0]), "=f"(d[1]), "=f"(d[2]), "=f"(d[3]) : "r"(a0), "r"(a1), "r"(a2), "r"(a3), "r"(b0), "r"(b1), "f"(0.f));
}
__device__ __forceinline__ void mma8(float* d, uint32_t a0, uint32_t a1, uint32_t b0) {
  asm volatile("mma.sync.aligned.m16n8k8.row.col.f32.bf16.bf16.f32 {%0,%1,%2,%3},{%4,%5},{%6},{%0,%1,%2,%3};"
               : "+f"(d[0]), "+f"(d[1]), "+f"(d[2]), "+f"(d[3]) : "r"(a0), "r"(a1), "r"(b0));
}
__device__ __forceinline__ uint32_t pin(uint32_t v) { uint32_t r; asm volatile("shfl.sync.bfly.b32 %0, %1, 0, 31, 0xffffffff;" : "=r"(r) : "r"(v)); return r; }
__device__ __forceinline__ uint32_t pin0(uint32_t v) { uint32_t r; asm volatile("{\n.reg .u32 t;\nor.b32 t, %1, 1;\nbfind.shiftamt.u32 %0, t;\nshr.u32 %0, %0, 5;\n}" : "=r"(r) : "r"(v)); return r; }
__device__ __forceinline__ void mma8z(float* d, uint32_t a0, uint32_t a1, uint32_t b0) {
  asm volatile("mma.sync.aligned.m16n8k8.row.col.f32.bf16.bf16.f32 {%0,%1,%2,%3},{%4,%5},{%6},{%7,%7,%7,%7};"
               : "=f"(d[0]), "=f"(d[1]), "=f"(d[2]), "=f"(d[3]) : "r"(a0), "r"(a1), "r"(b0), "f"(0.f));
}
__device__ __forceinline__ void wg_fence() { asm volatile("wgmma.fence.sync.aligned;" ::: "memory"); }
__device__ __forceinline__ void wg_commit() { asm volatile("wgmma.commit_group.sync.aligned;" ::: "memory"); }
template <int N> __device__ __forceinline__ void wg_wait() { asm volatile("wgmma.wait_group.sync.aligned %0;" ::"n"(N) : "memory"); }
template <int N> __device__ __forceinline__ void fence_regs(float* d) {
#pragma unroll
  for (int k = 0; k < N; k++) asm volatile("" : "+f"(d[k])::"memory");
}
__host__ __device__ constexpr uint32_t DLO(uint32_t addr, uint32_t lbo) { return (addr >> 4) | ((lbo >> 4) << 16); }
__host__ __device__ constexpr uint32_t DHI(uint32_t sbo, uint32_t swz) { return (sbo >> 4) | (swz << 30); }
template <int N>
__device__ __forceinline__ void wait_flags(const void* base, const uint32_t V, const int lane) {
  const unsigned char* p = (const unsigned char*)base + lane * 32;
  const unsigned char* p2 = p + (lane < N - 32 ? 1024 : 0);
  uint32_t a0 = ldg_rlx32(p), a1 = N > 32 ? ldg_rlx32(p2) : V;
  __nanosleep(POLL_GAP);
  int n = 0;
#pragma unroll 1
  while (true) {
    const uint32_t b0 = ldg_rlx32(p), b1 = N > 32 ? ldg_rlx32(p2) : V;
    if (__all_sync(0xffffffffu, (int)((a0 - V) | (a1 - V)) >= 0)) break;
    a0 = ldg_rlx32(p); a1 = N > 32 ? ldg_rlx32(p2) : V;
    if (__all_sync(0xffffffffu, (int)((b0 - V) | (b1 - V)) >= 0)) break;
    if (++n > SPIN) TIMEOUT(__LINE__)
  }
}
__device__ __forceinline__ uint32_t ftag(float v, uint32_t par) { return (asu(v) & ~1u) | par; }
__device__ __forceinline__ uint32_t selu(uint32_t c, uint32_t a, uint32_t b) { uint32_t r; asm("{\n.reg .pred p;\nsetp.ne.u32 p, %1, 0;\nselp.b32 %0, %2, %3, p;\n}" : "=r"(r) : "r"(c), "r"(a), "r"(b)); return r; }
__device__ __forceinline__ float self(uint32_t c, float a, float b) { return asf(selu(c, asu(a), asu(b))); }
__device__ __forceinline__ uint32_t orx(uint32_t acc, uint32_t a, uint32_t ref) { uint32_t r; asm("lop3.b32 %0, %1, %2, %3, 0xF6;" : "=r"(r) : "r"(acc), "r"(a), "r"(ref)); return r; }
__device__ __forceinline__ uint32_t fkey(float r) {
  uint32_t u = asu(r);
  u = (u & 0x80000000u) ? ~u : (u | 0x80000000u);
  return (r == r) ? u : 0u;
}
__host__ __device__ constexpr int GI(int part, int t) { return t < 8 ? part * 8 + t : 24 + part; }

__device__ __forceinline__ void wgmma_ss_216(float* d, uint32_t al, uint32_t ah, uint32_t bl, uint32_t bh) {
  asm volatile("{\n.reg .b64 da, db;\nmov.b64 da, {%108, %109};\nmov.b64 db, {%110, %111};\n"
      "wgmma.mma_async.sync.aligned.m64n216k16.f32.bf16.bf16 {"
      "%0,%1,%2,%3,%4,%5,%6,%7,%8,%9,%10,%11,%12,%13,%14,%15,%16,%17,%18,%19,%20,%21,%22,%23,%24,%25,%26,"
      "%27,%28,%29,%30,%31,%32,%33,%34,%35,%36,%37,%38,%39,%40,%41,%42,%43,%44,%45,%46,%47,%48,%49,%50,%51,%52,%53,"
      "%54,%55,%56,%57,%58,%59,%60,%61,%62,%63,%64,%65,%66,%67,%68,%69,%70,%71,%72,%73,%74,%75,%76,%77,%78,%79,%80,"
      "%81,%82,%83,%84,%85,%86,%87,%88,%89,%90,%91,%92,%93,%94,%95,%96,%97,%98,%99,%100,%101,%102,%103,%104,%105,%106,%107"
      "}, da, db, 1, 1, 1, 0, 1;\n}\n"
      : "+f"(d[0]), "+f"(d[1]), "+f"(d[2]), "+f"(d[3]), "+f"(d[4]), "+f"(d[5]), "+f"(d[6]), "+f"(d[7]), "+f"(d[8]),
        "+f"(d[9]), "+f"(d[10]), "+f"(d[11]), "+f"(d[12]), "+f"(d[13]), "+f"(d[14]), "+f"(d[15]), "+f"(d[16]), "+f"(d[17]),
        "+f"(d[18]), "+f"(d[19]), "+f"(d[20]), "+f"(d[21]), "+f"(d[22]), "+f"(d[23]), "+f"(d[24]), "+f"(d[25]), "+f"(d[26]),
        "+f"(d[27]), "+f"(d[28]), "+f"(d[29]), "+f"(d[30]), "+f"(d[31]), "+f"(d[32]), "+f"(d[33]), "+f"(d[34]), "+f"(d[35]),
        "+f"(d[36]), "+f"(d[37]), "+f"(d[38]), "+f"(d[39]), "+f"(d[40]), "+f"(d[41]), "+f"(d[42]), "+f"(d[43]), "+f"(d[44]),
        "+f"(d[45]), "+f"(d[46]), "+f"(d[47]), "+f"(d[48]), "+f"(d[49]), "+f"(d[50]), "+f"(d[51]), "+f"(d[52]), "+f"(d[53]),
        "+f"(d[54]), "+f"(d[55]), "+f"(d[56]), "+f"(d[57]), "+f"(d[58]), "+f"(d[59]), "+f"(d[60]), "+f"(d[61]), "+f"(d[62]),
        "+f"(d[63]), "+f"(d[64]), "+f"(d[65]), "+f"(d[66]), "+f"(d[67]), "+f"(d[68]), "+f"(d[69]), "+f"(d[70]), "+f"(d[71]),
        "+f"(d[72]), "+f"(d[73]), "+f"(d[74]), "+f"(d[75]), "+f"(d[76]), "+f"(d[77]), "+f"(d[78]), "+f"(d[79]), "+f"(d[80]),
        "+f"(d[81]), "+f"(d[82]), "+f"(d[83]), "+f"(d[84]), "+f"(d[85]), "+f"(d[86]), "+f"(d[87]), "+f"(d[88]), "+f"(d[89]),
        "+f"(d[90]), "+f"(d[91]), "+f"(d[92]), "+f"(d[93]), "+f"(d[94]), "+f"(d[95]), "+f"(d[96]), "+f"(d[97]), "+f"(d[98]),
        "+f"(d[99]), "+f"(d[100]), "+f"(d[101]), "+f"(d[102]), "+f"(d[103]), "+f"(d[104]), "+f"(d[105]), "+f"(d[106]), "+f"(d[107])
      : "r"(al), "r"(ah), "r"(bl), "r"(bh));
}
__device__ __forceinline__ void wgmma_ss_72(float* d, uint32_t al, uint32_t ah, uint32_t bl, uint32_t bh) {
  asm volatile("{\n.reg .b64 da, db;\nmov.b64 da, {%36, %37};\nmov.b64 db, {%38, %39};\n"
      "wgmma.mma_async.sync.aligned.m64n72k16.f32.bf16.bf16 {"
      "%0,%1,%2,%3,%4,%5,%6,%7,%8,%9,%10,%11,%12,%13,%14,%15,%16,%17,%18,%19,%20,%21,%22,%23,%24,%25,%26,"
      "%27,%28,%29,%30,%31,%32,%33,%34,%35"
      "}, da, db, 1, 1, 1, 0, 1;\n}\n"
      : "+f"(d[0]), "+f"(d[1]), "+f"(d[2]), "+f"(d[3]), "+f"(d[4]), "+f"(d[5]), "+f"(d[6]), "+f"(d[7]), "+f"(d[8]),
        "+f"(d[9]), "+f"(d[10]), "+f"(d[11]), "+f"(d[12]), "+f"(d[13]), "+f"(d[14]), "+f"(d[15]), "+f"(d[16]), "+f"(d[17]),
        "+f"(d[18]), "+f"(d[19]), "+f"(d[20]), "+f"(d[21]), "+f"(d[22]), "+f"(d[23]), "+f"(d[24]), "+f"(d[25]), "+f"(d[26]),
        "+f"(d[27]), "+f"(d[28]), "+f"(d[29]), "+f"(d[30]), "+f"(d[31]), "+f"(d[32]), "+f"(d[33]), "+f"(d[34]), "+f"(d[35])
      : "r"(al), "r"(ah), "r"(bl), "r"(bh));
}
template <uint32_t BH>
__device__ __forceinline__ void wgmma_rs_216(float* d, uint32_t a0, uint32_t a1, uint32_t a2, uint32_t a3, uint32_t bl) {
  asm volatile("{\n.reg .b64 db;\nmov.b64 db, {%112, %113};\n"
      "wgmma.mma_async.sync.aligned.m64n216k16.f32.bf16.bf16 {"
      "%0,%1,%2,%3,%4,%5,%6,%7,%8,%9,%10,%11,%12,%13,%14,%15,%16,%17,%18,%19,%20,%21,%22,%23,%24,%25,%26,"
      "%27,%28,%29,%30,%31,%32,%33,%34,%35,%36,%37,%38,%39,%40,%41,%42,%43,%44,%45,%46,%47,%48,%49,%50,%51,%52,%53,"
      "%54,%55,%56,%57,%58,%59,%60,%61,%62,%63,%64,%65,%66,%67,%68,%69,%70,%71,%72,%73,%74,%75,%76,%77,%78,%79,%80,"
      "%81,%82,%83,%84,%85,%86,%87,%88,%89,%90,%91,%92,%93,%94,%95,%96,%97,%98,%99,%100,%101,%102,%103,%104,%105,%106,%107"
      "}, {%108,%109,%110,%111}, db, 1, 1, 1, 1;\n}\n"
      : "+f"(d[0]), "+f"(d[1]), "+f"(d[2]), "+f"(d[3]), "+f"(d[4]), "+f"(d[5]), "+f"(d[6]), "+f"(d[7]), "+f"(d[8]),
        "+f"(d[9]), "+f"(d[10]), "+f"(d[11]), "+f"(d[12]), "+f"(d[13]), "+f"(d[14]), "+f"(d[15]), "+f"(d[16]), "+f"(d[17]),
        "+f"(d[18]), "+f"(d[19]), "+f"(d[20]), "+f"(d[21]), "+f"(d[22]), "+f"(d[23]), "+f"(d[24]), "+f"(d[25]), "+f"(d[26]),
        "+f"(d[27]), "+f"(d[28]), "+f"(d[29]), "+f"(d[30]), "+f"(d[31]), "+f"(d[32]), "+f"(d[33]), "+f"(d[34]), "+f"(d[35]),
        "+f"(d[36]), "+f"(d[37]), "+f"(d[38]), "+f"(d[39]), "+f"(d[40]), "+f"(d[41]), "+f"(d[42]), "+f"(d[43]), "+f"(d[44]),
        "+f"(d[45]), "+f"(d[46]), "+f"(d[47]), "+f"(d[48]), "+f"(d[49]), "+f"(d[50]), "+f"(d[51]), "+f"(d[52]), "+f"(d[53]),
        "+f"(d[54]), "+f"(d[55]), "+f"(d[56]), "+f"(d[57]), "+f"(d[58]), "+f"(d[59]), "+f"(d[60]), "+f"(d[61]), "+f"(d[62]),
        "+f"(d[63]), "+f"(d[64]), "+f"(d[65]), "+f"(d[66]), "+f"(d[67]), "+f"(d[68]), "+f"(d[69]), "+f"(d[70]), "+f"(d[71]),
        "+f"(d[72]), "+f"(d[73]), "+f"(d[74]), "+f"(d[75]), "+f"(d[76]), "+f"(d[77]), "+f"(d[78]), "+f"(d[79]), "+f"(d[80]),
        "+f"(d[81]), "+f"(d[82]), "+f"(d[83]), "+f"(d[84]), "+f"(d[85]), "+f"(d[86]), "+f"(d[87]), "+f"(d[88]), "+f"(d[89]),
        "+f"(d[90]), "+f"(d[91]), "+f"(d[92]), "+f"(d[93]), "+f"(d[94]), "+f"(d[95]), "+f"(d[96]), "+f"(d[97]), "+f"(d[98]),
        "+f"(d[99]), "+f"(d[100]), "+f"(d[101]), "+f"(d[102]), "+f"(d[103]), "+f"(d[104]), "+f"(d[105]), "+f"(d[106]), "+f"(d[107])
      : "r"(a0), "r"(a1), "r"(a2), "r"(a3), "r"(bl), "n"(BH));
}

struct Ctx {
  int i, j, cta;
};
#define TSTAMP(k) do {} while (0)
#define PSTAMP(k) do {} while (0)
#define PROF_DUMP() do {} while (0)
#define PROF_END() do {} while (0)
#define GSTAMP(k) do {} while (0)
#define CSTAMP(k) STAMPIF(1, L * 40 + p * 20 + (k))

__device__ __forceinline__ int ffn_c32(int cta) { return 32 * cta; }
__device__ __forceinline__ int ffn_c8(int cta) { return 4096 + 8 * (cta >> 1); }
__device__ __forceinline__ void load_gu(const Params& P, const int cta_, const int mat, const int b, const uint32_t bar) {
  const int cta = cta_;
  w_tma2d(sb + SM_G + mat * 46080 + b * 6144, &P.mg + mat, ffn_c32(cta), b * 96, bar);
  if (cta & 1) w_tma2d(sb + SM_G + mat * 46080 + 36864 + b * 1536, &P.mg8 + mat, ffn_c8(cta), b * 96, bar);
}

struct Winner { float r, m, rstd; int ci, rr; };

__device__ __forceinline__ Winner poll_winner(const void* p, uint4 v, const uint32_t tg) {
  int n = 0;
#pragma unroll 1
  while (!__all_sync(0xffffffffu, ((v.y ^ (tg << 6)) >> 6) == 0)) {
    rld128(v, p);
    if (++n > SPIN) TIMEOUT(__LINE__)
  }
  uint32_t key = fkey(asf(v.x));
  uint32_t mx = __reduce_max_sync(0xffffffffu, key);
  int src = __ffs(__ballot_sync(0xffffffffu, key == mx)) - 1;
  Winner w;
  w.ci = src;
  w.r = asf(__shfl_sync(0xffffffffu, v.x, src));
  w.rr = (int)__shfl_sync(0xffffffffu, v.y, src) & 63;
  w.m = asf(__shfl_sync(0xffffffffu, v.z, src));
  w.rstd = asf(__shfl_sync(0xffffffffu, v.w, src));
  return w;
}

__device__ __forceinline__ float2 row_stats(const Params& P, const int r, const int lane) {
  const unsigned char* src = (const unsigned char*)P.x + (((r & ~127) + 2 * (r & 63) + ((r >> 6) & 1)) * 1152 + (lane & 15) * 16);
  uint4 v[4];
#pragma unroll
  for (int m = 0; m < 4; m++) v[m] = ldg_nc128(src + m * 256);
  uint2 v4;
  asm volatile("ld.global.nc.v2.b32 {%0,%1}, [%2];" : "=r"(v4.x), "=r"(v4.y) : "l"(src + (1024 - (lane & 15) * 8)));
  nb_arrive(NB_START, 288 + pin0(v4.x));
  const float sft = __shfl_sync(0xffffffffu, bf_lo(v[0].x), lane & 16);
  float s1 = 0.f, s2 = 0.f, s3 = 0.f;
#pragma unroll
  for (int e = 0; e < 18; e++) {
    const uint32_t u = e < 16 ? (&v[0].x)[e] : (&v4.x)[e - 16];
    const float d0 = bf_lo(u) - sft, d1 = bf_hi(u) - sft;
    s1 += d0 + d1; s2 = fmaf(d0, d0, s2); s3 = fmaf(d1, d1, s3);
  }
  s2 += s3;
#pragma unroll
  for (int o = 1; o < 16; o <<= 1) { s1 += shx(s1, o); s2 += shx(s2, o); }
  s1 *= (1.f / 576.f);
  return make_float2(s1 + sft, rsq(fmaxf(s2 * (1.f / 576.f) - s1 * s1, 0.f) + EPS));
}

struct Unit { uint4 v[3]; };
__device__ __forceinline__ Unit unit_load(const unsigned char* src) {
  Unit u;
#pragma unroll
  for (int m = 0; m < 3; m++) u.v[m] = ldg_nc128(src + m * 48);
  return u;
}
__device__ __forceinline__ uint32_t unit_store(unsigned char* sc, const Unit& u, const int lane, const uint32_t o0, const uint32_t o1, const uint32_t o2) {
  stg128(sc + o0, u.v[0].x, u.v[0].y, u.v[0].z, u.v[0].w);
  stg128(sc + o1, u.v[1].x, u.v[1].y, u.v[1].z, u.v[1].w);
  stg128(sc + o2, u.v[2].x, u.v[2].y, u.v[2].z, u.v[2].w);
  return ldg_rlx32(sc + ((lane & 3) == 0 ? o0 : (lane & 3) == 1 ? o1 : o2));
}

__device__ __forceinline__ void store_rows(const uint32_t stg, unsigned char* obase, const int skip, const int lane) {
#pragma unroll
  for (int m = 0; m < 5; m++) {
    const int e = lane + 32 * m, r = (e * 57) >> 9;
    const uint4 v = lds128(stg + min(e, 143) * 16);
    if (e < 144 && r != skip) *(uint4*)(obase + (r * (2304 - 144) + e * 16)) = v;
  }
}

__device__ __forceinline__ void consumer_role(const Ctx& cx, const Params& P, const unsigned char* smem, const int p, const int w, const int lane_) {
  int lane = lane_;
#define g (lane >> 2)
#define q (lane & 3)
#define first_lane (lane == 0)
  const int i = cx.i, j = cx.j, ip = i * 2 + p;
  unsigned char* const sc = (unsigned char*)P.sc;
  float m_lo = 0.f, m_hi = 0.f, rs_lo = 0.f, rs_hi = 0.f;
  nb_sync(NB_ORD, T_LATE == 2 ? 384 : 352);
  uint32_t T = ldg_rlx32(P.sc->cflag[ip][j * 4 + w]);
  if (X_DELAY && T_LATE != 3) { const int c0 = clock(); while ((int)(clock() - c0) < X_DELAY + (p * 4 + w) * X_STEP) {} }
  {
    const int t = min(w * 32 + lane, 95);
    uint32_t u0 = 0, u1 = 0, u2 = 0, u = 0;
    if (p == 0) {
      u0 = ldg_nc32((const uint32_t*)P.wr + t); u1 = ldg_nc32((const uint32_t*)P.wr + 96 + t); u2 = ldg_nc32((const uint32_t*)P.wr + 192 + t);
      u = ldg_nc32((const uint32_t*)P.wr + 36 * j + min(t, 35));
    }
    const int r = cx.cta * 16 + (p * 4 + w) * 2 + (lane >> 4);
    const float2 st = row_stats(P, r, lane);
    T = __shfl_sync(0xffffffffu, (T >> 3) + 1, 0);
    if ((lane & 15) == 0) stg128(sc + (OFF(st0) + r * 16), asu(st.x), asu(st.y), T, 0u);
    STAMPIF(1, 111);
    if (p == 0) {
      float s = (bf_lo(u0) + bf_hi(u0)) + (bf_lo(u1) + bf_hi(u1)) + (bf_lo(u2) + bf_hi(u2));
#pragma unroll
      for (int o = 1; o < 32; o <<= 1) s += shx(s, o);
      stsf(sb + SM_WR + 288 + w * 4, s);
      sts64(sb + SM_WR + min(t, 35) * 8, u << 16, u & 0xFFFF0000u);
    }
  }
#pragma unroll 1
  for (int L = 0; L < 2; L++) {
    lane = pin(lane);
    const uint32_t tg = 2 * T + L;
    float c_lo = 0.f, c_hi = 0.f;
    bool sel_lo = false, sel_hi = false;
    float acc[108];
#pragma unroll
    for (int k = 0; k < 108; k++) acc[k] = 0.f;
    fence_regs<108>(acc);
    {
      const uint32_t ah = L == 0 ? DHI(1024, 1) : DHI(128, 0);
      const uint32_t astep = L == 0 ? 2 : 128;
      const uint32_t a0 = (L == 0 ? DLO(sb + SM_A, 16) : DLO(sb + SM_A, 1024)) + p * 512;
      constexpr uint32_t bh = DHI(512, 0);
      if (L == 1) {
        const float ul = 1.f + rs_lo, uh = 1.f + rs_hi;
        const float vl = fmaxf(rcp(rs_lo * rs_lo) - EPS, 0.f), vh = fmaxf(rcp(rs_hi * rs_hi) - EPS, 0.f);
        c_lo = ul * rsq(vl * ul * ul + EPS);
        c_hi = uh * rsq(vh * uh * uh + EPS);
      }
      if (L == 1) mbar_wait(sb + BAR_AFULL + p * 8, 0);
      mbar_wait(sb + BAR_FULL, 0);
      if (L == 1 && (p == 1 || Q1_BOTH)) nb_sync(NB_FFN2, Q1_BOTH ? 352 : 224);
      CSTAMP(0); GSTAMP(120 + 2 * L);
      uint32_t e0 = 0, e1 = 0;
      bool prepped = false, gone = false;
      auto prep_ext = [&]() {
        const int row = p * 64 + w * 16 + g;
        if (L == 0) {
          const uint2 u0 = lds64(sb + SM_R + row * 8), u1 = lds64(sb + SM_R + row * 8 + 64);
          m_lo = asf(u0.x); c_lo = asf(u0.y); m_hi = asf(u1.x); c_hi = asf(u1.y);
        } else {
          const uint4 sv = lds128(sb + SM_SEL);
          sel_lo = (int)sv.x == row; sel_hi = (int)sv.x == row + 8;
          if (sel_lo) { m_lo = asf(sv.z); c_lo = asf(sv.w); }
          if (sel_hi) { m_hi = asf(sv.z); c_hi = asf(sv.w); }
        }
        const float hl = rbf(-m_lo), hh = rbf(-m_hi);
        const uint32_t em = selu(lane & 1, 0x0000FFFFu, 0xFFFFFFFFu);
        e0 = selu(lane & 2, selu(sel_lo && !(lane & 1), 0x3F803F80u, 0u), pack_bf16(hl, -m_lo - hl) & em);
        e1 = selu(lane & 2, selu(sel_hi && !(lane & 1), 0x3F803F80u, 0u), pack_bf16(hh, -m_hi - hh) & em);
      };
      bool pend = false;
#pragma unroll 1
      for (int r = 0; r < 3; r++) {
#pragma unroll
        for (int h = 0; h < 6; h++) {
          const uint32_t al = a0 + (h >> 1) * 1024 + (h & 1) * 2 * astep, bl = DLO(sb + SM_B, 128) + h * 864;
          const uint32_t nb = sb + BAR_FULL + ((h + 1) % 6) * 8, np = (r + (h == 5)) & 1;
          TSTAMP((6 * r + h) * 2);
          wg_fence();
          wgmma_ss_216(acc, al, ah, bl, bh);
          wgmma_ss_216(acc, al + astep, ah, bl + 16, bh);
          wg_commit();
          if (h == 5 && r == 2) break;
          const uint32_t ok = mbar_test(nb, np);
          if ((h == 1 || h == 3) && r == 0 && L == 1) mbar_wait(sb + BAR_AFULL + (h + 1 + p) * 8, 0);
          if (h == 0 && r == 1 && L == 0) {
          if (lane < 16) stg128(sc + (OFF(stats) + (ip * 4 + w) * 2048 + j * 256 + lane * 16), 0u, 0u, 0u, 0u);
          if (w == 3 && i < 15 && lane < 28) {
#pragma unroll
            for (int e = 0; e < 6; e++) stg128(sc + (OFF(halo) + ((ip + 2) * 8 + j) * 2688 + lane * 16) + e * 448, 0u, 0u, 0u, 0u);
          }
          if (w == 0 && lane < 2) stg128(sc + (OFF(cand) + (j * 32 + ip) * (CAND_W * 4) + lane * 16), 0u, 0u, 0u, 0u);
          }
          wg_wait<1>();
          if (first_lane && pend) mbar_arrive(sb + BAR_EMPTY + ((h + 5) % 6) * 8);
          pend = true;
          const bool hold = h == HOLD_C % 6 && r == HOLD_C / 6 && p == 1;
          if (hold || (!ok && !mbar_test(nb, np))) {
            wg_wait<0>();
            if (first_lane) mbar_arrive(sb + BAR_EMPTY + h * 8);
            pend = false;
            TSTAMP((6 * r + h) * 2 + 1);
            mbar_wait(nb, np);
            if (hold) {
              if (mbar_test(sb + BAR_FIX + 8, L)) { prep_ext(); prepped = true; }
              nb_sync(NB_STAG, 256);
            }
          }
        }
      }
      if (!prepped) {
        if (p == 0 && !gone && !mbar_test(sb + BAR_FIX, L)) { nb_arrive(NB_STAG, 256); gone = true; }
        mbar_wait(sb + BAR_FIX + p * 8, L);
        prep_ext();
      }
      wg_fence();
      wgmma_rs_216<DHI(128, 0)>(acc, e0, e1, 0u, 0u, DLO(sb + SM_BEXT, 0));
      wg_commit();
      if (p == 0 && !gone) nb_arrive(NB_STAG, 256);
      wg_wait<2>();
      if (first_lane && pend) mbar_arrive(sb + BAR_EMPTY + 32);
    }
    lane = pin(lane);
    const uint32_t fragoff = ip * 73728 + (9 * j) * 1024 + w * 256 + lane * 4;
    const uint32_t rboff = (min(lane, 17) >> 1) * 1024 + (lane < 18 ? lane & 1 : 0) * 128;
    const uint32_t hl16 = (lane < 4 ? lane : lane - 4) * 16;
    const uint32_t o_halo = pin(OFF(halo) + ((ip + (w == 3 ? 2 : 0)) * 8 + j) * 2688 + hl16);
    const uint32_t o_o = pin(OFF(obuf) + fragoff);
    nb_sync(NB_WG + p, 128);
    if ((o_halo | o_o) == 0xFFFFFFFFu) __trap();
    wg_wait<0>();
    fence_regs<108>(acc);
    if (first_lane) mbar_arrive(sb + BAR_EMPTY + 40);
    CSTAMP(1); GSTAMP(121 + 2 * L);
    {
      uint32_t Kh[9], Vh[9], Kl[9], Vl[9], Kx[9], Vx[9], Ql[9], Qh[9];
#pragma unroll
      for (int t = 0; t < 9; t++) {
        Kh[t] = pack_bf16(acc[4 * GI(1, t) + 2] * c_hi, acc[4 * GI(1, t) + 3] * c_hi);
        Vh[t] = pack_bf16(acc[4 * GI(2, t) + 2] * c_hi, acc[4 * GI(2, t) + 3] * c_hi);
        Ql[t] = pack_bf16(acc[4 * GI(0, t)], acc[4 * GI(0, t) + 1]);
        Qh[t] = pack_bf16(acc[4 * GI(0, t) + 2], acc[4 * GI(0, t) + 3]);
      }
      const uint32_t hbuf = sb + SM_A + p * 8192 + w * 2688 + hl16;
      if (w < 3) {
        if (lane >= 4) {
#pragma unroll
          for (int e = 0; e < 4; e++) sts128(hbuf + e * 448, Kh[2 * e], Kh[2 * e + 1], Vh[e], tg);
          sts128(hbuf + 4 * 448, Kh[8], Vh[4], Vh[5], tg);
          sts128(hbuf + 5 * 448, Vh[6], Vh[7], Vh[8], tg);
        }
      } else if (i < 15 && lane >= 4) {
#pragma unroll
        for (int e = 0; e < 4; e++) stg128(sc + o_halo + e * 448, Kh[2 * e], Kh[2 * e + 1], Vh[e], tg);
        stg128(sc + o_halo + 4 * 448, Kh[8], Vh[4], Vh[5], tg);
        stg128(sc + o_halo + 5 * 448, Vh[6], Vh[7], Vh[8], tg);
      }
      nb_sync(NB_WG + p, 128);
#pragma unroll
      for (int t = 0; t < 9; t++) {
        Kl[t] = pack_bf16(acc[4 * GI(1, t)] * c_lo, acc[4 * GI(1, t) + 1] * c_lo);
      }
#pragma unroll
      for (int t = 0; t < HALO_V; t++) Vl[t] = pack_bf16(acc[4 * GI(2, t)] * c_lo, acc[4 * GI(2, t) + 1] * c_lo);
      uint32_t dep = (Kl[0] ^ Kl[1] ^ Kl[2]) | (Kl[3] ^ Kl[4] ^ Kl[5]) | (Kl[6] ^ Kl[7] ^ Kl[8]);
#pragma unroll
      for (int t = 0; t < HALO_V; t += 3) dep |= Vl[t] ^ Vl[t + 1] ^ Vl[t + 2];
      const unsigned char* hp = (w > 0 ? smem + (hbuf - 2688 - sb) : sc + o_halo) + pin0(dep);
      uint4 hv[6];
#pragma unroll
      for (int e = 0; e < 6; e++)
        asm volatile("ld.relaxed.gpu.v4.b32 {%0,%1,%2,%3}, [%4];" : "=r"(hv[e].x), "=r"(hv[e].y), "=r"(hv[e].z), "=r"(hv[e].w) : "l"(hp + e * 448) : "memory");
      CSTAMP(2);
#pragma unroll
      for (int t = 0; t < 9; t++) {
        if (t >= HALO_V) Vl[t] = pack_bf16(acc[4 * GI(2, t)] * c_lo, acc[4 * GI(2, t) + 1] * c_lo);
        Vl[t] = movm(Vl[t]);
        Vh[t] = movm(Vh[t]);
      }
      uint32_t qa[4][2], qb[4][2];
      float s1[4][4], s2[4][4];
#pragma unroll
      for (int h = 0; h < 4; h++) {
        qa[h][0] = q >= h ? Ql[2 * h] : 0u; qa[h][1] = q >= h ? Qh[2 * h] : 0u;
        qb[h][0] = q <= h ? Ql[2 * h + 2] : 0u; qb[h][1] = q <= h ? Qh[2 * h + 2] : 0u;
      }
      const bool first = (i == 0 && w == 0);
      if (w == 0 && i > 0) {
        int n = 0;
#pragma unroll 1
        while (__any_sync(0xffffffffu, (orx(orx(orx(0, hv[0].w, tg), hv[1].w, tg), hv[2].w, tg) | orx(orx(orx(0, hv[3].w, tg), hv[4].w, tg), hv[5].w, tg)) != 0)) {
#pragma unroll
          for (int e = 0; e < 6; e++) rld128(hv[e], sc + o_halo + e * 448);
          if (++n > SPIN) TIMEOUT(__LINE__)
        }
      }
#pragma unroll
      for (int e = 0; e < 4; e++) { Kx[2 * e] = hv[e].x; Kx[2 * e + 1] = hv[e].y; Vx[e] = hv[e].z; }
      Kx[8] = hv[4].x; Vx[4] = hv[4].y; Vx[5] = hv[4].z; Vx[6] = hv[5].x; Vx[7] = hv[5].y; Vx[8] = hv[5].z;
      CSTAMP(3);
#pragma unroll
      for (int t = 0; t < 9; t++) Vx[t] = movm(Vx[t]);
#pragma unroll
      for (int h = 0; h < 4; h++) { mma8z(s1[h], qb[h][0], qb[h][1], Kl[2 * h + 2]); mma8z(s2[h], qb[h][0], qb[h][1], Kh[2 * h + 2]); }
#pragma unroll
      for (int h = 0; h < 4; h++) {
        mma16(s1[h], qa[h][0], qa[h][1], Ql[2 * h + 1], Qh[2 * h + 1], Kl[2 * h], Kl[2 * h + 1]);
        mma16(s2[h], qa[h][0], qa[h][1], Ql[2 * h + 1], Qh[2 * h + 1], Kh[2 * h], Kh[2 * h + 1]);
      }
      float s0[4][4];
#pragma unroll
      for (int h = 0; h < 4; h++) mma8z(s0[h], qb[h][0], qb[h][1], Kx[2 * h + 2]);
#pragma unroll
      for (int h = 0; h < 4; h++) mma16(s0[h], qa[h][0], qa[h][1], Ql[2 * h + 1], Qh[2 * h + 1], Kx[2 * h], Kx[2 * h + 1]);
      const bool pv0 = 2 * q > g, pv1 = 2 * q + 1 > g;
      const uint32_t PM = (pv0 ? 0x0000FFFFu : 0u) | (pv1 ? 0xFFFF0000u : 0u);
      const float kS = 0.23570226039551584f * 1.4426950408889634f;
      const float sc_lo = c_lo * kS, sc_hi = c_hi * kS;
      float sl[4][2], sh[4][2], ml[4], mh[4];
#pragma unroll
      for (int h = 0; h < 4; h++) {
        sh[h][0] = pv0 ? s1[h][2] : s2[h][2];
        sh[h][1] = pv1 ? s1[h][3] : s2[h][3];
        mh[h] = fmaxf(sh[h][0], sh[h][1]);
        sl[h][0] = pv0 ? (first ? -INFINITY : s0[h][0]) : s1[h][0];
        sl[h][1] = pv1 ? (first ? -INFINITY : s0[h][1]) : s1[h][1];
        ml[h] = fmaxf(sl[h][0], sl[h][1]);
      }
#pragma unroll
      for (int s = 1; s <= 2; s <<= 1) {
        float tl[4], th[4];
#pragma unroll
        for (int h = 0; h < 4; h++) { th[h] = shx(mh[h], s); tl[h] = shx(ml[h], s); }
#pragma unroll
        for (int h = 0; h < 4; h++) { mh[h] = fmaxf(mh[h], th[h]); ml[h] = fmaxf(ml[h], tl[h]); }
      }
      float o[4][3][4], den[4][4];
      uint32_t px[4];
#pragma unroll
      for (int h = 0; h < 4; h++) {
        const float bl = -ml[h] * sc_lo, bh = -mh[h] * sc_hi;
        const uint32_t pl = pack_bf16(ex2(fmaf(sl[h][0], sc_lo, bl)), ex2(fmaf(sl[h][1], sc_lo, bl)));
        const uint32_t ph = pack_bf16(ex2(fmaf(sh[h][0], sc_hi, bh)), ex2(fmaf(sh[h][1], sc_hi, bh)));
        mma8z(den[h], pl, ph, 0x3F803F80u);
        px[h] = pl & PM;
#pragma unroll
        for (int u = 0; u < 3; u++) mma16z(o[h][u], pl & ~PM, ph & PM, 0u, ph & ~PM, Vl[2 * h + u], Vh[2 * h + u]);
      }
#pragma unroll
      for (int h = 0; h < 4; h++)
#pragma unroll
        for (int u = 0; u < 3; u++) mma8(o[h][u], px[h], 0u, Vx[2 * h + u]);
      float il[4], ih[4];
#pragma unroll
      for (int h = 0; h < 4; h++) { il[h] = rcp(den[h][0]); ih[h] = rcp(den[h][2]); }
#pragma unroll
      for (int t = 0; t < 9; t++) {
        const int h = t == 8 ? 3 : t >> 1, u = t == 8 ? 2 : t & 1;
        float v0 = o[h][u][0], v1 = o[h][u][1], v2 = o[h][u][2], v3 = o[h][u][3], kl = il[h], kh = ih[h];
        if (u == 0 && h > 0 && q < h) {
          v0 = o[h - 1][2][0]; v1 = o[h - 1][2][1]; v2 = o[h - 1][2][2]; v3 = o[h - 1][2][3]; kl = il[h - 1]; kh = ih[h - 1];
        }
        stg32(sc + o_o + t * 1024, pack_bf16(v0 * kl, v1 * kl));
        stg32(sc + o_o + t * 1024 + 128, pack_bf16(v2 * kh, v3 * kh));
      }
    }
    CSTAMP(4);
    const uint32_t rbo = ldg_rlx32(sc + (o_o + rboff));
    lane = pin(lane);
    const uint32_t o_x = o_o + (OFF(xbuf) - OFF(obuf)), o_xrb = o_x + rboff;
    const uint32_t o_cf = OFF(cflag) + (ip * 32 + j * 4 + w) * 32 + lane * 4;
    if (L == 1 && first_lane) mbar_arrive(sb + BAR_HDONE + p * 8);
    flag_after(sc + o_cf, rbo, 8 * T + 2 * L, lane < 8);
    STAMPD(asf(rbo), L * 40 + p * 20 + 13);
    uint32_t resid[18];
    mbar_wait(sb + BAR_FULL + 16, 1); mbar_wait(sb + BAR_FULL + 32, 1);
    if (L == 0) {
      const uint32_t ra = sb + SM_A + (2 + p) * 8192 + (w * 16 + (lane & 15)) * 128;
#pragma unroll
      for (int t = 0; t < 9; t++) ldsm2(resid[2 * t], resid[2 * t + 1], ra + ((j + t) >> 3) * 16384 + ((((j + t) ^ lane) & 7) << 4));
      if (first_lane) mbar_arrive(sb + BAR_HDONE + p * 8 + pin0(resid[17]));
    } else {
#pragma unroll
      for (int t = 0; t < 9; t++) { resid[2 * t] = ldg_rlx32(sc + o_x + t * 1024); resid[2 * t + 1] = ldg_rlx32(sc + o_x + t * 1024 + 128); }
    }
    const uint32_t o_st = OFF(stats) + (ip * 4 + w) * 2048;
    const uint32_t o_stw = pin(o_st + j * 256 + (g + 8 * (q & 1)) * 16), o_str = pin(o_st + q * 512 + g * 16);
    const uint32_t o_cand = pin(OFF(cand) + (j * 32 + ip) * (CAND_W * 4) + q * 16);
    const uint32_t o_xc = pin(OFF(xcand) + (ip * 8 + j) * 192 + q * 16);
    float accw[36];
    float wr[18];
#pragma unroll
    for (int t = 0; t < 9; t++) { const uint2 u = lds64(sb + SM_WR + t * 32 + q * 8); wr[2 * t] = asf(u.x); wr[2 * t + 1] = asf(u.y); }
    const uint4 ws4 = lds128(sb + SM_WR + 288);
    const float wsum = asf(pin(asu(asf(ws4.x) + asf(ws4.y) + asf(ws4.z))));
    {
      float ul = 1.f, uh = 1.f, vl = 0.f, vh = 0.f;
      if (L == 1) {
        ul += rs_lo; uh += rs_hi; vl = -m_lo * rs_lo; vh = -m_hi * rs_hi;
        if (sel_lo || sel_hi) {
#pragma unroll
          for (int t = 0; t < 9; t++) {
            const uint32_t z = lds32(sb + SM_X2S + t * 16 + q * 4);
            if (sel_hi) resid[2 * t + 1] = z; else resid[2 * t] = z;
          }
          if (sel_hi) { uh = 1.f; vh = 0.f; } else { ul = 1.f; vl = 0.f; }
        }
        __syncwarp();
      }
#pragma unroll
      for (int t = 0; t < 9; t++) {
        accw[4 * t] = fmaf(bf_lo(resid[2 * t]), ul, vl); accw[4 * t + 1] = fmaf(bf_hi(resid[2 * t]), ul, vl);
        accw[4 * t + 2] = fmaf(bf_lo(resid[2 * t + 1]), uh, vh); accw[4 * t + 3] = fmaf(bf_hi(resid[2 * t + 1]), uh, vh);
      }
    }
    fence_regs<36>(accw);
    mbar_wait(sb + BAR_FULL, 1); mbar_wait(sb + BAR_FULL + 8, 1); mbar_wait(sb + BAR_FULL + 24, 1); mbar_wait(sb + BAR_FULL + 40, 1);
    {
      uint32_t wf = sb + BAR_WFULL + p * 72;
      uint32_t bl = DLO(sb + SM_B, 128);
      uint32_t half = p;
      mbar_wait(wf, L);
      CSTAMP(5);
#pragma unroll 1
      for (int c3 = 0; c3 < 3; c3++) {
        const uint32_t al = DLO(sb + SM_A, 1024) + half * 512;
        const uint32_t ae = sb + BAR_AEMPTY + half * 24;
#pragma unroll
        for (int cc = 0; cc < 3; cc++) {
          TSTAMP(36 + (c3 * 3 + cc) * 2);
          wg_fence();
          wgmma_ss_72(accw, al + cc * 1024, DHI(128, 0), bl + cc * 576, DHI(256, 0));
          wgmma_ss_72(accw, al + cc * 1024 + 128, DHI(128, 0), bl + cc * 576 + 144, DHI(256, 0));
          const uint32_t ok = mbar_test(wf + cc * 8 + 8, L);
          wgmma_ss_72(accw, al + cc * 1024 + 256, DHI(128, 0), bl + cc * 576 + 288, DHI(256, 0));
          wgmma_ss_72(accw, al + cc * 1024 + 384, DHI(128, 0), bl + cc * 576 + 432, DHI(256, 0));
          wg_commit();
          wg_wait<1>();
          if (cc > 0) { if (first_lane) { mbar_arrive(ae + cc * 8 - 8); if (cc == 2) mbar_arrive(sb + BAR_EMPTY + c3 * 16); } }
          else if (first_lane && c3 > 0) { mbar_arrive(sb + BAR_AEMPTY + 40 - half * 24); mbar_arrive(sb + BAR_EMPTY + c3 * 16 - 8); }
          if (!ok && (cc < 2 || c3 < 2)) mbar_wait(wf + cc * 8 + 8, L);
        }
        wf += 24; bl += 1728; half ^= 1;
      }
    }
    wg_wait<0>();
    fence_regs<36>(accw);
    if (first_lane) { mbar_arrive(sb + BAR_AEMPTY + (2 + 3 * p) * 8); mbar_arrive(sb + BAR_EMPTY + 40); }
    CSTAMP(6);
    uint32_t xw[18];
    uint32_t rb = 0;
    if (L == 0 && p == 0) {
#pragma unroll
      for (int t = 0; t < 9; t++) {
        stg32(sc + o_x + t * 1024, pack_bf16(accw[4 * t], accw[4 * t + 1]));
        stg32(sc + o_x + t * 1024 + 128, pack_bf16(accw[4 * t + 2], accw[4 * t + 3]));
      }
      rb = ldg_rlx32(sc + o_xrb);
      fence_regs<36>(accw);
    }
    {
      float a0[2] = {0.f, 0.f}, a1[2] = {0.f, 0.f}, a2[2] = {0.f, 0.f}, b0[2] = {0.f, 0.f}, b1[2] = {0.f, 0.f}, b2[2] = {0.f, 0.f};
#pragma unroll
      for (int t = 0; t < 9; t++) {
#pragma unroll
        for (int e = 0; e < 2; e++) {
          const float x = accw[4 * t + e], y = accw[4 * t + 2 + e];
          a0[e] += x; a1[e] = fmaf(x, x, a1[e]); a2[e] = fmaf(x, wr[2 * t + e], a2[e]);
          b0[e] += y; b1[e] = fmaf(y, y, b1[e]); b2[e] = fmaf(y, wr[2 * t + e], b2[e]);
        }
      }
      const bool od = q & 1;
      const float A0 = a0[0] + a0[1], A1 = a1[0] + a1[1], A2 = a2[0] + a2[1], B0 = b0[0] + b0[1], B1 = b1[0] + b1[1], B2 = b2[0] + b2[1];
      float k0 = od ? B0 : A0, k1 = od ? B1 : A1, k2 = od ? B2 : A2;
      k0 += shx(od ? A0 : B0, 1); k1 += shx(od ? A1 : B1, 1); k2 += shx(od ? A2 : B2, 1);
      k0 += shx(k0, 2); k1 += shx(k1, 2); k2 += shx(k2, 2);
      if (q < 2) stg128(sc + o_stw, asu(k0), asu(k1), asu(k2), tg);
      STAMPD(k0, L * 40 + p * 20 + 14);
    }
#pragma unroll
    for (int t = 0; t < 9; t++) {
      xw[2 * t] = pack_bf16(accw[4 * t], accw[4 * t + 1]);
      xw[2 * t + 1] = pack_bf16(accw[4 * t + 2], accw[4 * t + 3]);
    }
    float r_lo, r_hi;
    {
      if (D_STATS) { const int c0 = clock(); while ((int)(clock() - c0) < D_STATS) {} }
      uint4 u0 = ldg_rlx128(sc + o_str), u1 = ldg_rlx128(sc + o_str + 256), u2 = ldg_rlx128(sc + o_str + 128), u3 = ldg_rlx128(sc + o_str + 384);
      flag_after(sc + o_cf, rb, 8 * T + 1, lane < 8 && L == 0 && p == 0);
      STAMPD(asf(u3.w), L * 40 + p * 20 + 15);
      int n = 0;
#pragma unroll 1
      while (__any_sync(0xffffffffu, orx(orx(orx(orx(0, u0.w, tg), u1.w, tg), u2.w, tg), u3.w, tg) != 0)) {
        rld128(u0, sc + o_str); rld128(u1, sc + o_str + 256); rld128(u2, sc + o_str + 128); rld128(u3, sc + o_str + 384);
        if (++n > SPIN) TIMEOUT(__LINE__)
      }
      float a0 = asf(u0.x) + asf(u1.x), a1 = asf(u0.y) + asf(u1.y), a2 = asf(u0.z) + asf(u1.z);
      float b0 = asf(u2.x) + asf(u3.x), b1 = asf(u2.y) + asf(u3.y), b2 = asf(u2.z) + asf(u3.z);
#pragma unroll
      for (int s = 1; s <= 2; s <<= 1) {
        const float t0 = shx(a0, s), t1 = shx(a1, s), t2 = shx(a2, s), t3 = shx(b0, s), t4 = shx(b1, s), t5 = shx(b2, s);
        a0 += t0; a1 += t1; a2 += t2; b0 += t3; b1 += t4; b2 += t5;
      }
      m_lo = a0 * (1.f / 576.f); m_hi = b0 * (1.f / 576.f);
      rs_lo = rsq(fmaxf(a1 * (1.f / 576.f) - m_lo * m_lo, 0.f) + EPS);
      rs_hi = rsq(fmaxf(b1 * (1.f / 576.f) - m_hi * m_hi, 0.f) + EPS);
      r_lo = (a2 - m_lo * wsum) * rs_lo; r_hi = (b2 - m_hi * wsum) * rs_hi;
    }
    CSTAMP(7);
    if (ST_HOLD && L == 0 && p == ST_P && w == 0 && first_lane) mbar_arrive(sb + BAR_ST + pin0(asu(r_lo)));
    if (LATE_Q1 == 3 && L == 0 && p == 1 && w == 0 && first_lane) mbar_arrive(sb + BAR_ST + pin0(asu(r_lo)));
    int candrow = -1;
    {
      const uint32_t kl = fkey(r_lo), kh = fkey(r_hi);
      const bool hi = kh > kl;
      const uint32_t kb = hi ? kh : kl;
      const uint32_t mx = __reduce_max_sync(0xffffffffu, kb);
      if (first_lane) sts32(sb + SM_BEST + p * 16 + w * 4, mx);
      const uint32_t bal = __ballot_sync(0xffffffffu, kb == mx);
      const bool mine = (bal & ((1u << (lane & 28)) - 1u)) == 0u && kb == mx;
      const uint32_t x0 = hi ? xw[1] : xw[0], x1 = hi ? xw[3] : xw[2], x2 = hi ? xw[5] : xw[4], x3 = hi ? xw[7] : xw[6], x4 = hi ? xw[9] : xw[8];
      const uint32_t x5 = hi ? xw[11] : xw[10], x6 = hi ? xw[13] : xw[12], x7 = hi ? xw[15] : xw[14], x8 = hi ? xw[17] : xw[16];
      nb_sync(NB_WG + p, 128);
      const uint4 bs = lds128(sb + SM_BEST + p * 16);
      const bool best = (w > 0 ? bs.x < mx : true) && (w > 1 ? bs.y < mx : bs.y <= mx) && (w > 2 ? bs.z < mx : bs.z <= mx) && bs.w <= mx;
      if (best && mine) {
        if (q < 2) stg128(sc + o_cand, asu(hi ? r_hi : r_lo), (tg << 6) + (uint32_t)(w * 16 + g + (hi ? 8 : 0)), asu(hi ? m_hi : m_lo), asu(hi ? rs_hi : rs_lo));
        stg128(sc + o_xc, x0, x1, x2, tg);
        stg128(sc + o_xc + 64, x3, x4, x5, tg);
        stg128(sc + o_xc + 128, x6, x7, x8, tg);
      }
      candrow = __reduce_max_sync(0xffffffffu, best && mine ? g + (hi ? 8 : 0) : -1);
    }
    if (L == 0 && p == 1) {
#pragma unroll
      for (int t = 0; t < 9; t++) { stg32(sc + o_x + t * 1024, xw[2 * t]); stg32(sc + o_x + t * 1024 + 128, xw[2 * t + 1]); }
      rb = ldg_rlx32(sc + o_xrb);
    }
    const uint32_t stg = sb + SM_B + p * 13824 + w * 2304;
    unsigned char* obase = (unsigned char*)P.out + ((128 * i + 32 * w + p) * 1152 + 144 * j);
    if (L == 1) {
      const float ul = 1.f + rs_lo, uh = 1.f + rs_hi, vl = -m_lo * rs_lo, vh = -m_hi * rs_hi;
#pragma unroll
      for (int t = 0; t < 9; t++) {
        xw[2 * t] = pack_bf16(fmaf(accw[4 * t], ul, vl), fmaf(accw[4 * t + 1], ul, vl));
        xw[2 * t + 1] = pack_bf16(fmaf(accw[4 * t + 2], uh, vh), fmaf(accw[4 * t + 3], uh, vh));
      }
      mbar_wait(sb + BAR_EMPTY + p * 8, 1);
      const uint32_t sa = stg + (lane & 15) * 144;
#pragma unroll
      for (int t = 0; t < 8; t += 2) stsm4(sa + (lane >> 4) * 16 + t * 16, xw[2 * t], xw[2 * t + 1], xw[2 * t + 2], xw[2 * t + 3]);
      stsm2(sa + 128, xw[16], xw[17]);
      __syncwarp();
      if (p == 0 || !OUT_LATE) store_rows(stg, obase, candrow, lane);
    }
    CSTAMP(8);
    lane = pin(lane);
    const unsigned char* cp = sc + (OFF(cand) + (j * 32 + lane) * (CAND_W * 4));
    if (p == 0) {
      if (L == 1 && candrow >= 0) {
        const Winner wn = poll_winner(cp, ldg_rlx128(cp), tg);
        if (lane < 9 && wn.ci != ip) *(uint4*)(obase + (candrow * 2304 + lane * 16)) = lds128(stg + candrow * 144 + lane * 16);
      }
    } else {
      const uint32_t gr = w * 144 + (lane & 7) + (lane >> 4) * 8, gm = sb + SM_G + ((lane >> 3) & 1) * 46080;
      const uint32_t ga = gm + gr * 64 + (((lane >> 1) & 3) << 4), gl = gm + 36864 + gr * 16;
#define GADDR(s, u) ((u) < 4 ? (ga ^ ((u) << 4)) + (s) * 1024 : gl + (s) * 256)
      uint32_t wf[NPRE][5][4];
      mbar_wait(sb + BAR_GU, 0);
#pragma unroll
      for (int s = 0; s < NPRE - 2; s++)
#pragma unroll
        for (int u = 0; u < 5; u++) ldsm4t(wf[s][u], GADDR(s, u));
      const uint4 c0 = ldg_rlx128(cp);
#pragma unroll
      for (int s = NPRE - 2; s < NPRE; s++)
#pragma unroll
        for (int u = 0; u < 5; u++) ldsm4t(wf[s][u], GADDR(s, u));
      flag_after(sc + o_cf, rb, 8 * T + 1, lane < 8 && L == 0);
      const Winner wn = poll_winner(cp, c0, tg);
      if (w == 0 && first_lane) sts128(sb + SM_WIN, asu(wn.r), asu(wn.m), asu(wn.rstd), (uint32_t)(wn.ci * 64 + wn.rr));
      if (LATE_Q1 == 2 && L == 0 && w == 0 && first_lane) mbar_arrive(sb + BAR_ST + pin0(wn.ci));
      CSTAMP(9);
      if (!OUT_LATE && L == 1 && candrow >= 0 && lane < 9 && wn.ci != ip) *(uint4*)(obase + (candrow * 2304 + lane * 16)) = lds128(stg + candrow * 144 + lane * 16);
      {
        uint32_t hb[18];
        const unsigned char* xc = sc + (OFF(xcand) + wn.ci * 1536 + q * 16);
        const int fp = min(cx.cta / 3, 23);
        uint4 u[7];
        int n = 0;
#pragma unroll 1
        while (true) {
          uint32_t d = 0;
#pragma unroll
          for (int e = 0; e < 7; e++) u[e] = ldg_rlx128(xc + (e < 6 ? w * 384 + e * 64 : fp * 64));
#pragma unroll
          for (int e = 0; e < 7; e++) d = orx(d, u[e].w, tg);
          if (__all_sync(0xffffffffu, d == 0)) break;
          if (++n > SPIN) TIMEOUT(__LINE__)
        }
        if (LATE_Q1 == 1 && L == 0 && w == 0 && first_lane) mbar_arrive(sb + BAR_ST + pin0(u[0].x));
        if (OUT_LATE == 3 && L == 1) store_rows(stg, obase, wn.ci == ip ? candrow : -1, lane);
#pragma unroll
        for (int e = 0; e < 6; e++) { hb[3 * e] = u[e].x; hb[3 * e + 1] = u[e].y; hb[3 * e + 2] = u[e].z; }
        if (w == 0) sts128(sb + SM_XW + q * 16, u[6].x, u[6].y, u[6].z, u[6].w);
        const float nb = -wn.m * wn.rstd;
#pragma unroll
        for (int b = 0; b < 18; b++) hb[b] = pack_bf16(fmaf(bf_lo(hb[b]), wn.rstd, nb), fmaf(bf_hi(hb[b]), wn.rstd, nb));
        CSTAMP(10);
        float d[5][4];
#pragma unroll
        for (int u = 0; u < 5; u++) d[u][0] = d[u][1] = d[u][2] = d[u][3] = 0.f;
#pragma unroll
        for (int s = 0; s < 9; s++) {
#pragma unroll
          for (int u = 0; u < 5; u++) {
            uint32_t* f = wf[s % NPRE][u];
            mma16(d[u], f[0], f[1], f[2], f[3], hb[2 * s], hb[2 * s + 1]);
            if (s + NPRE < 9) ldsm4t(f, GADDR(s + NPRE, u));
          }
        }
        if (q == 0) {
#pragma unroll
          for (int u = 0; u < 5; u++) sts64(sb + R_FPART + w * 320 + (u * 8 + g) * 8, asu(d[u][0]), asu(d[u][2]));
        }
        nb_arrive(NB_FFN, 224);
        CSTAMP(11);
      }
      if (OUT_LATE == 1 && L == 1) store_rows(stg, obase, wn.ci == ip ? candrow : -1, lane);
    }
  }
  STAMPIF(w == 0 && lane == 0, 40 + p * 20 + 12);
  PROF_DUMP();
#undef g
#undef q
#undef first_lane
}

__device__ __forceinline__ void load_wo_a(const Ctx& cx, const Params& P, const uint32_t T, const int L, const int p, const int lane) {
  const unsigned char* src = P.sc->obuf[cx.i * 2 + p];
#pragma unroll
  for (int c = 0; c < 9; c++) w_expect(sb + BAR_WFULL + (9 * p + c) * 8, 8192);
  mbar_wait(sb + BAR_HDONE + p * 8, L);
  wait_flags<32>(P.sc->cflag[cx.i * 2 + p], 8 * T + 2 * L, lane);
  fence_async_glob();
  STAMP(100 + L * 2 + p);
#pragma unroll
  for (int c = 0; c < 9; c++) {
    const int e = 9 * p + c, s = e % 6;
    if (e == 3) mbar_wait(sb + BAR_HDONE + 8, L);
    if (e >= 6) mbar_wait(sb + BAR_AEMPTY + s * 8, (L ^ (e / 6) ^ 1) & 1);
    w_bulk(sb + SM_A + (2 * (s % 3) + s / 3) * 8192, src + c * 8192, 8192, sb + BAR_WFULL + e * 8);
    PSTAMP(48 + L * 36 + 18 + e);
  }
}

__device__ __forceinline__ void finalize_row(const Params& P, const Winner& wn, const uint32_t T, const int L, const int grp, const int a, const int lane) {
  const unsigned char* yp = (const unsigned char*)P.sc->ypart[grp] + (a * 32 + lane) * 16;
  const uint32_t par = L ^ 1;
  if (L == 0 ? D_Y0 : D_Y1) { const int c0 = clock(); while ((int)(clock() - c0) < (L == 0 ? D_Y0 : D_Y1)) {} }
  uint4 u0 = ldg_rlx128(yp), u1 = ldg_rlx128(yp + 1536), u2 = make_uint4(par, 0, 0, 0);
  if (a < 2) rld128(u2, yp + 3072);
  const int col = lane & 7;
  const uint32_t xw = lds32(sb + SM_XW + (col >> 1) * 16 + (grp % 3) * 4);
  const float xsel = (col & 1) ? bf_hi(xw) : bf_lo(xw);
  const float sg = rbf(rcp(1.f + ex2(-1.4426950408889634f * rbf(wn.r))));
  const float h = rbf((xsel - wn.m) * wn.rstd);
  unsigned char* dst = L == 0 ? (unsigned char*)P.sc->xsel + (((lane >> 3) & 1) * 576 + grp * 8 + col) * 4
                              : (unsigned char*)P.out + ((128 * (wn.ci >> 1) + 2 * wn.rr + (wn.ci & 1)) * 576 + grp * 8 + col) * 2;
  int n = 0;
#pragma unroll 1
  while (__any_sync(0xffffffffu, orx(orx(orx(0, u0.x, par), u1.x, par), u2.x, par) & 1)) {
    rld128(u0, yp); rld128(u1, yp + 1536);
    if (a < 2) rld128(u2, yp + 3072);
    if (++n > SPIN) TIMEOUT(__LINE__)
  }
  const float s0 = asf(u0.x) + asf(u1.x) + asf(u2.x), s1 = asf(u0.y) + asf(u1.y) + asf(u2.y);
  const float s2 = asf(u0.z) + asf(u1.z) + asf(u2.z), s3 = asf(u0.w) + asf(u1.w) + asf(u2.w);
  const float k0 = self(lane & 2, s2, s0) + shx(self(lane & 2, s0, s2), 2), k1 = self(lane & 2, s3, s1) + shx(self(lane & 2, s1, s3), 2);
  float k = self(lane & 4, k1, k0) + shx(self(lane & 4, k0, k1), 4);
  k += shx(k, 8); k += shx(k, 16);
  if (lane < 8) stsf(sb + SM_YRED + ((lane & 1) * 4 + (lane & 2) + (lane >> 2)) * 16 + a * 4, k);
  nb_sync(NB_AUX, 96);
  if (a == 0) {
    const uint4 yy = lds128(sb + SM_YRED + col * 16);
    const float xn = rbf(xsel + rbf(h + rbf(rbf(asf(yy.x) + asf(yy.y) + asf(yy.z)) * sg)));
    if (L == 0) { if (lane < 16) stg32(dst, ftag(lane < 8 ? xn : xn - xsel, T & 1)); }
    else if (lane < 8) *(unsigned short*)dst = (unsigned short)(asu(xn) >> 16);
  }
}

__device__ __forceinline__ void aux_role(const Ctx& cx, const Params& P, const int a, const int lane_, const Unit& h0, const Unit& h1, const uint32_t hT) {
  int lane = lane_;
#define t (a * 32 + lane)
#define g (lane >> 2)
#define q (lane & 3)
  const int i = cx.i, j = cx.j, cta = cx.cta;
  unsigned char* const sc = (unsigned char*)P.sc;
  const int rk = 36 * i + 12 * a;
  const uint32_t o_bf = OFF(bflag) + (j * 48 + i * 3 + a) * 32 + (lane & 7) * 4;
  uint32_t T;
  {
    const int k0 = lane & 7, tt = min(lane >> 3, 2), col = (9 * j + tt) * 16;
    const unsigned char* src = (const unsigned char*)P.wqkv + ((i * 8 + k0) * 3456 + a * 1152 + col);
    const Unit b0 = h0, b1 = h1;
    T = hT;
    nb_arrive(NB_ORD, T_LATE == 2 ? 384 : 352);
    STAMPIF(1, 96);
    const uint32_t d2 = tt == 2 ? (22 - 7 * a) * 512 : 3072;
    const uint32_t o = OFF(wq) + (j * 18 + (i >> 2)) * 13824 + ((i & 3) * 8 + k0) * 16 + (a * 8 + tt) * 512;
    const uint32_t r0 = unit_store(sc, b0, lane, o, o + 1536, o + d2);
    STAMPD(asf(b0.v[2].w ^ b1.v[2].w), 80);
    const uint32_t r1 = unit_store(sc, b1, lane, o + 55296, o + 55296 + 1536, o + 55296 + d2);
    T = __shfl_sync(0xffffffffu, (T >> 3) + 1, 0);
    flag_after(sc + o_bf, r0 ^ r1, 8 * T + 1, lane < 8);
    STAMPD(asf(r0 ^ r1), 98);
    const Unit b2 = unit_load(src + 256 * 3456), b3 = unit_load(src + 384 * 3456);
    const bool qkv = k0 < 4;
    const int q0 = rk + k0 - 4, q1 = rk + 4 + k0;
    const Unit u0 = unit_load(qkv ? (const unsigned char*)P.wqkv + ((512 + 4 * i + k0) * 3456 + a * 1152 + col) : (const unsigned char*)P.wo + (q0 * 1152 + col));
    const Unit u1 = unit_load((const unsigned char*)P.wo + (q1 * 1152 + col));
    const uint32_t r2 = unit_store(sc, b2, lane, o + 2 * 55296, o + 2 * 55296 + 1536, o + 2 * 55296 + d2);
    const uint32_t r3 = unit_store(sc, b3, lane, o + 3 * 55296, o + 3 * 55296 + 1536, o + 3 * 55296 + d2);
    float cs[3][8];
#pragma unroll
    for (int m = 0; m < 3; m++) {
      const uint32_t* w0 = &b0.v[m].x; const uint32_t* w1 = &b1.v[m].x; const uint32_t* w2 = &b2.v[m].x; const uint32_t* w3 = &b3.v[m].x; const uint32_t* w4 = &u0.v[m].x;
#pragma unroll
      for (int e = 0; e < 4; e++) {
        const uint32_t z = qkv ? w4[e] : 0u;
        cs[m][2 * e] = (bf_lo(w0[e]) + bf_lo(w1[e])) + (bf_lo(w2[e]) + bf_lo(w3[e])) + bf_lo(z);
        cs[m][2 * e + 1] = (bf_hi(w0[e]) + bf_hi(w1[e])) + (bf_hi(w2[e]) + bf_hi(w3[e])) + bf_hi(z);
      }
    }
    flag_after(sc + o_bf, r2 ^ r3, 8 * T + 3, lane < 8);
    STAMPIF(1, 82);
#pragma unroll
    for (int st = 4; st >= 1; st >>= 1) {
      const bool up = lane & st;
#pragma unroll
      for (int m = 0; m < 3; m++)
#pragma unroll
        for (int e = 0; e < st; e++) cs[m][e] = (up ? cs[m][e + st] : cs[m][e]) + shx(up ? cs[m][e] : cs[m][e + st], st);
    }
    {
      const uint32_t oz = OFF(zpart) + j * 13824 + i * 864 + (a * 8 + tt) * 32 + k0 * 4;
      stg32(sc + oz, ftag(cs[0][0], 1)); stg32(sc + (oz + 96), ftag(cs[1][0], 1)); stg32(sc + (oz + (d2 >> 4)), ftag(cs[2][0], 1));
    }
    STAMPIF(1, 81);
    nb_sync(NB_GO, 128);
    mbar_wait(sb + BAR_FULL + LATE_WAIT * 8, 0);
    const uint32_t ow = OFF(wo) + j * 82944 + tt * 256;
    const uint32_t oa = qkv ? OFF(wq) + (j * 18 + 16 + (i >> 3)) * 13824 + (4 * (i & 7) + k0) * 16 + (a * 8 + tt) * 512 : ow + (q0 >> 4) * 2304 + (q0 & 15) * 16;
    const uint32_t ob = ow + (q1 >> 4) * 2304 + (q1 & 15) * 16;
    const uint32_t ra = unit_store(sc, u0, lane, oa, oa + (qkv ? 1536 : 768), oa + (qkv ? d2 : 1536));
    const uint32_t rb = unit_store(sc, u1, lane, ob, ob + 768, ob + 1536);
    STAMPIF(1, 113);
#pragma unroll
    for (int S = 0; S < 3; S++) stg64(sc + (OFF(ypart) + (a * 24 + g) * 4096 + cta * 32 + q * 8) + S * 32768, 0u, 0u);
    if (cta < 72 && t < 16) stg32(sc + (OFF(xsel) + (lane >> 3) * 2304 + cta * 32 + (lane & 7) * 4), (T & 1) ^ 1);
    uint4 sv, sw;
    int n = 0;
#pragma unroll 1
    while (true) {
      sv = ldg_rlx128(sc + (OFF(st0) + i * 2048 + t * 16)); sw = ldg_rlx128(sc + (OFF(st0) + i * 2048 + 1536 + lane * 16));
      if (__all_sync(0xffffffffu, ((sv.z ^ T) | (sw.z ^ T)) == 0)) break;
      if (++n > SPIN) TIMEOUT(__LINE__)
    }
    flag_after(sc + o_bf, ra ^ rb, 8 * T + 4, lane < 8);
    sts64(sb + SM_R + t * 8, sv.x, sv.y);
    sts64(sb + SM_R + 768 + lane * 8, sw.x, sw.y);
    STAMPIF(1, 94);
  }
  asm volatile("setmaxnreg.inc.sync.aligned.u32 %0;" ::"n"(REG_AUX));
  Winner wn;
  bool owner = false;
  uint32_t wd[5][3][8];
  auto load_wd = [&](uint32_t (*d)[8], const unsigned char* sk) {
#pragma unroll
    for (int S = 0; S < 3; S++) {
      const uint4 v0 = ldg_wd128(sk + S * 128), v1 = ldg_wd128(sk + S * 128 + 1152);
      d[S][0] = v0.x; d[S][1] = v1.x; d[S][2] = v0.y; d[S][3] = v1.y; d[S][4] = v0.z; d[S][5] = v1.z; d[S][6] = v0.w; d[S][7] = v1.w;
    }
  };
  auto perm_wd = [&](uint32_t (*d)[8]) {
#pragma unroll
    for (int S = 0; S < 3; S++)
#pragma unroll
      for (int u = 0; u < 4; u++) {
        const uint32_t x = d[S][2 * u], y = d[S][2 * u + 1];
        asm volatile("prmt.b32 %0, %2, %3, 0x5410;\nprmt.b32 %1, %2, %3, 0x7632;" : "=&r"(d[S][2 * u]), "=r"(d[S][2 * u + 1]) : "r"(x), "r"(y));
      }
  };
#pragma unroll
  for (int kb = 0; kb < 3; kb++)
#pragma unroll
    for (int S = 0; S < 3; S++)
#pragma unroll
      for (int e = 0; e < 8; e++) wd[kb][S][e] = 0u;
#pragma unroll 1
  for (int L = 0; L < 2; L++) {
    lane = pin(lane);
    const uint32_t o_part = OFF(zpart) + j * 13824, par = L ^ 1;
    const int pk = a * 18 + min(lane, 17);
    uint2 xu[3] = {make_uint2(0, 0), make_uint2(0, 0), make_uint2(0, 0)};
    if (L == 1) {
      if (cta < 72) finalize_row(P, wn, T, 0, cta, a, lane);
      const int gi = min(lane, 26);
      uint4 wv[12];
      {
        const int pc = gi < 24 ? gi >> 3 : gi - 24, tc = gi < 24 ? gi & 7 : 8;
        const unsigned char* se = (const unsigned char*)P.wqkv + (rk * 3456 + pc * 1152 + (9 * j + tc) * 16);
#pragma unroll
        for (int r = 0; r < 12; r++) wv[r] = ldg_nc128(se + r * 3456);
      }
      STAMPIF(1, 85);
      nb_sync(NB_AUX, 96);
      uint4 xq[3];
      {
        const unsigned char* dp = sc + (OFF(xsel) + 2304 + rk * 4);
        int n = 0;
#pragma unroll 1
        while (true) {
#pragma unroll
          for (int e = 0; e < 3; e++) xq[e] = ldg_rlx128(dp + e * 16);
          uint32_t d = orx(orx(orx(0, xq[0].x, T), xq[1].x, T), xq[2].x, T);
          if (owner) {
#pragma unroll
            for (int m = 0; m < 3; m++) xu[m] = ldg_rlx64(sc + (OFF(xsel) + t * 8) + m * 768);
            d = orx(orx(orx(d, xu[0].x, T), xu[1].x, T), xu[2].x, T);
          }
          if (__all_sync(0xffffffffu, (d & 1) == 0)) break;
          if (++n > SPIN) TIMEOUT(__LINE__)
        }
        if (t == 0) {
          sts32(sb + SM_SEL, owner ? (wn.ci & 1) * 64 + wn.rr : 0x7FFFFFFFu);
          if (wn.ci != 2 * i) mbar_arrive(sb + BAR_FIX);
          if (wn.ci != 2 * i + 1) mbar_arrive(sb + BAR_FIX + 8);
        }
        STAMPIF(1, 88);
      }
      float s[8];
#pragma unroll
      for (int e = 0; e < 8; e++) s[e] = 0.f;
#pragma unroll
      for (int r = 0; r < 12; r++) {
        const float x = asf((&xq[0].x)[r]);
        s[0] = fmaf(x, bf_lo(wv[r].x), s[0]); s[1] = fmaf(x, bf_hi(wv[r].x), s[1]);
        s[2] = fmaf(x, bf_lo(wv[r].y), s[2]); s[3] = fmaf(x, bf_hi(wv[r].y), s[3]);
        s[4] = fmaf(x, bf_lo(wv[r].z), s[4]); s[5] = fmaf(x, bf_hi(wv[r].z), s[5]);
        s[6] = fmaf(x, bf_lo(wv[r].w), s[6]); s[7] = fmaf(x, bf_hi(wv[r].w), s[7]);
      }
      sts128(sb + SM_R + a * 864 + gi * 32, asu(s[0]), asu(s[1]), asu(s[2]), asu(s[3]));
      sts128(sb + SM_R + a * 864 + gi * 32 + 16, asu(s[4]), asu(s[5]), asu(s[6]), asu(s[7]));
      nb_sync(NB_AUX, 96);
      const uint32_t ad = sb + SM_R + pk * 16;
      const uint4 u0 = lds128(ad), u1 = lds128(ad + 864), u2 = lds128(ad + 1728);
      stg128(sc + (o_part + i * 864 + pk * 16), ftag(asf(u0.x) + asf(u1.x) + asf(u2.x), par), ftag(asf(u0.y) + asf(u1.y) + asf(u2.y), par),
             ftag(asf(u0.z) + asf(u1.z) + asf(u2.z), par), ftag(asf(u0.w) + asf(u1.w) + asf(u2.w), par));
      STAMPIF(1, 86);
    }
    if (owner) {
      const uint2* u = xu;
      STAMPIF(1, 109);
      float s1 = 0.f, s2 = 0.f;
#pragma unroll
      for (int m = 0; m < 3; m++) {
        const float x0 = asf(u[m].x), x1 = asf(u[m].y);
        s1 += x0 + x1; s2 = fmaf(x0, x0, fmaf(x1, x1, s2));
        const unsigned cc = 96 * m + t - 36 * j;
        if (cc < 36u) sts32(sb + SM_X2S + cc * 4, __byte_perm(u[m].x, u[m].y, 0x7632));
      }
      wn.m = s1; wn.rstd = s2;
    }
    if (L == 0 || owner) {
      uint4 u[16];
      int n = 0;
#pragma unroll 1
      while (true) {
        uint32_t d0 = 0, d1 = 0;
#pragma unroll
        for (int e = 0; e < 16; e++) u[e] = ldg_rlx128(sc + (o_part + pk * 16) + e * 864);
        if (L == 1 && n == 0) {
#pragma unroll
          for (int s = 1; s < 32; s <<= 1) { wn.m += shx(wn.m, s); wn.rstd += shx(wn.rstd, s); }
          if (lane == 0) sts64(sb + SM_RED2 + a * 8, asu(wn.m), asu(wn.rstd));
        }
#pragma unroll
        for (int e = 0; e < 8; e++) { d0 = orx(d0, u[e].x, par); d1 = orx(d1, u[8 + e].x, par); }
        if (__all_sync(0xffffffffu, ((d0 | d1) & 1) == 0)) break;
        if (++n > SPIN) TIMEOUT(__LINE__)
      }
      STAMPIF(1, 118 + L);
      float4 z = make_float4(0.f, 0.f, 0.f, 0.f);
#pragma unroll
      for (int e = 0; e < 16; e++) { z.x += asf(u[e].x); z.y += asf(u[e].y); z.z += asf(u[e].z); z.w += asf(u[e].w); }
      const uint32_t h0 = pack_bf16(z.x, z.y), h1 = pack_bf16(z.z, z.w);
      const uint32_t l0 = pack_bf16(z.x - bf_lo(h0), z.y - bf_hi(h0)), l1 = pack_bf16(z.z - bf_lo(h1), z.w - bf_hi(h1));
      const uint32_t ad = sb + SM_BEXT + (pk >> 1) * 128 + (pk & 1) * 8;
      if (L == 0) {
        sts64(ad, h0, h1);
#pragma unroll
        for (int r = 3; r < 8; r++) sts64(ad + r * 16, 0u, 0u);
      }
      sts64(ad + 16 + L * 48, h0, h1); sts64(ad + 32 + L * 48, l0, l1);
      fence_async_smem();
      nb_sync(NB_AUX, 96);
      if (t == 0) {
        if (L == 1) {
          const uint4 ra = lds128(sb + SM_RED2);
          const uint2 rb = lds64(sb + SM_RED2 + 16);
          const float m2 = (asf(ra.x) + asf(ra.z) + asf(rb.x)) * (1.f / 576.f);
          const float rs2 = rsq(fmaxf((asf(ra.y) + asf(ra.w) + asf(rb.y)) * (1.f / 576.f) - m2 * m2, 0.f) + EPS);
          sts64(sb + SM_SEL + 8, asu(m2), asu(rs2));
          mbar_arrive(sb + BAR_FIX + (wn.ci & 1) * 8);
        } else {
          mbar_arrive(sb + BAR_FIX); mbar_arrive(sb + BAR_FIX + 8);
        }
        STAMP(83 + L * 4);
      }
    }
    lane = pin(lane);
    const unsigned char* const wsrc = (const unsigned char*)P.wd + ((ffn_c32(cta) + 2 * q) * 1152 + a * 384 + g * 16);
    if (L == 0) {
#pragma unroll
      for (int kb = 0; kb < 3; kb++) { load_wd(wd[kb], wsrc + (kb * 9216 + (kb ? pin0(wd[kb - 1][2][7]) : 0u))); perm_wd(wd[kb]); }
    }
    if (L == 0)
    {
    load_wd(wd[3], wsrc + 3 * 9216);
    load_wd(wd[4], wsrc + ((cta & 1) ? (ffn_c8(cta) - ffn_c32(cta)) * 1152 : 24 * 1152));
    perm_wd(wd[3]); perm_wd(wd[4]);
    }
    const uint32_t o_y = pin(OFF(ypart) + (a * 24 + g) * 4096 + cta * 32 + q * 8 + pin0(wd[4][2][7]));
    STAMPIF(1, 89 + L);
    if (a == 2) load_wo_a(cx, P, T, L, 1, lane);
    nb_sync(NB_FFN, 224);
    {
      const uint32_t ad = sb + R_FPART + min(lane, 19) * 16;
      const uint4 u0 = lds128(ad), u1 = lds128(ad + 320), u2 = lds128(ad + 640), u3 = lds128(ad + 960);
      const uint4 wv = lds128(sb + SM_WIN);
      const float g0 = rbf((asf(u0.x) + asf(u1.x)) + (asf(u2.x) + asf(u3.x))), g1 = rbf((asf(u0.z) + asf(u1.z)) + (asf(u2.z) + asf(u3.z)));
      const float v0 = rbf((asf(u0.y) + asf(u1.y)) + (asf(u2.y) + asf(u3.y))), v1 = rbf((asf(u0.w) + asf(u1.w)) + (asf(u2.w) + asf(u3.w)));
      const float s0 = rbf(g0 * rcp(1.f + ex2(-1.4426950408889634f * g0))), s1 = rbf(g1 * rcp(1.f + ex2(-1.4426950408889634f * g1)));
      const uint32_t act = lane < 16 + (cta & 1) * 4 ? pack_bf16(s0 * v0, s1 * v1) : 0u;
      uint32_t b[5];
#pragma unroll
      for (int kb = 0; kb < 5; kb++) b[kb] = __shfl_sync(0xffffffffu, act, 4 * kb + q);
#pragma unroll
      for (int S = 0; S < 3; S++) {
        float y[4][4];
#pragma unroll
        for (int u = 0; u < 4; u++) mma8z(y[u], wd[2][S][2 * u], wd[2][S][2 * u + 1], b[2]);
#pragma unroll
        for (int u = 0; u < 4; u++) mma16(y[u], wd[0][S][2 * u], wd[0][S][2 * u + 1], wd[1][S][2 * u], wd[1][S][2 * u + 1], b[0], b[1]);
#pragma unroll
        for (int u = 0; u < 4; u++) mma16(y[u], wd[3][S][2 * u], wd[3][S][2 * u + 1], wd[4][S][2 * u], wd[4][S][2 * u + 1], b[3], b[4]);
        const float y0 = self(lane & 2, self(lane & 1, y[3][0], y[2][0]), self(lane & 1, y[1][0], y[0][0]));
        const float y1 = self(lane & 2, self(lane & 1, y[3][2], y[2][2]), self(lane & 1, y[1][2], y[0][2]));
        stg64(sc + o_y + S * 32768, ftag(y0, par), ftag(y1, par));
      }
      if (L == 0) nb_arrive(NB_FFN2, Q1_BOTH ? 352 : 224);
      wn.r = asf(wv.x); wn.m = asf(wv.y); wn.rstd = asf(wv.z); wn.ci = wv.w >> 6; wn.rr = wv.w & 63;
    }
    STAMPIF(1, 84 + L * 8);
    owner = (wn.ci >> 1) == i;
  }
  if (cta < 72) finalize_row(P, wn, T, 1, cta, a, lane);
  STAMPIF(1, 93);
  PROF_END();
#undef t
#undef g
#undef q
}

__device__ __forceinline__ int sched_box(const uint32_t at, const int a) {
  int r = -1;
#pragma unroll
  for (int b = 0; b < 6; b++) if (((at >> (4 * b)) & 15) != 15) r = a == (int)((at >> (4 * b)) & 15) ? b : r;
  return r;
}
__host__ __device__ constexpr int sched_first(const uint32_t at) { int b = 0; while (b < 6 && ((at >> (4 * b)) & 15) != 15) b++; return b; }
__host__ __device__ constexpr int sched_last(const uint32_t at) { int b = 5; while (b >= 0 && ((at >> (4 * b)) & 15) != 15) b--; return b; }
__device__ __forceinline__ void producer_role(const Ctx& cx, const Params& P, const int lane) {
  const int i = cx.i, j = cx.j;
  nb_sync(NB_ORD, 384);
  if (elect_one()) asm volatile("prefetch.tensormap [%0];" ::"l"(&P.mx) : "memory");
  const uint32_t T = __shfl_sync(0xffffffffu, (ldg_rlx32(P.sc->cflag[i * 2][j * 4]) >> 3) + 1, 0);
  const unsigned char* const wq = P.sc->wq[j][0];
  nb_sync(NB_START, 288);
#pragma unroll
  for (int s = 0; s < 2 * NA0; s++) w_tma3d(sb + SM_A + s * 8192, &P.mx, (s >> 1) * 64, s & 1, i * 64, sb + BAR_FULL + (s >> 1) * 16);
#pragma unroll
  for (int h = 0; h < 6; h++) w_expect(sb + BAR_FULL + h * 8, h & 1 ? 13824 : 13824 + 16384);
  STAMP(97);
  wait_flags<48>(P.sc->bflag[j], 8 * T + 1, lane);
  fence_async_glob();
  STAMP(120);
#pragma unroll
  for (int h = 0; h < 6; h++) {
    if (h >= P_FROM && P_GAP) { const int c0 = clock(); while ((int)(clock() - c0) < P_GAP) {} }
    w_bulk(sb + SM_B + h * 13824, wq + h * 13824, 13824, sb + BAR_FULL + h * 8);
    if (!(h & 1) && h >= 2 * NA0) {
      w_tma3d(sb + SM_A + h * 8192, &P.mx, h * 32, 0, i * 64, sb + BAR_FULL + h * 8);
      w_tma3d(sb + SM_A + h * 8192 + 8192, &P.mx, h * 32, 1, i * 64, sb + BAR_FULL + h * 8);
    }
  }
  PSTAMP(0);
  asm volatile("setmaxnreg.inc.sync.aligned.u32 %0;" ::"n"(REG_AUX));
  nb_arrive(NB_GO, 128);
  mbar_wait(sb + BAR_FULL + PF_WAIT * 8, 0);
  w_prefetch((const unsigned char*)P.wd + cx.cta * 41472, 10368);
  const unsigned char* const xb = P.sc->xbuf[i * 2];
  const unsigned char* const fp = (const unsigned char*)P.sc->bflag[j] + lane * 32;
  uint32_t f0 = 0, f1 = 0;
#pragma unroll 1
  for (int L = 0; L < 2; L++) {
    if (L == 1 && !LATE_Q1) {
#pragma unroll 1
      for (int p = 0; p < 2; p++) {
        mbar_wait(sb + BAR_AEMPTY + (2 + 3 * p) * 8, 0);
        wait_flags<32>(P.sc->cflag[i * 2 + p], 8 * T + 1, lane);
        fence_async_glob();
        STAMP(104 + p);
#pragma unroll
        for (int a = 0; a < 3; a++) {
          const int s = 2 * a + p;
          w_expect(sb + BAR_AFULL + s * 8, 8192);
          w_bulk(sb + SM_A + s * 8192, xb + (p * 73728 + a * 8192), 8192, sb + BAR_AFULL + s * 8);
          PSTAMP(48 + 36 + 3 * p + a);
        }
      }
    }
#pragma unroll 1
    for (int a = 3; a < 15; a++) {
      if (a == 12) {
        load_wo_a(cx, P, T, L, 0, lane);
        if (L == 1) break;
        if (LATE_Q1) {
#pragma unroll 1
          for (int b = LATE_U0; b < 6; b++) {
            if (LATE_GGAP) { const int c0 = clock(); while ((int)(clock() - c0) < LATE_GGAP) {} }
            load_gu(P, cx.cta, 1, b, sb + BAR_GU);
          }
#pragma unroll 1
          for (int b = LATE_G0; b < 6; b++) {
            if (LATE_GGAP) { const int c0 = clock(); while ((int)(clock() - c0) < LATE_GGAP) {} }
            load_gu(P, cx.cta, 0, b, sb + BAR_GU);
          }
#pragma unroll 1
          for (int p = 0; p < 2; p++) {
            mbar_wait(sb + BAR_AEMPTY + (2 + 3 * p) * 8, 0);
            wait_flags<32>(P.sc->cflag[i * 2 + p], 8 * T + 1, lane);
            STAMP(104 + p);
          }
          fence_async_glob();
          mbar_wait(sb + BAR_ST, 0);
#pragma unroll 1
          for (int s = 0; s < 3; s++) {
            const uint32_t fb = sb + BAR_FULL + s * 16, ab = sb + BAR_AFULL + s * 16, db = sb + SM_B + s * 27648, da = sb + SM_A + s * 16384;
            mbar_wait(sb + BAR_EMPTY + s * 16, 1);
            w_expect(fb, 13824);
            w_bulk(db, wq + s * 27648, 13824, fb);
            w_expect(ab, 8192);
            w_bulk(da, xb + s * 8192, 8192, ab);
            w_expect(ab + 8, 8192);
            w_bulk(da + 8192, xb + (73728 + s * 8192), 8192, ab + 8);
            mbar_wait(sb + BAR_EMPTY + s * 16 + 8, 1);
            w_expect(fb + 8, 13824);
            w_bulk(db + 13824, wq + (s * 27648 + 13824), 13824, fb + 8);
          }
          break;
        }
      }
      const int r = (a * 11) >> 5, s = a - 3 * r;
      const uint32_t fb = sb + BAR_FULL + s * 16, da = sb + SM_A + s * 16384, db = sb + SM_B + s * 27648;
      const unsigned char* bsrc = wq + (a < 9 ? a : a < 12 ? 72 - 6 * j + s : s) * 27648;
      const unsigned char* asrc = xb + a * 8192;
      const int kc = (a < 9 ? a : j + a - 10) * 64;
      const int amode = a == 9 || a > 11 ? 0 : L == 0 ? 1 : a < 9 ? 2 : 0;
      mbar_wait(sb + BAR_EMPTY + s * 16, (r & 1) ^ 1);
      if (ST_HOLD && a == ST_HOLD) mbar_wait(sb + BAR_ST, 0);
      if (L == 0) {
        if (a == 4 || a == 8) {
          const uint32_t need = 8 * T + (a == 4 ? 3 : 4);
          if (__any_sync(0xffffffffu, (int)((f0 - need) | (f1 - need)) < 0)) wait_flags<48>(P.sc->bflag[j], need, lane);
          fence_async_glob();
          STAMP(120 + (a >> 1));
        }
        if (a == 3 || a == 7) { f0 = ldg_rlx32(fp); f1 = ldg_rlx32(fp + (lane < 16 ? 1024 : 0)); }
      }
      w_bulk(db, bsrc, 13824, fb);
      if (amode == 2) {
        w_bulk(da, asrc, 4096, fb);
        w_bulk(da + 8192, asrc + 73728, 4096, fb);
      }
      w_expect(fb, amode == 1 ? 13824 + 16384 : amode == 2 ? 13824 + 8192 : 13824);
      mbar_wait(sb + BAR_EMPTY + s * 16 + 8, (r & 1) ^ 1);
      if (amode == 1) {
        w_tma3d(da, &P.mx, kc, 0, i * 64, fb);
        w_tma3d(da + 8192, &P.mx, kc, 1, i * 64, fb);
      }
      w_bulk(db + 13824, bsrc + 13824, 13824, fb + 8);
      if (amode == 2) {
        w_bulk(da + 4096, asrc + 4096, 4096, fb + 8);
        w_bulk(da + 8192 + 4096, asrc + 73728 + 4096, 4096, fb + 8);
      }
      w_expect(fb + 8, amode == 2 ? 13824 + 8192 : 13824);
      PSTAMP(a < 12 ? L * 24 + a : 12 + a);
      if (L == 0) {
        {
          if (a >= WD_PF && a < WD_PF + 3) w_prefetch((const unsigned char*)P.wd + (cx.cta * 4 + a - WD_PF + 1) * 10368, 10368);
          if (a >= PG_0 && a < PG_0 + 6) w_prefetch((const unsigned char*)P.wg + ((a - PG_0) * 128 + cx.cta) * 6912, 6912);
        }
        if (a == 3) w_expect(sb + BAR_GU, 12 * (6144 + (cx.cta & 1) * 1536));
        {
          const int bu = sched_box(U_AT, a), bg = sched_box(G_AT, a);
          if (bu >= 0) load_gu(P, cx.cta, 1, bu, sb + BAR_GU);
          if (bg >= 0) load_gu(P, cx.cta, 0, bg, sb + BAR_GU);
          if (a == U_WIN) {
#pragma unroll 1
            for (int b = sched_first(U_AT); b <= sched_last(U_AT); b++) {
              const int c0 = clock();
              while ((int)(clock() - c0) < U_GAP) {}
              load_gu(P, cx.cta, 1, b, sb + BAR_GU);
            }
          }
          if (a == G_WIN) {
#pragma unroll 1
            for (int b = sched_first(G_AT); b <= sched_last(G_AT); b++) {
              const int c0 = clock();
              while ((int)(clock() - c0) < G_GAP) {}
              load_gu(P, cx.cta, 0, b, sb + BAR_GU);
            }
          }
        }
      }
    }
  }
}

template <bool BY_SMID>
__global__ void __launch_bounds__(384, 1) fused_kernel(const __grid_constant__ Params P) {
  extern __shared__ __align__(1024) unsigned char smem[];
  Ctx cx;
  STAMPIF(threadIdx.x == 64, 125);
  unsigned id;
  if (BY_SMID) asm volatile("mov.u32 %0, %%smid;" : "=r"(id)); else id = blockIdx.x;
  const int work = __shfl_sync(0xffffffffu, (int)P.work[min(id, 131u)], 0);
  const int warp = __shfl_sync(0xffffffffu, (int)(threadIdx.x >> 5), 0), lane = threadIdx.x & 31;
  if (work < 0) {
    if (warp == 0) {
      const int sp = -1 - work;
      if (lane == 0) { mbar_init(sb, 1); fence_async_smem(); }
      __syncwarp();
      __nanosleep(SPARE_DELAY);
#pragma unroll 1
      for (int k = 32 + sp; k < 72; k += 4) w_prefetch((const unsigned char*)P.wqkv + k * 27648, 27648);
#pragma unroll 1
      for (int k = sp; k < 24; k += 4) w_prefetch((const unsigned char*)P.wo + k * 27648, 27648);
#pragma unroll 1
      for (int k = sp; k < X_NU; k += 4) w_prefetch((const unsigned char*)P.wu + k * 27648, 27648);
      w_expect(sb, 16);
      w_bulk(sb + 128, P.wr, 16, sb);
      mbar_wait(sb, 0);
    }
    return;
  }
  cx.cta = work; cx.i = work >> 3; cx.j = work & 7;
  STAMPIF(threadIdx.x == 32, 95);
  Unit h0, h1;
  uint32_t hT = 0;
  if (warp >= 8 && warp < 11) {
    const int a = warp - 8, k0 = lane & 7, tt = min(lane >> 3, 2);
    const unsigned char* src = (const unsigned char*)P.wqkv + ((cx.i * 8 + k0) * 3456 + a * 1152 + (9 * cx.j + tt) * 16);
    h0 = unit_load(src); h1 = unit_load(src + 128 * 3456);
    hT = ldg_rlx32((const unsigned char*)P.sc + (OFF(bflag) + (cx.j * 48 + cx.i * 3 + a) * 32 + (lane & 7) * 4));
  }
  if (warp < 8) {
    asm volatile("setmaxnreg.dec.sync.aligned.u32 %0;" ::"n"(REG_CONS));
    if (warp == 0) {
      if (elect_one()) {
        if ((uint32_t)__cvta_generic_to_shared(smem) != sb) __trap();
#pragma unroll
        for (int b = 0; b < 48; b++) mbar_init(sb + SM_BAR + b * 8, b < 34 ? 1 : b < 42 ? 4 : 8);
        fence_async_smem();
      }
      __syncwarp();
    }
    consumer_role(cx, P, smem, warp >> 2, warp & 3, lane);
  } else {
    if (warp < 11) aux_role(cx, P, warp - 8, lane, h0, h1, hT);
    else producer_role(cx, P, lane);
  }
}

int work_of_smid(int smid) {
  const int t = smid >> 1;
  if (t == 60 || t == 61) return -1 - ((t - 60) * 2 + (smid & 1));
  const int gpc = t < 32 ? t & 7 : t < 60 ? 1 + (t - 32) % 7 : 0;
  const int x = 2 * (t < 32 ? t >> 3 : t < 60 ? 4 + (t - 32) / 7 : t - 58) + (smid & 1);
  const int blk[8] = {6, 0, 2, 3, 4, 7, 5, 1}, b = blk[gpc];
  return ((b >> 1) * 4 + (x & 1) + (x >> 3) * 2) * 8 + (b & 1) * 4 + ((x >> 1) & 3);
}

typedef CUresult (*EncodeFn)(CUtensorMap*, CUtensorMapDataType, cuuint32_t, void*, const cuuint64_t*, const cuuint64_t*,
                             const cuuint32_t*, const cuuint32_t*, CUtensorMapInterleave, CUtensorMapSwizzle,
                             CUtensorMapL2promotion, CUtensorMapFloatOOBfill);

void make_map(EncodeFn enc, CUtensorMap* m, const void* base, int rank, const cuuint64_t* dims, const cuuint64_t* strides,
              const cuuint32_t* box, CUtensorMapSwizzle sw, CUtensorMapL2promotion promo = CU_TENSOR_MAP_L2_PROMOTION_L2_128B) {
  const cuuint32_t es[3] = {1, 1, 1};
  enc(m, CU_TENSOR_MAP_DATA_TYPE_BFLOAT16, rank, const_cast<void*>(base), dims, strides, box, es, CU_TENSOR_MAP_INTERLEAVE_NONE, sw,
      promo, CU_TENSOR_MAP_FLOAT_OOB_FILL_NONE);
}

}

extern "C" void kernel_launch(void* const* d_in, const int* in_sizes, int n_in, void* d_out, int out_size) {
  (void)in_sizes; (void)n_in; (void)out_size;
  static EncodeFn enc = nullptr;
  static int nsm = 0;
  static void* scr = nullptr;
  if (!enc) {
    void* f = nullptr;
    cudaDriverEntryPointQueryResult qr;
    cudaGetDriverEntryPoint("cuTensorMapEncodeTiled", &f, cudaEnableDefault, &qr);
    enc = (EncodeFn)f;
    cudaGetSymbolAddress(&scr, g_scratch);
    int dev = 0;
    cudaGetDevice(&dev);
    cudaDeviceGetAttribute(&nsm, cudaDevAttrMultiProcessorCount, dev);
    cudaFuncSetAttribute(fused_kernel<true>, cudaFuncAttributeMaxDynamicSharedMemorySize, SM_TOTAL);
    cudaFuncSetAttribute(fused_kernel<false>, cudaFuncAttributeMaxDynamicSharedMemorySize, SM_TOTAL);
  }
  Params P;
  P.x = (const __nv_bfloat16*)d_in[0];
  P.wqkv = (const __nv_bfloat16*)d_in[1];
  P.wo = (const __nv_bfloat16*)d_in[2];
  P.wr = (const __nv_bfloat16*)d_in[4];
  P.wg = (const __nv_bfloat16*)d_in[5];
  P.wu = (const __nv_bfloat16*)d_in[6];
  P.wd = (const __nv_bfloat16*)d_in[7];
  P.out = (__nv_bfloat16*)d_out;
  P.sc = (Scratch*)scr;
  for (int k = 0; k < 136; k++) P.work[k] = (signed char)(nsm == 132 ? (k < 132 ? work_of_smid(k) : -1) : (k < 128 ? k : k < 132 ? 127 - k : -1));
  {
    const cuuint64_t dims[3] = {576, 2, 1024}, str[2] = {1152, 2304};
    const cuuint32_t box[3] = {64, 1, 64};
    make_map(enc, &P.mx, P.x, 3, dims, str, box, CU_TENSOR_MAP_SWIZZLE_128B);
  }
  {
    const cuuint64_t dims[2] = {4608, 576}, str[1] = {9216};
    const cuuint32_t box[2] = {32, 96}, box8[2] = {8, 96};
    make_map(enc, &P.mg, d_in[5], 2, dims, str, box, CU_TENSOR_MAP_SWIZZLE_64B);
    make_map(enc, &P.mu, d_in[6], 2, dims, str, box, CU_TENSOR_MAP_SWIZZLE_64B);
    make_map(enc, &P.mg8, d_in[5], 2, dims, str, box8, CU_TENSOR_MAP_SWIZZLE_NONE);
    make_map(enc, &P.mu8, d_in[6], 2, dims, str, box8, CU_TENSOR_MAP_SWIZZLE_NONE);
  }
  if (nsm == 132) fused_kernel<true><<<132, 384, SM_TOTAL>>>(P);
  else fused_kernel<false><<<132, 384, SM_TOTAL>>>(P);
}
```

```cpp
#include <cuda_runtime.h>
#include <cuda.h>
#include <cuda_bf16.h>
#include <stdint.h>
#include <stddef.h>

namespace {

#define NPRE_ 4
constexpr int NPRE = NPRE_;
#define X_NU 192
#define CAND_W 8
#define X_DELAY 200
#define X_STEP 100
#define HOLD_C 13
#define NA0 3
#define LATE_WAIT 1
#define U_AT 0xFFFF75
#define G_AT 0xEEEEEB
#define PG_0 6
#define WD_PF 3
#define U_WIN 11
#define U_GAP 400
#define LATE_G0 1
#define LATE_GGAP 600
#define REG_AUX 200
#define REG_CONS 152
#define D_STATS 400
#define D_Y0 500
#define PF_WAIT 0
#define POLL_GAP 100
#define SPARE_DELAY 400
constexpr float EPS = 1e-5f;
constexpr int SPIN = 1 << 22;
#define TIMEOUT(line) __trap();

struct __align__(128) Scratch {
  uint32_t bflag[8][48][8];
  uint32_t cflag[32][32][8];
  uint32_t halo[32][8][672];
  uint32_t stats[32][4][8][64];
  uint32_t cand[8][32][CAND_W];
  uint32_t xcand[32][8][48];
  uint32_t ypart[72][128][8];
  uint32_t zpart[8][16][216];
  uint32_t st0[2048][4];
  uint32_t xsel[2][576];
  unsigned char wq[8][9][27648];
  unsigned char wo[8][3][27648];
  unsigned char obuf[32][73728];
  unsigned char xbuf[32][73728];
};
__device__ Scratch g_scratch;
#define OFF(f) ((uint32_t)offsetof(Scratch, f))
#define STAMPD(v, k) do {} while (0)
#define STAMPIF(c, k) do {} while (0)
#define STAMP(k) do {} while (0)

constexpr uint32_t sb = 1024;
constexpr uint32_t SM_A = 0;
constexpr uint32_t SM_B = 49152;
constexpr uint32_t SM_G = 132096;
constexpr uint32_t SM_BEXT = 224256;

constexpr uint32_t SM_WIN = 227712;
constexpr uint32_t SM_XW = 228320;
constexpr uint32_t SM_YRED = 228448;
constexpr uint32_t SM_X2S = 228576;
constexpr uint32_t SM_RED2 = 228736;
constexpr uint32_t SM_WR = 228864;
constexpr uint32_t SM_R = 229168;
constexpr uint32_t SM_BEST = 231760;
constexpr uint32_t SM_SEL = 231824;
constexpr uint32_t SM_BAR = 231840;
constexpr uint32_t SM_TOTAL = 232448;
constexpr uint32_t R_FPART = SM_R;
constexpr uint32_t BAR_FULL = SM_BAR  , BAR_AFULL = SM_BAR + 48  , BAR_WFULL = SM_BAR + 96  , BAR_ST = SM_BAR + 240, BAR_GU = SM_BAR + 248,
                   BAR_FIX = SM_BAR + 256  , BAR_AEMPTY = SM_BAR + 272  , BAR_HDONE = SM_BAR + 320  ,
                   BAR_EMPTY = SM_BAR + 336  ;
enum { NB_WG = 1  , NB_STAG = 3, NB_AUX = 4, NB_FFN2 = 5, NB_FFN = 8, NB_START = 9, NB_GO = 6, NB_ORD = 7, NB_PF = 11, NB_INIT = 12 };

struct Params {
  const __nv_bfloat16 *wqkv, *x, *wr, *wo;
  Scratch* sc;
  const __nv_bfloat16 *wd, *wg, *wu;
  __nv_bfloat16* out;
  signed char work[136];
  CUtensorMap mx, mg, mu, mg8, mu8;
};

__device__ __forceinline__ void mbar_init(uint32_t bar, int cnt) { asm volatile("mbarrier.init.shared::cta.b64 [%0], %1;" ::"r"(bar), "r"(cnt) : "memory"); }
__device__ __forceinline__ void mbar_arrive(uint32_t bar) { asm volatile("mbarrier.arrive.shared::cta.b64 _, [%0];" ::"r"(bar) : "memory"); }
__device__ __forceinline__ void mbar_wait(uint32_t bar, uint32_t par) {
  asm volatile("{\n.reg .pred p;\nLOOP:\nmbarrier.try_wait.parity.shared::cta.b64 p, [%0], %1;\n@!p bra.uni LOOP;\n}\n" ::"r"(bar), "r"(par) : "memory");
}
__device__ __forceinline__ uint32_t mbar_test(uint32_t bar, uint32_t par) {
  uint32_t ok;
  asm volatile("{\n.reg .pred p;\nmbarrier.test_wait.parity.shared::cta.b64 p, [%1], %2;\nselp.u32 %0,1,0,p;\n}" : "=r"(ok) : "r"(bar), "r"(par) : "memory");
  return ok;
}
__device__ __forceinline__ bool elect_one() {
  uint32_t ok;
  asm volatile("{\n.reg .pred p;\nelect.sync _|p, 0xffffffff;\nselp.u32 %0, 1, 0, p;\n}" : "=r"(ok));
  return ok;
}
__device__ __forceinline__ float ex2(float x) { float r; asm("ex2.approx.ftz.f32 %0, %1;" : "=f"(r) : "f"(x)); return r; }
__device__ __forceinline__ float rsq(float x) { float r; asm("rsqrt.approx.ftz.f32 %0, %1;" : "=f"(r) : "f"(x)); return r; }
__device__ __forceinline__ float rcp(float x) { float r; asm("rcp.approx.ftz.f32 %0, %1;" : "=f"(r) : "f"(x)); return r; }
__device__ __forceinline__ void w_expect(uint32_t bar, uint32_t bytes) {
  asm volatile("{\n.reg .pred p;\nelect.sync _|p, 0xffffffff;\n@p mbarrier.arrive.expect_tx.shared::cta.b64 _, [%0], %1;\n}" ::"r"(bar), "r"(bytes) : "memory");
}
__device__ __forceinline__ void w_bulk(uint32_t dst, const void* src, uint32_t bytes, uint32_t bar) {
  asm volatile("{\n.reg .pred p;\nelect.sync _|p, 0xffffffff;\n@p cp.async.bulk.shared::cluster.global.mbarrier::complete_tx::bytes [%0], [%1], %2, [%3];\n}" ::"r"(dst), "l"(src), "r"(bytes), "r"(bar) : "memory");
}
__device__ __forceinline__ void w_tma2d(uint32_t dst, const CUtensorMap* m, int c0, int c1, uint32_t bar) {
  asm volatile("{\n.reg .pred p;\nelect.sync _|p, 0xffffffff;\n@p cp.async.bulk.tensor.2d.shared::cluster.global.mbarrier::complete_tx::bytes [%0], [%1, {%3, %4}], [%2];\n}" ::"r"(dst), "l"(m), "r"(bar), "r"(c0), "r"(c1) : "memory");
}
__device__ __forceinline__ void w_tma3d(uint32_t dst, const CUtensorMap* m, int c0, int c1, int c2, uint32_t bar) {
  asm volatile("{\n.reg .pred p;\nelect.sync _|p, 0xffffffff;\n@p cp.async.bulk.tensor.3d.shared::cluster.global.mbarrier::complete_tx::bytes [%0], [%1, {%3, %4, %5}], [%2];\n}" ::"r"(dst), "l"(m), "r"(bar), "r"(c0), "r"(c1), "r"(c2) : "memory");
}
__device__ __forceinline__ void w_prefetch(const void* src, uint32_t bytes) {
  asm volatile("{\n.reg .pred p;\nelect.sync _|p, 0xffffffff;\n@p cp.async.bulk.prefetch.L2.global [%0], %1;\n}" ::"l"(src), "r"(bytes) : "memory");
}
__device__ __forceinline__ void nb_sync(int id, int n) { asm volatile("bar.sync %0, %1;" ::"r"(id), "r"(n) : "memory"); }
__device__ __forceinline__ void nb_arrive(int id, int n) { asm volatile("bar.arrive %0, %1;" ::"r"(id), "r"(n) : "memory"); }
__device__ __forceinline__ void fence_async_smem() { asm volatile("fence.proxy.async.shared::cta;" ::: "memory"); }
__device__ __forceinline__ void fence_async_glob() { asm volatile("fence.proxy.async.global;" ::: "memory"); }
__device__ __forceinline__ void flag_after(void* p, uint32_t readback, uint32_t T, bool writer) {
  asm volatile("{\n.reg .pred p;\n.reg .u32 v;\nsetp.ne.u32 p, %3, 0;\nor.b32 v, %1, %2;\nmin.u32 v, v, %2;\n@p st.relaxed.gpu.global.u32 [%0], v;\n}"
               ::"l"(p), "r"(readback), "r"(T), "r"((uint32_t)writer) : "memory");
}
__device__ __forceinline__ uint4 ldg_rlx128(const void* p) { uint4 v; asm volatile("ld.relaxed.gpu.global.v4.b32 {%0,%1,%2,%3}, [%4];" : "=r"(v.x), "=r"(v.y), "=r"(v.z), "=r"(v.w) : "l"(p) : "memory"); return v; }
__device__ __forceinline__ uint2 ldg_rlx64(const void* p) { uint2 v; asm volatile("ld.relaxed.gpu.global.v2.b32 {%0,%1}, [%2];" : "=r"(v.x), "=r"(v.y) : "l"(p) : "memory"); return v; }
__device__ __forceinline__ void rld128(uint4& v, const void* p) { asm volatile("ld.relaxed.gpu.global.v4.b32 {%0,%1,%2,%3}, [%4];" : "+r"(v.x), "+r"(v.y), "+r"(v.z), "+r"(v.w) : "l"(p) : "memory"); }
__device__ __forceinline__ uint32_t ldg_rlx32(const void* p) { uint32_t v; asm volatile("ld.relaxed.gpu.global.b32 %0, [%1];" : "=r"(v) : "l"(p) : "memory"); return v; }
#define NC_HINT ""
__device__ __forceinline__ uint4 ldg_nc128(const void* p) { uint4 v; asm volatile("ld.global.nc" NC_HINT ".v4.b32 {%0,%1,%2,%3}, [%4];" : "=r"(v.x), "=r"(v.y), "=r"(v.z), "=r"(v.w) : "l"(p)); return v; }
#define WD_HINT ".nc.L1::no_allocate"
__device__ __forceinline__ uint4 ldg_wd128(const void* p) { uint4 v; asm volatile("ld.global" WD_HINT ".v4.b32 {%0,%1,%2,%3}, [%4];" : "=r"(v.x), "=r"(v.y), "=r"(v.z), "=r"(v.w) : "l"(p)); return v; }
__device__ __forceinline__ uint32_t ldg_nc32(const void* p) { uint32_t v; asm volatile("ld.global.nc.L1::no_allocate.b32 %0, [%1];" : "=r"(v) : "l"(p)); return v; }
__device__ __forceinline__ void stg128(void* p, uint32_t a, uint32_t b, uint32_t c, uint32_t d) { asm volatile("st.relaxed.gpu.global.v4.b32 [%0], {%1,%2,%3,%4};" ::"l"(p), "r"(a), "r"(b), "r"(c), "r"(d) : "memory"); }
__device__ __forceinline__ void stg64(void* p, uint32_t a, uint32_t b) { asm volatile("st.relaxed.gpu.global.v2.b32 [%0], {%1,%2};" ::"l"(p), "r"(a), "r"(b) : "memory"); }
__device__ __forceinline__ void stg32(void* p, uint32_t a) { asm volatile("st.relaxed.gpu.global.b32 [%0], %1;" ::"l"(p), "r"(a) : "memory"); }
__device__ __forceinline__ void sts128(uint32_t a, uint32_t x, uint32_t y, uint32_t z, uint32_t w) { asm volatile("st.shared.v4.b32 [%0], {%1,%2,%3,%4};" ::"r"(a), "r"(x), "r"(y), "r"(z), "r"(w) : "memory"); }
__device__ __forceinline__ void sts64(uint32_t a, uint32_t x, uint32_t y) { asm volatile("st.shared.v2.b32 [%0], {%1,%2};" ::"r"(a), "r"(x), "r"(y) : "memory"); }
__device__ __forceinline__ void sts32(uint32_t a, uint32_t x) { asm volatile("st.shared.b32 [%0], %1;" ::"r"(a), "r"(x) : "memory"); }
__device__ __forceinline__ void stsf(uint32_t a, float x) { sts32(a, __float_as_uint(x)); }
__device__ __forceinline__ uint4 lds128(uint32_t a) { uint4 v; asm volatile("ld.shared.v4.b32 {%0,%1,%2,%3}, [%4];" : "=r"(v.x), "=r"(v.y), "=r"(v.z), "=r"(v.w) : "r"(a) : "memory"); return v; }
__device__ __forceinline__ uint2 lds64(uint32_t a) { uint2 v; asm volatile("ld.shared.v2.b32 {%0,%1}, [%2];" : "=r"(v.x), "=r"(v.y) : "r"(a) : "memory"); return v; }
__device__ __forceinline__ uint32_t lds32(uint32_t a) { uint32_t v; asm volatile("ld.shared.b32 %0, [%1];" : "=r"(v) : "r"(a) : "memory"); return v; }
__device__ __forceinline__ uint32_t pack_bf16(float lo, float hi) { uint32_t r; asm("cvt.rn.bf16x2.f32 %0, %1, %2;" : "=r"(r) : "f"(hi), "f"(lo)); return r; }
__device__ __forceinline__ float bf_lo(uint32_t w) { return __uint_as_float(w << 16); }
__device__ __forceinline__ float bf_hi(uint32_t w) { return __uint_as_float(w & 0xFFFF0000u); }
__device__ __forceinline__ float rbf(float x) { return bf_lo(pack_bf16(x, 0.f)); }
__device__ __forceinline__ float asf(uint32_t u) { return __uint_as_float(u); }
__device__ __forceinline__ uint32_t asu(float f) { return __float_as_uint(f); }
__device__ __forceinline__ float shx(float v, int m) { return __shfl_xor_sync(0xffffffffu, v, m); }
__device__ __forceinline__ uint32_t movm(uint32_t a) { uint32_t o; asm volatile("movmatrix.sync.aligned.m8n8.trans.b16 %0, %1;" : "=r"(o) : "r"(a)); return o; }
__device__ __forceinline__ void ldsm2(uint32_t& a, uint32_t& b, uint32_t addr) { asm volatile("ldmatrix.sync.aligned.m8n8.x2.shared.b16 {%0,%1}, [%2];" : "=r"(a), "=r"(b) : "r"(addr) : "memory"); }
__device__ __forceinline__ void ldsm4t(uint32_t* r, uint32_t addr) { asm volatile("ldmatrix.sync.aligned.m8n8.x4.trans.shared.b16 {%0,%1,%2,%3}, [%4];" : "=r"(r[0]), "=r"(r[1]), "=r"(r[2]), "=r"(r[3]) : "r"(addr) : "memory"); }
__device__ __forceinline__ void stsm4(uint32_t addr, uint32_t a, uint32_t b, uint32_t c, uint32_t d) { asm volatile("stmatrix.sync.aligned.m8n8.x4.shared.b16 [%0], {%1,%2,%3,%4};" ::"r"(addr), "r"(a), "r"(b), "r"(c), "r"(d) : "memory"); }
__device__ __forceinline__ void stsm2(uint32_t addr, uint32_t a, uint32_t b) { asm volatile("stmatrix.sync.aligned.m8n8.x2.shared.b16 [%0], {%1,%2};" ::"r"(addr), "r"(a), "r"(b) : "memory"); }
__device__ __forceinline__ void mma16(float* d, uint32_t a0, uint32_t a1, uint32_t a2, uint32_t a3, uint32_t b0, uint32_t b1) {
  asm volatile("mma.sync.aligned.m16n8k16.row.col.f32.bf16.bf16.f32 {%0,%1,%2,%3},{%4,%5,%6,%7},{%8,%9},{%0,%1,%2,%3};"
               : "+f"(d[0]), "+f"(d[1]), "+f"(d[2]), "+f"(d[3]) : "r"(a0), "r"(a1), "r"(a2), "r"(a3), "r"(b0), "r"(b1));
}
__device__ __forceinline__ void mma16z(float* d, uint32_t a0, uint32_t a1, uint32_t a2, uint32_t a3, uint32_t b0, uint32_t b1) {
  asm volatile("mma.sync.aligned.m16n8k16.row.col.f32.bf16.bf16.f32 {%0,%1,%2,%3},{%4,%5,%6,%7},{%8,%9},{%10,%10,%10,%10};"
               : "=f"(d[0]), "=f"(d[1]), "=f"(d[2]), "=f"(d[3]) : "r"(a0), "r"(a1), "r"(a2), "r"(a3), "r"(b0), "r"(b1), "f"(0.f));
}
__device__ __forceinline__ void mma8(float* d, uint32_t a0, uint32_t a1, uint32_t b0) {
  asm volatile("mma.sync.aligned.m16n8k8.row.col.f32.bf16.bf16.f32 {%0,%1,%2,%3},{%4,%5},{%6},{%0,%1,%2,%3};"
               : "+f"(d[0]), "+f"(d[1]), "+f"(d[2]), "+f"(d[3]) : "r"(a0), "r"(a1), "r"(b0));
}
__device__ __forceinline__ uint32_t pin(uint32_t v) { uint32_t r; asm volatile("shfl.sync.bfly.b32 %0, %1, 0, 31, 0xffffffff;" : "=r"(r) : "r"(v)); return r; }
__device__ __forceinline__ uint32_t pin0(uint32_t v) { uint32_t r; asm volatile("{\n.reg .u32 t;\nor.b32 t, %1, 1;\nbfind.shiftamt.u32 %0, t;\nshr.u32 %0, %0, 5;\n}" : "=r"(r) : "r"(v)); return r; }
__device__ __forceinline__ void mma8z(float* d, uint32_t a0, uint32_t a1, uint32_t b0) {
  asm volatile("mma.sync.aligned.m16n8k8.row.col.f32.bf16.bf16.f32 {%0,%1,%2,%3},{%4,%5},{%6},{%7,%7,%7,%7};"
               : "=f"(d[0]), "=f"(d[1]), "=f"(d[2]), "=f"(d[3]) : "r"(a0), "r"(a1), "r"(b0), "f"(0.f));
}
__device__ __forceinline__ void wg_fence() { asm volatile("wgmma.fence.sync.aligned;" ::: "memory"); }
__device__ __forceinline__ void wg_commit() { asm volatile("wgmma.commit_group.sync.aligned;" ::: "memory"); }
template <int N> __device__ __forceinline__ void wg_wait() { asm volatile("wgmma.wait_group.sync.aligned %0;" ::"n"(N) : "memory"); }
template <int N> __device__ __forceinline__ void fence_regs(float* d) {
#pragma unroll
  for (int k = 0; k < N; k++) asm volatile("" : "+f"(d[k])::"memory");
}
__host__ __device__ constexpr uint32_t DLO(uint32_t addr, uint32_t lbo) { return (addr >> 4) | ((lbo >> 4) << 16); }
__host__ __device__ constexpr uint32_t DHI(uint32_t sbo, uint32_t swz) { return (sbo >> 4) | (swz << 30); }
template <int N>
__device__ __forceinline__ void wait_flags(const void* base, const uint32_t V, const int lane) {
  const unsigned char* p = (const unsigned char*)base + lane * 32;
  const unsigned char* p2 = p + (lane < N - 32 ? 1024 : 0);
  uint32_t a0 = ldg_rlx32(p), a1 = N > 32 ? ldg_rlx32(p2) : V;
  __nanosleep(POLL_GAP);
  int n = 0;
#pragma unroll 1
  while (true) {
    const uint32_t b0 = ldg_rlx32(p), b1 = N > 32 ? ldg_rlx32(p2) : V;
    if (__all_sync(0xffffffffu, (int)((a0 - V) | (a1 - V)) >= 0)) break;
    a0 = ldg_rlx32(p); a1 = N > 32 ? ldg_rlx32(p2) : V;
    if (__all_sync(0xffffffffu, (int)((b0 - V) | (b1 - V)) >= 0)) break;
    if (++n > SPIN) TIMEOUT(__LINE__)
  }
}
__device__ __forceinline__ uint32_t ftag(float v, uint32_t par) { return (asu(v) & ~1u) | par; }
__device__ __forceinline__ uint32_t selu(uint32_t c, uint32_t a, uint32_t b) { uint32_t r; asm("{\n.reg .pred p;\nsetp.ne.u32 p, %1, 0;\nselp.b32 %0, %2, %3, p;\n}" : "=r"(r) : "r"(c), "r"(a), "r"(b)); return r; }
__device__ __forceinline__ float self(uint32_t c, float a, float b) { return asf(selu(c, asu(a), asu(b))); }
__device__ __forceinline__ uint32_t orx(uint32_t acc, uint32_t a, uint32_t ref) { uint32_t r; asm("lop3.b32 %0, %1, %2, %3, 0xF6;" : "=r"(r) : "r"(acc), "r"(a), "r"(ref)); return r; }
__device__ __forceinline__ uint32_t fkey(float r) {
  uint32_t u = asu(r);
  u = (u & 0x80000000u) ? ~u : (u | 0x80000000u);
  return (r == r) ? u : 0u;
}
__host__ __device__ constexpr int GI(int part, int t) { return t < 8 ? part * 8 + t : 24 + part; }

__device__ __forceinline__ void wgmma_ss_216(float* d, uint32_t al, uint32_t ah, uint32_t bl, uint32_t bh) {
  asm volatile("{\n.reg .b64 da, db;\nmov.b64 da, {%108, %109};\nmov.b64 db, {%110, %111};\n"
      "wgmma.mma_async.sync.aligned.m64n216k16.f32.bf16.bf16 {"
      "%0,%1,%2,%3,%4,%5,%6,%7,%8,%9,%10,%11,%12,%13,%14,%15,%16,%17,%18,%19,%20,%21,%22,%23,%24,%25,%26,"
      "%27,%28,%29,%30,%31,%32,%33,%34,%35,%36,%37,%38,%39,%40,%41,%42,%43,%44,%45,%46,%47,%48,%49,%50,%51,%52,%53,"
      "%54,%55,%56,%57,%58,%59,%60,%61,%62,%63,%64,%65,%66,%67,%68,%69,%70,%71,%72,%73,%74,%75,%76,%77,%78,%79,%80,"
      "%81,%82,%83,%84,%85,%86,%87,%88,%89,%90,%91,%92,%93,%94,%95,%96,%97,%98,%99,%100,%101,%102,%103,%104,%105,%106,%107"
      "}, da, db, 1, 1, 1, 0, 1;\n}\n"
      : "+f"(d[0]), "+f"(d[1]), "+f"(d[2]), "+f"(d[3]), "+f"(d[4]), "+f"(d[5]), "+f"(d[6]), "+f"(d[7]), "+f"(d[8]),
        "+f"(d[9]), "+f"(d[10]), "+f"(d[11]), "+f"(d[12]), "+f"(d[13]), "+f"(d[14]), "+f"(d[15]), "+f"(d[16]), "+f"(d[17]),
        "+f"(d[18]), "+f"(d[19]), "+f"(d[20]), "+f"(d[21]), "+f"(d[22]), "+f"(d[23]), "+f"(d[24]), "+f"(d[25]), "+f"(d[26]),
        "+f"(d[27]), "+f"(d[28]), "+f"(d[29]), "+f"(d[30]), "+f"(d[31]), "+f"(d[32]), "+f"(d[33]), "+f"(d[34]), "+f"(d[35]),
        "+f"(d[36]), "+f"(d[37]), "+f"(d[38]), "+f"(d[39]), "+f"(d[40]), "+f"(d[41]), "+f"(d[42]), "+f"(d[43]), "+f"(d[44]),
        "+f"(d[45]), "+f"(d[46]), "+f"(d[47]), "+f"(d[48]), "+f"(d[49]), "+f"(d[50]), "+f"(d[51]), "+f"(d[52]), "+f"(d[53]),
        "+f"(d[54]), "+f"(d[55]), "+f"(d[56]), "+f"(d[57]), "+f"(d[58]), "+f"(d[59]), "+f"(d[60]), "+f"(d[61]), "+f"(d[62]),
        "+f"(d[63]), "+f"(d[64]), "+f"(d[65]), "+f"(d[66]), "+f"(d[67]), "+f"(d[68]), "+f"(d[69]), "+f"(d[70]), "+f"(d[71]),
        "+f"(d[72]), "+f"(d[73]), "+f"(d[74]), "+f"(d[75]), "+f"(d[76]), "+f"(d[77]), "+f"(d[78]), "+f"(d[79]), "+f"(d[80]),
        "+f"(d[81]), "+f"(d[82]), "+f"(d[83]), "+f"(d[84]), "+f"(d[85]), "+f"(d[86]), "+f"(d[87]), "+f"(d[88]), "+f"(d[89]),
        "+f"(d[90]), "+f"(d[91]), "+f"(d[92]), "+f"(d[93]), "+f"(d[94]), "+f"(d[95]), "+f"(d[96]), "+f"(d[97]), "+f"(d[98]),
        "+f"(d[99]), "+f"(d[100]), "+f"(d[101]), "+f"(d[102]), "+f"(d[103]), "+f"(d[104]), "+f"(d[105]), "+f"(d[106]), "+f"(d[107])
      : "r"(al), "r"(ah), "r"(bl), "r"(bh));
}
__device__ __forceinline__ void wgmma_ss_72(float* d, uint32_t al, uint32_t ah, uint32_t bl, uint32_t bh) {
  asm volatile("{\n.reg .b64 da, db;\nmov.b64 da, {%36, %37};\nmov.b64 db, {%38, %39};\n"
      "wgmma.mma_async.sync.aligned.m64n72k16.f32.bf16.bf16 {"
      "%0,%1,%2,%3,%4,%5,%6,%7,%8,%9,%10,%11,%12,%13,%14,%15,%16,%17,%18,%19,%20,%21,%22,%23,%24,%25,%26,"
      "%27,%28,%29,%30,%31,%32,%33,%34,%35"
      "}, da, db, 1, 1, 1, 0, 1;\n}\n"
      : "+f"(d[0]), "+f"(d[1]), "+f"(d[2]), "+f"(d[3]), "+f"(d[4]), "+f"(d[5]), "+f"(d[6]), "+f"(d[7]), "+f"(d[8]),
        "+f"(d[9]), "+f"(d[10]), "+f"(d[11]), "+f"(d[12]), "+f"(d[13]), "+f"(d[14]), "+f"(d[15]), "+f"(d[16]), "+f"(d[17]),
        "+f"(d[18]), "+f"(d[19]), "+f"(d[20]), "+f"(d[21]), "+f"(d[22]), "+f"(d[23]), "+f"(d[24]), "+f"(d[25]), "+f"(d[26]),
        "+f"(d[27]), "+f"(d[28]), "+f"(d[29]), "+f"(d[30]), "+f"(d[31]), "+f"(d[32]), "+f"(d[33]), "+f"(d[34]), "+f"(d[35])
      : "r"(al), "r"(ah), "r"(bl), "r"(bh));
}
template <uint32_t BH>
__device__ __forceinline__ void wgmma_rs_216(float* d, uint32_t a0, uint32_t a1, uint32_t a2, uint32_t a3, uint32_t bl) {
  asm volatile("{\n.reg .b64 db;\nmov.b64 db, {%112, %113};\n"
      "wgmma.mma_async.sync.aligned.m64n216k16.f32.bf16.bf16 {"
      "%0,%1,%2,%3,%4,%5,%6,%7,%8,%9,%10,%11,%12,%13,%14,%15,%16,%17,%18,%19,%20,%21,%22,%23,%24,%25,%26,"
      "%27,%28,%29,%30,%31,%32,%33,%34,%35,%36,%37,%38,%39,%40,%41,%42,%43,%44,%45,%46,%47,%48,%49,%50,%51,%52,%53,"
      "%54,%55,%56,%57,%58,%59,%60,%61,%62,%63,%64,%65,%66,%67,%68,%69,%70,%71,%72,%73,%74,%75,%76,%77,%78,%79,%80,"
      "%81,%82,%83,%84,%85,%86,%87,%88,%89,%90,%91,%92,%93,%94,%95,%96,%97,%98,%99,%100,%101,%102,%103,%104,%105,%106,%107"
      "}, {%108,%109,%110,%111}, db, 1, 1, 1, 1;\n}\n"
      : "+f"(d[0]), "+f"(d[1]), "+f"(d[2]), "+f"(d[3]), "+f"(d[4]), "+f"(d[5]), "+f"(d[6]), "+f"(d[7]), "+f"(d[8]),
        "+f"(d[9]), "+f"(d[10]), "+f"(d[11]), "+f"(d[12]), "+f"(d[13]), "+f"(d[14]), "+f"(d[15]), "+f"(d[16]), "+f"(d[17]),
        "+f"(d[18]), "+f"(d[19]), "+f"(d[20]), "+f"(d[21]), "+f"(d[22]), "+f"(d[23]), "+f"(d[24]), "+f"(d[25]), "+f"(d[26]),
        "+f"(d[27]), "+f"(d[28]), "+f"(d[29]), "+f"(d[30]), "+f"(d[31]), "+f"(d[32]), "+f"(d[33]), "+f"(d[34]), "+f"(d[35]),
        "+f"(d[36]), "+f"(d[37]), "+f"(d[38]), "+f"(d[39]), "+f"(d[40]), "+f"(d[41]), "+f"(d[42]), "+f"(d[43]), "+f"(d[44]),
        "+f"(d[45]), "+f"(d[46]), "+f"(d[47]), "+f"(d[48]), "+f"(d[49]), "+f"(d[50]), "+f"(d[51]), "+f"(d[52]), "+f"(d[53]),
        "+f"(d[54]), "+f"(d[55]), "+f"(d[56]), "+f"(d[57]), "+f"(d[58]), "+f"(d[59]), "+f"(d[60]), "+f"(d[61]), "+f"(d[62]),
        "+f"(d[63]), "+f"(d[64]), "+f"(d[65]), "+f"(d[66]), "+f"(d[67]), "+f"(d[68]), "+f"(d[69]), "+f"(d[70]), "+f"(d[71]),
        "+f"(d[72]), "+f"(d[73]), "+f"(d[74]), "+f"(d[75]), "+f"(d[76]), "+f"(d[77]), "+f"(d[78]), "+f"(d[79]), "+f"(d[80]),
        "+f"(d[81]), "+f"(d[82]), "+f"(d[83]), "+f"(d[84]), "+f"(d[85]), "+f"(d[86]), "+f"(d[87]), "+f"(d[88]), "+f"(d[89]),
        "+f"(d[90]), "+f"(d[91]), "+f"(d[92]), "+f"(d[93]), "+f"(d[94]), "+f"(d[95]), "+f"(d[96]), "+f"(d[97]), "+f"(d[98]),
        "+f"(d[99]), "+f"(d[100]), "+f"(d[101]), "+f"(d[102]), "+f"(d[103]), "+f"(d[104]), "+f"(d[105]), "+f"(d[106]), "+f"(d[107])
      : "r"(a0), "r"(a1), "r"(a2), "r"(a3), "r"(bl), "n"(BH));
}

struct Ctx {
  int i, j, cta;
};
#define TSTAMP(k) do {} while (0)
#define PSTAMP(k) do {} while (0)
#define PROF_DUMP() do {} while (0)
#define PROF_END() do {} while (0)
#define GSTAMP(k) do {} while (0)
#define CSTAMP(k) STAMPIF(1, L * 40 + p * 20 + (k))

__device__ __forceinline__ int ffn_c32(int cta) { return 32 * cta; }
__device__ __forceinline__ int ffn_c8(int cta) { return 4096 + 8 * (cta >> 1); }
__device__ __forceinline__ void load_gu(const Params& P, const int cta_, const int mat, const int b, const uint32_t bar) {
  const int cta = cta_;
  w_tma2d(sb + SM_G + mat * 46080 + b * 6144, &P.mg + mat, ffn_c32(cta), b * 96, bar);
  if (cta & 1) w_tma2d(sb + SM_G + mat * 46080 + 36864 + b * 1536, &P.mg8 + mat, ffn_c8(cta), b * 96, bar);
}

struct Winner { float r, m, rstd; int ci, rr; };

__device__ __forceinline__ Winner poll_winner(const void* p, uint4 v, const uint32_t tg) {
  int n = 0;
#pragma unroll 1
  while (!__all_sync(0xffffffffu, ((v.y ^ (tg << 6)) >> 6) == 0)) {
    rld128(v, p);
    if (++n > SPIN) TIMEOUT(__LINE__)
  }
  uint32_t key = fkey(asf(v.x));
  uint32_t mx = __reduce_max_sync(0xffffffffu, key);
  int src = __ffs(__ballot_sync(0xffffffffu, key == mx)) - 1;
  Winner w;
  w.ci = src;
  w.r = asf(__shfl_sync(0xffffffffu, v.x, src));
  w.rr = (int)__shfl_sync(0xffffffffu, v.y, src) & 63;
  w.m = asf(__shfl_sync(0xffffffffu, v.z, src));
  w.rstd = asf(__shfl_sync(0xffffffffu, v.w, src));
  return w;
}

__device__ __forceinline__ float2 row_stats(const Params& P, const int r, const int lane) {
  const unsigned char* src = (const unsigned char*)P.x + (((r & ~127) + 2 * (r & 63) + ((r >> 6) & 1)) * 1152 + (lane & 15) * 16);
  uint4 v[4];
#pragma unroll
  for (int m = 0; m < 4; m++) v[m] = ldg_nc128(src + m * 256);
  uint2 v4;
  asm volatile("ld.global.nc.v2.b32 {%0,%1}, [%2];" : "=r"(v4.x), "=r"(v4.y) : "l"(src + (1024 - (lane & 15) * 8)));
  nb_arrive(NB_START, 288 + pin0(v4.x));
  const float sft = __shfl_sync(0xffffffffu, bf_lo(v[0].x), lane & 16);
  float s1 = 0.f, s2 = 0.f, s3 = 0.f;
#pragma unroll
  for (int e = 0; e < 18; e++) {
    const uint32_t u = e < 16 ? (&v[0].x)[e] : (&v4.x)[e - 16];
    const float d0 = bf_lo(u) - sft, d1 = bf_hi(u) - sft;
    s1 += d0 + d1; s2 = fmaf(d0, d0, s2); s3 = fmaf(d1, d1, s3);
  }
  s2 += s3;
#pragma unroll
  for (int o = 1; o < 16; o <<= 1) { s1 += shx(s1, o); s2 += shx(s2, o); }
  s1 *= (1.f / 576.f);
  return make_float2(s1 + sft, rsq(fmaxf(s2 * (1.f / 576.f) - s1 * s1, 0.f) + EPS));
}

struct Unit { uint4 v[3]; };
__device__ __forceinline__ Unit unit_load(const unsigned char* src) {
  Unit u;
#pragma unroll
  for (int m = 0; m < 3; m++) u.v[m] = ldg_nc128(src + m * 48);
  return u;
}
__device__ __forceinline__ uint32_t unit_store(unsigned char* sc, const Unit& u, const int lane, const uint32_t o0, const uint32_t o1, const uint32_t o2) {
  stg128(sc + o0, u.v[0].x, u.v[0].y, u.v[0].z, u.v[0].w);
  stg128(sc + o1, u.v[1].x, u.v[1].y, u.v[1].z, u.v[1].w);
  stg128(sc + o2, u.v[2].x, u.v[2].y, u.v[2].z, u.v[2].w);
  return ldg_rlx32(sc + ((lane & 3) == 0 ? o0 : (lane & 3) == 1 ? o1 : o2));
}

__device__ __forceinline__ void store_rows(const uint32_t stg, unsigned char* obase, const int skip, const int lane) {
#pragma unroll
  for (int m = 0; m < 5; m++) {
    const int e = lane + 32 * m, r = (e * 57) >> 9;
    const uint4 v = lds128(stg + min(e, 143) * 16);
    if (e < 144 && r != skip) *(uint4*)(obase + (r * (2304 - 144) + e * 16)) = v;
  }
}

__device__ __forceinline__ void consumer_role(const Ctx& cx, const Params& P, const unsigned char* smem, const int p, const int w, const int lane_) {
  int lane = lane_;
#define g (lane >> 2)
#define q (lane & 3)
#define first_lane (lane == 0)
  const int i = cx.i, j = cx.j, ip = i * 2 + p;
  unsigned char* const sc = (unsigned char*)P.sc;
  float m_lo = 0.f, m_hi = 0.f, rs_lo = 0.f, rs_hi = 0.f;
  nb_sync(NB_ORD, 384);
  uint32_t T = ldg_rlx32(P.sc->cflag[ip][j * 4 + w]);
  if (X_DELAY) { const int c0 = clock(); while ((int)(clock() - c0) < X_DELAY + (p * 4 + w) * X_STEP) {} }
  {
    const int t = min(w * 32 + lane, 95);
    uint32_t u0 = 0, u1 = 0, u2 = 0, u = 0;
    if (p == 0) {
      u0 = ldg_nc32((const uint32_t*)P.wr + t); u1 = ldg_nc32((const uint32_t*)P.wr + 96 + t); u2 = ldg_nc32((const uint32_t*)P.wr + 192 + t);
      u = ldg_nc32((const uint32_t*)P.wr + 36 * j + min(t, 35));
    }
    const int r = cx.cta * 16 + (p * 4 + w) * 2 + (lane >> 4);
    const float2 st = row_stats(P, r, lane);
    T = __shfl_sync(0xffffffffu, (T >> 3) + 1, 0);
    if ((lane & 15) == 0) stg128(sc + (OFF(st0) + r * 16), asu(st.x), asu(st.y), T, 0u);
    STAMPIF(1, 111);
    if (p == 0) {
      float s = (bf_lo(u0) + bf_hi(u0)) + (bf_lo(u1) + bf_hi(u1)) + (bf_lo(u2) + bf_hi(u2));
#pragma unroll
      for (int o = 1; o < 32; o <<= 1) s += shx(s, o);
      stsf(sb + SM_WR + 288 + w * 4, s);
      sts64(sb + SM_WR + min(t, 35) * 8, u << 16, u & 0xFFFF0000u);
    }
  }
#pragma unroll 1
  for (int L = 0; L < 2; L++) {
    lane = pin(lane);
    const uint32_t tg = 2 * T + L;
    float c_lo = 0.f, c_hi = 0.f;
    bool sel_lo = false, sel_hi = false;
    float acc[108];
#pragma unroll
    for (int k = 0; k < 108; k++) acc[k] = 0.f;
    fence_regs<108>(acc);
    {
      const uint32_t ah = L == 0 ? DHI(1024, 1) : DHI(128, 0);
      const uint32_t astep = L == 0 ? 2 : 128;
      const uint32_t a0 = (L == 0 ? DLO(sb + SM_A, 16) : DLO(sb + SM_A, 1024)) + p * 512;
      constexpr uint32_t bh = DHI(512, 0);
      if (L == 1) {
        const float ul = 1.f + rs_lo, uh = 1.f + rs_hi;
        const float vl = fmaxf(rcp(rs_lo * rs_lo) - EPS, 0.f), vh = fmaxf(rcp(rs_hi * rs_hi) - EPS, 0.f);
        c_lo = ul * rsq(vl * ul * ul + EPS);
        c_hi = uh * rsq(vh * uh * uh + EPS);
      }
      if (L == 1) mbar_wait(sb + BAR_AFULL + p * 8, 0);
      mbar_wait(sb + BAR_FULL, 0);
      if (L == 1) nb_sync(NB_FFN2, 352);
      CSTAMP(0); GSTAMP(120 + 2 * L);
      uint32_t e0 = 0, e1 = 0;
      bool prepped = false, gone = false;
      auto prep_ext = [&]() {
        const int row = p * 64 + w * 16 + g;
        if (L == 0) {
          const uint2 u0 = lds64(sb + SM_R + row * 8), u1 = lds64(sb + SM_R + row * 8 + 64);
          m_lo = asf(u0.x); c_lo = asf(u0.y); m_hi = asf(u1.x); c_hi = asf(u1.y);
        } else {
          const uint4 sv = lds128(sb + SM_SEL);
          sel_lo = (int)sv.x == row; sel_hi = (int)sv.x == row + 8;
          if (sel_lo) { m_lo = asf(sv.z); c_lo = asf(sv.w); }
          if (sel_hi) { m_hi = asf(sv.z); c_hi = asf(sv.w); }
        }
        const float hl = rbf(-m_lo), hh = rbf(-m_hi);
        const uint32_t em = selu(lane & 1, 0x0000FFFFu, 0xFFFFFFFFu);
        e0 = selu(lane & 2, selu(sel_lo && !(lane & 1), 0x3F803F80u, 0u), pack_bf16(hl, -m_lo - hl) & em);
        e1 = selu(lane & 2, selu(sel_hi && !(lane & 1), 0x3F803F80u, 0u), pack_bf16(hh, -m_hi - hh) & em);
      };
      bool pend = false;
#pragma unroll 1
      for (int r = 0; r < 3; r++) {
#pragma unroll
        for (int h = 0; h < 6; h++) {
          const uint32_t al = a0 + (h >> 1) * 1024 + (h & 1) * 2 * astep, bl = DLO(sb + SM_B, 128) + h * 864;
          const uint32_t nb = sb + BAR_FULL + ((h + 1) % 6) * 8, np = (r + (h == 5)) & 1;
          TSTAMP((6 * r + h) * 2);
          wg_fence();
          wgmma_ss_216(acc, al, ah, bl, bh);
          wgmma_ss_216(acc, al + astep, ah, bl + 16, bh);
          wg_commit();
          if (h == 5 && r == 2) break;
          const uint32_t ok = mbar_test(nb, np);
          if ((h == 1 || h == 3) && r == 0 && L == 1) mbar_wait(sb + BAR_AFULL + (h + 1 + p) * 8, 0);
          if (h == 0 && r == 1 && L == 0) {
          if (lane < 16) stg128(sc + (OFF(stats) + (ip * 4 + w) * 2048 + j * 256 + lane * 16), 0u, 0u, 0u, 0u);
          if (w == 3 && i < 15 && lane < 28) {
#pragma unroll
            for (int e = 0; e < 6; e++) stg128(sc + (OFF(halo) + ((ip + 2) * 8 + j) * 2688 + lane * 16) + e * 448, 0u, 0u, 0u, 0u);
          }
          if (w == 0 && lane < 2) stg128(sc + (OFF(cand) + (j * 32 + ip) * (CAND_W * 4) + lane * 16), 0u, 0u, 0u, 0u);
          }
          wg_wait<1>();
          if (first_lane && pend) mbar_arrive(sb + BAR_EMPTY + ((h + 5) % 6) * 8);
          pend = true;
          const bool hold = h == HOLD_C % 6 && r == HOLD_C / 6 && p == 1;
          if (hold || (!ok && !mbar_test(nb, np))) {
            wg_wait<0>();
            if (first_lane) mbar_arrive(sb + BAR_EMPTY + h * 8);
            pend = false;
            TSTAMP((6 * r + h) * 2 + 1);
            mbar_wait(nb, np);
            if (hold) {
              if (mbar_test(sb + BAR_FIX + 8, L)) { prep_ext(); prepped = true; }
              nb_sync(NB_STAG, 256);
            }
          }
        }
      }
      if (!prepped) {
        if (p == 0 && !gone && !mbar_test(sb + BAR_FIX, L)) { nb_arrive(NB_STAG, 256); gone = true; }
        mbar_wait(sb + BAR_FIX + p * 8, L);
        prep_ext();
      }
      wg_fence();
      wgmma_rs_216<DHI(128, 0)>(acc, e0, e1, 0u, 0u, DLO(sb + SM_BEXT, 0));
      wg_commit();
      if (p == 0 && !gone) nb_arrive(NB_STAG, 256);
      wg_wait<2>();
      if (first_lane && pend) mbar_arrive(sb + BAR_EMPTY + 32);
    }
    lane = pin(lane);
    const uint32_t fragoff = ip * 73728 + (9 * j) * 1024 + w * 256 + lane * 4;
    const uint32_t rboff = (min(lane, 17) >> 1) * 1024 + (lane < 18 ? lane & 1 : 0) * 128;
    const uint32_t hl16 = (lane < 4 ? lane : lane - 4) * 16;
    const uint32_t o_halo = pin(OFF(halo) + ((ip + (w == 3 ? 2 : 0)) * 8 + j) * 2688 + hl16);
    const uint32_t o_o = pin(OFF(obuf) + fragoff);
    nb_sync(NB_WG + p, 128);
    if ((o_halo | o_o) == 0xFFFFFFFFu) __trap();
    wg_wait<0>();
    fence_regs<108>(acc);
    if (first_lane) mbar_arrive(sb + BAR_EMPTY + 40);
    CSTAMP(1); GSTAMP(121 + 2 * L);
    {
      uint32_t Kh[9], Vh[9], Kl[9], Vl[9], Kx[9], Vx[9], Ql[9], Qh[9];
#pragma unroll
      for (int t = 0; t < 9; t++) {
        Kh[t] = pack_bf16(acc[4 * GI(1, t) + 2] * c_hi, acc[4 * GI(1, t) + 3] * c_hi);
        Vh[t] = pack_bf16(acc[4 * GI(2, t) + 2] * c_hi, acc[4 * GI(2, t) + 3] * c_hi);
        Ql[t] = pack_bf16(acc[4 * GI(0, t)], acc[4 * GI(0, t) + 1]);
        Qh[t] = pack_bf16(acc[4 * GI(0, t) + 2], acc[4 * GI(0, t) + 3]);
      }
      const uint32_t hbuf = sb + SM_A + p * 8192 + w * 2688 + hl16;
      if (w < 3) {
        if (lane >= 4) {
#pragma unroll
          for (int e = 0; e < 4; e++) sts128(hbuf + e * 448, Kh[2 * e], Kh[2 * e + 1], Vh[e], tg);
          sts128(hbuf + 4 * 448, Kh[8], Vh[4], Vh[5], tg);
          sts128(hbuf + 5 * 448, Vh[6], Vh[7], Vh[8], tg);
        }
      } else if (i < 15 && lane >= 4) {
#pragma unroll
        for (int e = 0; e < 4; e++) stg128(sc + o_halo + e * 448, Kh[2 * e], Kh[2 * e + 1], Vh[e], tg);
        stg128(sc + o_halo + 4 * 448, Kh[8], Vh[4], Vh[5], tg);
        stg128(sc + o_halo + 5 * 448, Vh[6], Vh[7], Vh[8], tg);
      }
      nb_sync(NB_WG + p, 128);
#pragma unroll
      for (int t = 0; t < 9; t++) {
        Kl[t] = pack_bf16(acc[4 * GI(1, t)] * c_lo, acc[4 * GI(1, t) + 1] * c_lo);
      }
      uint32_t dep = (Kl[0] ^ Kl[1] ^ Kl[2]) | (Kl[3] ^ Kl[4] ^ Kl[5]) | (Kl[6] ^ Kl[7] ^ Kl[8]);
      const unsigned char* hp = (w > 0 ? smem + (hbuf - 2688 - sb) : sc + o_halo) + pin0(dep);
      uint4 hv[6];
#pragma unroll
      for (int e = 0; e < 6; e++)
        asm volatile("ld.relaxed.gpu.v4.b32 {%0,%1,%2,%3}, [%4];" : "=r"(hv[e].x), "=r"(hv[e].y), "=r"(hv[e].z), "=r"(hv[e].w) : "l"(hp + e * 448) : "memory");
      CSTAMP(2);
#pragma unroll
      for (int t = 0; t < 9; t++) {
        Vl[t] = pack_bf16(acc[4 * GI(2, t)] * c_lo, acc[4 * GI(2, t) + 1] * c_lo);
        Vl[t] = movm(Vl[t]);
        Vh[t] = movm(Vh[t]);
      }
      uint32_t qa[4][2], qb[4][2];
      float s1[4][4], s2[4][4];
#pragma unroll
      for (int h = 0; h < 4; h++) {
        qa[h][0] = q >= h ? Ql[2 * h] : 0u; qa[h][1] = q >= h ? Qh[2 * h] : 0u;
        qb[h][0] = q <= h ? Ql[2 * h + 2] : 0u; qb[h][1] = q <= h ? Qh[2 * h + 2] : 0u;
      }
      const bool first = (i == 0 && w == 0);
      if (w == 0 && i > 0) {
        int n = 0;
#pragma unroll 1
        while (__any_sync(0xffffffffu, (orx(orx(orx(0, hv[0].w, tg), hv[1].w, tg), hv[2].w, tg) | orx(orx(orx(0, hv[3].w, tg), hv[4].w, tg), hv[5].w, tg)) != 0)) {
#pragma unroll
          for (int e = 0; e < 6; e++) rld128(hv[e], sc + o_halo + e * 448);
          if (++n > SPIN) TIMEOUT(__LINE__)
        }
      }
#pragma unroll
      for (int e = 0; e < 4; e++) { Kx[2 * e] = hv[e].x; Kx[2 * e + 1] = hv[e].y; Vx[e] = hv[e].z; }
      Kx[8] = hv[4].x; Vx[4] = hv[4].y; Vx[5] = hv[4].z; Vx[6] = hv[5].x; Vx[7] = hv[5].y; Vx[8] = hv[5].z;
      CSTAMP(3);
#pragma unroll
      for (int t = 0; t < 9; t++) Vx[t] = movm(Vx[t]);
#pragma unroll
      for (int h = 0; h < 4; h++) { mma8z(s1[h], qb[h][0], qb[h][1], Kl[2 * h + 2]); mma8z(s2[h], qb[h][0], qb[h][1], Kh[2 * h + 2]); }
#pragma unroll
      for (int h = 0; h < 4; h++) {
        mma16(s1[h], qa[h][0], qa[h][1], Ql[2 * h + 1], Qh[2 * h + 1], Kl[2 * h], Kl[2 * h + 1]);
        mma16(s2[h], qa[h][0], qa[h][1], Ql[2 * h + 1], Qh[2 * h + 1], Kh[2 * h], Kh[2 * h + 1]);
      }
      float s0[4][4];
#pragma unroll
      for (int h = 0; h < 4; h++) mma8z(s0[h], qb[h][0], qb[h][1], Kx[2 * h + 2]);
#pragma unroll
      for (int h = 0; h < 4; h++) mma16(s0[h], qa[h][0], qa[h][1], Ql[2 * h + 1], Qh[2 * h + 1], Kx[2 * h], Kx[2 * h + 1]);
      const bool pv0 = 2 * q > g, pv1 = 2 * q + 1 > g;
      const uint32_t PM = (pv0 ? 0x0000FFFFu : 0u) | (pv1 ? 0xFFFF0000u : 0u);
      const float kS = 0.23570226039551584f * 1.4426950408889634f;
      const float sc_lo = c_lo * kS, sc_hi = c_hi * kS;
      float sl[4][2], sh[4][2], ml[4], mh[4];
#pragma unroll
      for (int h = 0; h < 4; h++) {
        sh[h][0] = pv0 ? s1[h][2] : s2[h][2];
        sh[h][1] = pv1 ? s1[h][3] : s2[h][3];
        mh[h] = fmaxf(sh[h][0], sh[h][1]);
        sl[h][0] = pv0 ? (first ? -INFINITY : s0[h][0]) : s1[h][0];
        sl[h][1] = pv1 ? (first ? -INFINITY : s0[h][1]) : s1[h][1];
        ml[h] = fmaxf(sl[h][0], sl[h][1]);
      }
#pragma unroll
      for (int s = 1; s <= 2; s <<= 1) {
        float tl[4], th[4];
#pragma unroll
        for (int h = 0; h < 4; h++) { th[h] = shx(mh[h], s); tl[h] = shx(ml[h], s); }
#pragma unroll
        for (int h = 0; h < 4; h++) { mh[h] = fmaxf(mh[h], th[h]); ml[h] = fmaxf(ml[h], tl[h]); }
      }
      float o[4][3][4], den[4][4];
      uint32_t px[4];
#pragma unroll
      for (int h = 0; h < 4; h++) {
        const float bl = -ml[h] * sc_lo, bh = -mh[h] * sc_hi;
        const uint32_t pl = pack_bf16(ex2(fmaf(sl[h][0], sc_lo, bl)), ex2(fmaf(sl[h][1], sc_lo, bl)));
        const uint32_t ph = pack_bf16(ex2(fmaf(sh[h][0], sc_hi, bh)), ex2(fmaf(sh[h][1], sc_hi, bh)));
        mma8z(den[h], pl, ph, 0x3F803F80u);
        px[h] = pl & PM;
#pragma unroll
        for (int u = 0; u < 3; u++) mma16z(o[h][u], pl & ~PM, ph & PM, 0u, ph & ~PM, Vl[2 * h + u], Vh[2 * h + u]);
      }
#pragma unroll
      for (int h = 0; h < 4; h++)
#pragma unroll
        for (int u = 0; u < 3; u++) mma8(o[h][u], px[h], 0u, Vx[2 * h + u]);
      float il[4], ih[4];
#pragma unroll
      for (int h = 0; h < 4; h++) { il[h] = rcp(den[h][0]); ih[h] = rcp(den[h][2]); }
#pragma unroll
      for (int t = 0; t < 9; t++) {
        const int h = t == 8 ? 3 : t >> 1, u = t == 8 ? 2 : t & 1;
        float v0 = o[h][u][0], v1 = o[h][u][1], v2 = o[h][u][2], v3 = o[h][u][3], kl = il[h], kh = ih[h];
        if (u == 0 && h > 0 && q < h) {
          v0 = o[h - 1][2][0]; v1 = o[h - 1][2][1]; v2 = o[h - 1][2][2]; v3 = o[h - 1][2][3]; kl = il[h - 1]; kh = ih[h - 1];
        }
        stg32(sc + o_o + t * 1024, pack_bf16(v0 * kl, v1 * kl));
        stg32(sc + o_o + t * 1024 + 128, pack_bf16(v2 * kh, v3 * kh));
      }
    }
    CSTAMP(4);
    const uint32_t rbo = ldg_rlx32(sc + (o_o + rboff));
    lane = pin(lane);
    const uint32_t o_x = o_o + (OFF(xbuf) - OFF(obuf)), o_xrb = o_x + rboff;
    const uint32_t o_cf = OFF(cflag) + (ip * 32 + j * 4 + w) * 32 + lane * 4;
    if (L == 1 && first_lane) mbar_arrive(sb + BAR_HDONE + p * 8);
    flag_after(sc + o_cf, rbo, 8 * T + 2 * L, lane < 8);
    STAMPD(asf(rbo), L * 40 + p * 20 + 13);
    uint32_t resid[18];
    mbar_wait(sb + BAR_FULL + 16, 1); mbar_wait(sb + BAR_FULL + 32, 1);
    if (L == 0) {
      const uint32_t ra = sb + SM_A + (2 + p) * 8192 + (w * 16 + (lane & 15)) * 128;
#pragma unroll
      for (int t = 0; t < 9; t++) ldsm2(resid[2 * t], resid[2 * t + 1], ra + ((j + t) >> 3) * 16384 + ((((j + t) ^ lane) & 7) << 4));
      if (first_lane) mbar_arrive(sb + BAR_HDONE + p * 8 + pin0(resid[17]));
    } else {
#pragma unroll
      for (int t = 0; t < 9; t++) { resid[2 * t] = ldg_rlx32(sc + o_x + t * 1024); resid[2 * t + 1] = ldg_rlx32(sc + o_x + t * 1024 + 128); }
    }
    const uint32_t o_st = OFF(stats) + (ip * 4 + w) * 2048;
    const uint32_t o_stw = pin(o_st + j * 256 + (g + 8 * (q & 1)) * 16), o_str = pin(o_st + q * 512 + g * 16);
    const uint32_t o_cand = pin(OFF(cand) + (j * 32 + ip) * (CAND_W * 4) + q * 16);
    const uint32_t o_xc = pin(OFF(xcand) + (ip * 8 + j) * 192 + q * 16);
    float accw[36];
    float wr[18];
#pragma unroll
    for (int t = 0; t < 9; t++) { const uint2 u = lds64(sb + SM_WR + t * 32 + q * 8); wr[2 * t] = asf(u.x); wr[2 * t + 1] = asf(u.y); }
    const uint4 ws4 = lds128(sb + SM_WR + 288);
    const float wsum = asf(pin(asu(asf(ws4.x) + asf(ws4.y) + asf(ws4.z))));
    {
      float ul = 1.f, uh = 1.f, vl = 0.f, vh = 0.f;
      if (L == 1) {
        ul += rs_lo; uh += rs_hi; vl = -m_lo * rs_lo; vh = -m_hi * rs_hi;
        if (sel_lo || sel_hi) {
#pragma unroll
          for (int t = 0; t < 9; t++) {
            const uint32_t z = lds32(sb + SM_X2S + t * 16 + q * 4);
            if (sel_hi) resid[2 * t + 1] = z; else resid[2 * t] = z;
          }
          if (sel_hi) { uh = 1.f; vh = 0.f; } else { ul = 1.f; vl = 0.f; }
        }
        __syncwarp();
      }
#pragma unroll
      for (int t = 0; t < 9; t++) {
        accw[4 * t] = fmaf(bf_lo(resid[2 * t]), ul, vl); accw[4 * t + 1] = fmaf(bf_hi(resid[2 * t]), ul, vl);
        accw[4 * t + 2] = fmaf(bf_lo(resid[2 * t + 1]), uh, vh); accw[4 * t + 3] = fmaf(bf_hi(resid[2 * t + 1]), uh, vh);
      }
    }
    fence_regs<36>(accw);
    mbar_wait(sb + BAR_FULL, 1); mbar_wait(sb + BAR_FULL + 8, 1); mbar_wait(sb + BAR_FULL + 24, 1); mbar_wait(sb + BAR_FULL + 40, 1);
    {
      uint32_t wf = sb + BAR_WFULL + p * 72;
      uint32_t bl = DLO(sb + SM_B, 128);
      uint32_t half = p;
      mbar_wait(wf, L);
      CSTAMP(5);
#pragma unroll 1
      for (int c3 = 0; c3 < 3; c3++) {
        const uint32_t al = DLO(sb + SM_A, 1024) + half * 512;
        const uint32_t ae = sb + BAR_AEMPTY + half * 24;
#pragma unroll
        for (int cc = 0; cc < 3; cc++) {
          TSTAMP(36 + (c3 * 3 + cc) * 2);
          wg_fence();
          wgmma_ss_72(accw, al + cc * 1024, DHI(128, 0), bl + cc * 576, DHI(256, 0));
          wgmma_ss_72(accw, al + cc * 1024 + 128, DHI(128, 0), bl + cc * 576 + 144, DHI(256, 0));
          const uint32_t ok = mbar_test(wf + cc * 8 + 8, L);
          wgmma_ss_72(accw, al + cc * 1024 + 256, DHI(128, 0), bl + cc * 576 + 288, DHI(256, 0));
          wgmma_ss_72(accw, al + cc * 1024 + 384, DHI(128, 0), bl + cc * 576 + 432, DHI(256, 0));
          wg_commit();
          wg_wait<1>();
          if (cc > 0) { if (first_lane) { mbar_arrive(ae + cc * 8 - 8); if (cc == 2) mbar_arrive(sb + BAR_EMPTY + c3 * 16); } }
          else if (first_lane && c3 > 0) { mbar_arrive(sb + BAR_AEMPTY + 40 - half * 24); mbar_arrive(sb + BAR_EMPTY + c3 * 16 - 8); }
          if (!ok && (cc < 2 || c3 < 2)) mbar_wait(wf + cc * 8 + 8, L);
        }
        wf += 24; bl += 1728; half ^= 1;
      }
    }
    wg_wait<0>();
    fence_regs<36>(accw);
    if (first_lane) { mbar_arrive(sb + BAR_AEMPTY + (2 + 3 * p) * 8); mbar_arrive(sb + BAR_EMPTY + 40); }
    CSTAMP(6);
    uint32_t xw[18];
    uint32_t rb = 0;
    if (L == 0 && p == 0) {
#pragma unroll
      for (int t = 0; t < 9; t++) {
        stg32(sc + o_x + t * 1024, pack_bf16(accw[4 * t], accw[4 * t + 1]));
        stg32(sc + o_x + t * 1024 + 128, pack_bf16(accw[4 * t + 2], accw[4 * t + 3]));
      }
      rb = ldg_rlx32(sc + o_xrb);
      fence_regs<36>(accw);
    }
    {
      float a0[2] = {0.f, 0.f}, a1[2] = {0.f, 0.f}, a2[2] = {0.f, 0.f}, b0[2] = {0.f, 0.f}, b1[2] = {0.f, 0.f}, b2[2] = {0.f, 0.f};
#pragma unroll
      for (int t = 0; t < 9; t++) {
#pragma unroll
        for (int e = 0; e < 2; e++) {
          const float x = accw[4 * t + e], y = accw[4 * t + 2 + e];
          a0[e] += x; a1[e] = fmaf(x, x, a1[e]); a2[e] = fmaf(x, wr[2 * t + e], a2[e]);
          b0[e] += y; b1[e] = fmaf(y, y, b1[e]); b2[e] = fmaf(y, wr[2 * t + e], b2[e]);
        }
      }
      const bool od = q & 1;
      const float A0 = a0[0] + a0[1], A1 = a1[0] + a1[1], A2 = a2[0] + a2[1], B0 = b0[0] + b0[1], B1 = b1[0] + b1[1], B2 = b2[0] + b2[1];
      float k0 = od ? B0 : A0, k1 = od ? B1 : A1, k2 = od ? B2 : A2;
      k0 += shx(od ? A0 : B0, 1); k1 += shx(od ? A1 : B1, 1); k2 += shx(od ? A2 : B2, 1);
      k0 += shx(k0, 2); k1 += shx(k1, 2); k2 += shx(k2, 2);
      if (q < 2) stg128(sc + o_stw, asu(k0), asu(k1), asu(k2), tg);
      STAMPD(k0, L * 40 + p * 20 + 14);
    }
#pragma unroll
    for (int t = 0; t < 9; t++) {
      xw[2 * t] = pack_bf16(accw[4 * t], accw[4 * t + 1]);
      xw[2 * t + 1] = pack_bf16(accw[4 * t + 2], accw[4 * t + 3]);
    }
    float r_lo, r_hi;
    {
      if (D_STATS) { const int c0 = clock(); while ((int)(clock() - c0) < D_STATS) {} }
      uint4 u0 = ldg_rlx128(sc + o_str), u1 = ldg_rlx128(sc + o_str + 256), u2 = ldg_rlx128(sc + o_str + 128), u3 = ldg_rlx128(sc + o_str + 384);
      flag_after(sc + o_cf, rb, 8 * T + 1, lane < 8 && L == 0 && p == 0);
      STAMPD(asf(u3.w), L * 40 + p * 20 + 15);
      int n = 0;
#pragma unroll 1
      while (__any_sync(0xffffffffu, orx(orx(orx(orx(0, u0.w, tg), u1.w, tg), u2.w, tg), u3.w, tg) != 0)) {
        rld128(u0, sc + o_str); rld128(u1, sc + o_str + 256); rld128(u2, sc + o_str + 128); rld128(u3, sc + o_str + 384);
        if (++n > SPIN) TIMEOUT(__LINE__)
      }
      float a0 = asf(u0.x) + asf(u1.x), a1 = asf(u0.y) + asf(u1.y), a2 = asf(u0.z) + asf(u1.z);
      float b0 = asf(u2.x) + asf(u3.x), b1 = asf(u2.y) + asf(u3.y), b2 = asf(u2.z) + asf(u3.z);
#pragma unroll
      for (int s = 1; s <= 2; s <<= 1) {
        const float t0 = shx(a0, s), t1 = shx(a1, s), t2 = shx(a2, s), t3 = shx(b0, s), t4 = shx(b1, s), t5 = shx(b2, s);
        a0 += t0; a1 += t1; a2 += t2; b0 += t3; b1 += t4; b2 += t5;
      }
      m_lo = a0 * (1.f / 576.f); m_hi = b0 * (1.f / 576.f);
      rs_lo = rsq(fmaxf(a1 * (1.f / 576.f) - m_lo * m_lo, 0.f) + EPS);
      rs_hi = rsq(fmaxf(b1 * (1.f / 576.f) - m_hi * m_hi, 0.f) + EPS);
      r_lo = (a2 - m_lo * wsum) * rs_lo; r_hi = (b2 - m_hi * wsum) * rs_hi;
    }
    CSTAMP(7);
    int candrow = -1;
    {
      const uint32_t kl = fkey(r_lo), kh = fkey(r_hi);
      const bool hi = kh > kl;
      const uint32_t kb = hi ? kh : kl;
      const uint32_t mx = __reduce_max_sync(0xffffffffu, kb);
      if (first_lane) sts32(sb + SM_BEST + p * 16 + w * 4, mx);
      const uint32_t bal = __ballot_sync(0xffffffffu, kb == mx);
      const bool mine = (bal & ((1u << (lane & 28)) - 1u)) == 0u && kb == mx;
      const uint32_t x0 = hi ? xw[1] : xw[0], x1 = hi ? xw[3] : xw[2], x2 = hi ? xw[5] : xw[4], x3 = hi ? xw[7] : xw[6], x4 = hi ? xw[9] : xw[8];
      const uint32_t x5 = hi ? xw[11] : xw[10], x6 = hi ? xw[13] : xw[12], x7 = hi ? xw[15] : xw[14], x8 = hi ? xw[17] : xw[16];
      nb_sync(NB_WG + p, 128);
      const uint4 bs = lds128(sb + SM_BEST + p * 16);
      const bool best = (w > 0 ? bs.x < mx : true) && (w > 1 ? bs.y < mx : bs.y <= mx) && (w > 2 ? bs.z < mx : bs.z <= mx) && bs.w <= mx;
      if (best && mine) {
        if (q < 2) stg128(sc + o_cand, asu(hi ? r_hi : r_lo), (tg << 6) + (uint32_t)(w * 16 + g + (hi ? 8 : 0)), asu(hi ? m_hi : m_lo), asu(hi ? rs_hi : rs_lo));
        stg128(sc + o_xc, x0, x1, x2, tg);
        stg128(sc + o_xc + 64, x3, x4, x5, tg);
        stg128(sc + o_xc + 128, x6, x7, x8, tg);
      }
      candrow = __reduce_max_sync(0xffffffffu, best && mine ? g + (hi ? 8 : 0) : -1);
    }
    if (L == 0 && p == 1) {
#pragma unroll
      for (int t = 0; t < 9; t++) { stg32(sc + o_x + t * 1024, xw[2 * t]); stg32(sc + o_x + t * 1024 + 128, xw[2 * t + 1]); }
      rb = ldg_rlx32(sc + o_xrb);
    }
    const uint32_t stg = sb + SM_B + p * 13824 + w * 2304;
    unsigned char* obase = (unsigned char*)P.out + ((128 * i + 32 * w + p) * 1152 + 144 * j);
    if (L == 1) {
      const float ul = 1.f + rs_lo, uh = 1.f + rs_hi, vl = -m_lo * rs_lo, vh = -m_hi * rs_hi;
#pragma unroll
      for (int t = 0; t < 9; t++) {
        xw[2 * t] = pack_bf16(fmaf(accw[4 * t], ul, vl), fmaf(accw[4 * t + 1], ul, vl));
        xw[2 * t + 1] = pack_bf16(fmaf(accw[4 * t + 2], uh, vh), fmaf(accw[4 * t + 3], uh, vh));
      }
      mbar_wait(sb + BAR_EMPTY + p * 8, 1);
      const uint32_t sa = stg + (lane & 15) * 144;
#pragma unroll
      for (int t = 0; t < 8; t += 2) stsm4(sa + (lane >> 4) * 16 + t * 16, xw[2 * t], xw[2 * t + 1], xw[2 * t + 2], xw[2 * t + 3]);
      stsm2(sa + 128, xw[16], xw[17]);
      __syncwarp();
      store_rows(stg, obase, candrow, lane);
    }
    CSTAMP(8);
    lane = pin(lane);
    const unsigned char* cp = sc + (OFF(cand) + (j * 32 + lane) * (CAND_W * 4));
    if (p == 0) {
      if (L == 1 && candrow >= 0) {
        const Winner wn = poll_winner(cp, ldg_rlx128(cp), tg);
        if (lane < 9 && wn.ci != ip) *(uint4*)(obase + (candrow * 2304 + lane * 16)) = lds128(stg + candrow * 144 + lane * 16);
      }
    } else {
      const uint32_t gr = w * 144 + (lane & 7) + (lane >> 4) * 8, gm = sb + SM_G + ((lane >> 3) & 1) * 46080;
      const uint32_t ga = gm + gr * 64 + (((lane >> 1) & 3) << 4), gl = gm + 36864 + gr * 16;
#define GADDR(s, u) ((u) < 4 ? (ga ^ ((u) << 4)) + (s) * 1024 : gl + (s) * 256)
      uint32_t wf[NPRE][5][4];
      mbar_wait(sb + BAR_GU, 0);
#pragma unroll
      for (int s = 0; s < NPRE - 2; s++)
#pragma unroll
        for (int u = 0; u < 5; u++) ldsm4t(wf[s][u], GADDR(s, u));
      const uint4 c0 = ldg_rlx128(cp);
#pragma unroll
      for (int s = NPRE - 2; s < NPRE; s++)
#pragma unroll
        for (int u = 0; u < 5; u++) ldsm4t(wf[s][u], GADDR(s, u));
      flag_after(sc + o_cf, rb, 8 * T + 1, lane < 8 && L == 0);
      const Winner wn = poll_winner(cp, c0, tg);
      if (w == 0 && first_lane) sts128(sb + SM_WIN, asu(wn.r), asu(wn.m), asu(wn.rstd), (uint32_t)(wn.ci * 64 + wn.rr));
      CSTAMP(9);
      if (L == 1 && candrow >= 0 && lane < 9 && wn.ci != ip) *(uint4*)(obase + (candrow * 2304 + lane * 16)) = lds128(stg + candrow * 144 + lane * 16);
      {
        uint32_t hb[18];
        const unsigned char* xc = sc + (OFF(xcand) + wn.ci * 1536 + q * 16);
        const int fp = min(cx.cta / 3, 23);
        uint4 u[7];
        int n = 0;
#pragma unroll 1
        while (true) {
          uint32_t d = 0;
#pragma unroll
          for (int e = 0; e < 7; e++) u[e] = ldg_rlx128(xc + (e < 6 ? w * 384 + e * 64 : fp * 64));
#pragma unroll
          for (int e = 0; e < 7; e++) d = orx(d, u[e].w, tg);
          if (__all_sync(0xffffffffu, d == 0)) break;
          if (++n > SPIN) TIMEOUT(__LINE__)
        }
        if (L == 0 && w == 0 && first_lane) mbar_arrive(sb + BAR_ST + pin0(u[0].x));
#pragma unroll
        for (int e = 0; e < 6; e++) { hb[3 * e] = u[e].x; hb[3 * e + 1] = u[e].y; hb[3 * e + 2] = u[e].z; }
        if (w == 0) sts128(sb + SM_XW + q * 16, u[6].x, u[6].y, u[6].z, u[6].w);
        const float nb = -wn.m * wn.rstd;
#pragma unroll
        for (int b = 0; b < 18; b++) hb[b] = pack_bf16(fmaf(bf_lo(hb[b]), wn.rstd, nb), fmaf(bf_hi(hb[b]), wn.rstd, nb));
        CSTAMP(10);
        float d[5][4];
#pragma unroll
        for (int u = 0; u < 5; u++) d[u][0] = d[u][1] = d[u][2] = d[u][3] = 0.f;
#pragma unroll
        for (int s = 0; s < 9; s++) {
#pragma unroll
          for (int u = 0; u < 5; u++) {
            uint32_t* f = wf[s % NPRE][u];
            mma16(d[u], f[0], f[1], f[2], f[3], hb[2 * s], hb[2 * s + 1]);
            if (s + NPRE < 9) ldsm4t(f, GADDR(s + NPRE, u));
          }
        }
        if (q == 0) {
#pragma unroll
          for (int u = 0; u < 5; u++) sts64(sb + R_FPART + w * 320 + (u * 8 + g) * 8, asu(d[u][0]), asu(d[u][2]));
        }
        nb_arrive(NB_FFN, 224);
        CSTAMP(11);
      }
    }
  }
  STAMPIF(w == 0 && lane == 0, 40 + p * 20 + 12);
  PROF_DUMP();
#undef g
#undef q
#undef first_lane
}

__device__ __forceinline__ void load_wo_a(const Ctx& cx, const Params& P, const uint32_t T, const int L, const int p, const int lane) {
  const unsigned char* src = P.sc->obuf[cx.i * 2 + p];
#pragma unroll
  for (int c = 0; c < 9; c++) w_expect(sb + BAR_WFULL + (9 * p + c) * 8, 8192);
  mbar_wait(sb + BAR_HDONE + p * 8, L);
  wait_flags<32>(P.sc->cflag[cx.i * 2 + p], 8 * T + 2 * L, lane);
  fence_async_glob();
  STAMP(100 + L * 2 + p);
#pragma unroll
  for (int c = 0; c < 9; c++) {
    const int e = 9 * p + c, s = e % 6;
    if (e == 3) mbar_wait(sb + BAR_HDONE + 8, L);
    if (e >= 6) mbar_wait(sb + BAR_AEMPTY + s * 8, (L ^ (e / 6) ^ 1) & 1);
    w_bulk(sb + SM_A + (2 * (s % 3) + s / 3) * 8192, src + c * 8192, 8192, sb + BAR_WFULL + e * 8);
    PSTAMP(48 + L * 36 + 18 + e);
  }
}

__device__ __forceinline__ void finalize_row(const Params& P, const Winner& wn, const uint32_t T, const int L, const int grp, const int a, const int lane) {
  const unsigned char* yp = (const unsigned char*)P.sc->ypart[grp] + (a * 32 + lane) * 16;
  const uint32_t par = L ^ 1;
  if (L == 0 && D_Y0) { const int c0 = clock(); while ((int)(clock() - c0) < D_Y0) {} }
  uint4 u0 = ldg_rlx128(yp), u1 = ldg_rlx128(yp + 1536), u2 = make_uint4(par, 0, 0, 0);
  if (a < 2) rld128(u2, yp + 3072);
  const int col = lane & 7;
  const uint32_t xw = lds32(sb + SM_XW + (col >> 1) * 16 + (grp % 3) * 4);
  const float xsel = (col & 1) ? bf_hi(xw) : bf_lo(xw);
  const float sg = rbf(rcp(1.f + ex2(-1.4426950408889634f * rbf(wn.r))));
  const float h = rbf((xsel - wn.m) * wn.rstd);
  unsigned char* dst = L == 0 ? (unsigned char*)P.sc->xsel + (((lane >> 3) & 1) * 576 + grp * 8 + col) * 4
                              : (unsigned char*)P.out + ((128 * (wn.ci >> 1) + 2 * wn.rr + (wn.ci & 1)) * 576 + grp * 8 + col) * 2;
  int n = 0;
#pragma unroll 1
  while (__any_sync(0xffffffffu, orx(orx(orx(0, u0.x, par), u1.x, par), u2.x, par) & 1)) {
    rld128(u0, yp); rld128(u1, yp + 1536);
    if (a < 2) rld128(u2, yp + 3072);
    if (++n > SPIN) TIMEOUT(__LINE__)
  }
  const float s0 = asf(u0.x) + asf(u1.x) + asf(u2.x), s1 = asf(u0.y) + asf(u1.y) + asf(u2.y);
  const float s2 = asf(u0.z) + asf(u1.z) + asf(u2.z), s3 = asf(u0.w) + asf(u1.w) + asf(u2.w);
  const float k0 = self(lane & 2, s2, s0) + shx(self(lane & 2, s0, s2), 2), k1 = self(lane & 2, s3, s1) + shx(self(lane & 2, s1, s3), 2);
  float k = self(lane & 4, k1, k0) + shx(self(lane & 4, k0, k1), 4);
  k += shx(k, 8); k += shx(k, 16);
  if (lane < 8) stsf(sb + SM_YRED + ((lane & 1) * 4 + (lane & 2) + (lane >> 2)) * 16 + a * 4, k);
  nb_sync(NB_AUX, 96);
  if (a == 0) {
    const uint4 yy = lds128(sb + SM_YRED + col * 16);
    const float xn = rbf(xsel + rbf(h + rbf(rbf(asf(yy.x) + asf(yy.y) + asf(yy.z)) * sg)));
    if (L == 0) { if (lane < 16) stg32(dst, ftag(lane < 8 ? xn : xn - xsel, T & 1)); }
    else if (lane < 8) *(unsigned short*)dst = (unsigned short)(asu(xn) >> 16);
  }
}

__device__ __forceinline__ void aux_role(const Ctx& cx, const Params& P, const int a, const int lane_, const Unit& h0, const Unit& h1, const uint32_t hT) {
  int lane = lane_;
#define t (a * 32 + lane)
#define g (lane >> 2)
#define q (lane & 3)
  const int i = cx.i, j = cx.j, cta = cx.cta;
  unsigned char* const sc = (unsigned char*)P.sc;
  const int rk = 36 * i + 12 * a;
  const uint32_t o_bf = OFF(bflag) + (j * 48 + i * 3 + a) * 32 + (lane & 7) * 4;
  uint32_t T;
  {
    const int k0 = lane & 7, tt = min(lane >> 3, 2), col = (9 * j + tt) * 16;
    const unsigned char* src = (const unsigned char*)P.wqkv + ((i * 8 + k0) * 3456 + a * 1152 + col);
    const Unit b0 = h0, b1 = h1;
    T = hT;
    nb_arrive(NB_ORD, 384);
    STAMPIF(1, 96);
    const uint32_t d2 = tt == 2 ? (22 - 7 * a) * 512 : 3072;
    const uint32_t o = OFF(wq) + (j * 18 + (i >> 2)) * 13824 + ((i & 3) * 8 + k0) * 16 + (a * 8 + tt) * 512;
    const uint32_t r0 = unit_store(sc, b0, lane, o, o + 1536, o + d2);
    STAMPD(asf(b0.v[2].w ^ b1.v[2].w), 80);
    const uint32_t r1 = unit_store(sc, b1, lane, o + 55296, o + 55296 + 1536, o + 55296 + d2);
    T = __shfl_sync(0xffffffffu, (T >> 3) + 1, 0);
    flag_after(sc + o_bf, r0 ^ r1, 8 * T + 1, lane < 8);
    STAMPD(asf(r0 ^ r1), 98);
    const Unit b2 = unit_load(src + 256 * 3456), b3 = unit_load(src + 384 * 3456);
    const bool qkv = k0 < 4;
    const int q0 = rk + k0 - 4, q1 = rk + 4 + k0;
    const Unit u0 = unit_load(qkv ? (const unsigned char*)P.wqkv + ((512 + 4 * i + k0) * 3456 + a * 1152 + col) : (const unsigned char*)P.wo + (q0 * 1152 + col));
    const Unit u1 = unit_load((const unsigned char*)P.wo + (q1 * 1152 + col));
    const uint32_t r2 = unit_store(sc, b2, lane, o + 2 * 55296, o + 2 * 55296 + 1536, o + 2 * 55296 + d2);
    const uint32_t r3 = unit_store(sc, b3, lane, o + 3 * 55296, o + 3 * 55296 + 1536, o + 3 * 55296 + d2);
    float cs[3][8];
#pragma unroll
    for (int m = 0; m < 3; m++) {
      const uint32_t* w0 = &b0.v[m].x; const uint32_t* w1 = &b1.v[m].x; const uint32_t* w2 = &b2.v[m].x; const uint32_t* w3 = &b3.v[m].x; const uint32_t* w4 = &u0.v[m].x;
#pragma unroll
      for (int e = 0; e < 4; e++) {
        const uint32_t z = qkv ? w4[e] : 0u;
        cs[m][2 * e] = (bf_lo(w0[e]) + bf_lo(w1[e])) + (bf_lo(w2[e]) + bf_lo(w3[e])) + bf_lo(z);
        cs[m][2 * e + 1] = (bf_hi(w0[e]) + bf_hi(w1[e])) + (bf_hi(w2[e]) + bf_hi(w3[e])) + bf_hi(z);
      }
    }
#pragma unroll
    for (int st = 4; st >= 1; st >>= 1) {
      const bool up = lane & st;
#pragma unroll
      for (int m = 0; m < 3; m++)
#pragma unroll
        for (int e = 0; e < st; e++) cs[m][e] = (up ? cs[m][e + st] : cs[m][e]) + shx(up ? cs[m][e] : cs[m][e + st], st);
    }
    {
      const uint32_t oz = OFF(zpart) + j * 13824 + i * 864 + (a * 8 + tt) * 32 + k0 * 4;
      stg32(sc + oz, ftag(cs[0][0], 1)); stg32(sc + (oz + 96), ftag(cs[1][0], 1)); stg32(sc + (oz + (d2 >> 4)), ftag(cs[2][0], 1));
    }
    STAMPIF(1, 81);
    flag_after(sc + o_bf, r2 ^ r3, 8 * T + 3, lane < 8);
    STAMPIF(1, 82);
    nb_sync(NB_GO, 128);
    mbar_wait(sb + BAR_FULL + LATE_WAIT * 8, 0);
    const uint32_t ow = OFF(wo) + j * 82944 + tt * 256;
    const uint32_t oa = qkv ? OFF(wq) + (j * 18 + 16 + (i >> 3)) * 13824 + (4 * (i & 7) + k0) * 16 + (a * 8 + tt) * 512 : ow + (q0 >> 4) * 2304 + (q0 & 15) * 16;
    const uint32_t ob = ow + (q1 >> 4) * 2304 + (q1 & 15) * 16;
    const uint32_t ra = unit_store(sc, u0, lane, oa, oa + (qkv ? 1536 : 768), oa + (qkv ? d2 : 1536));
    const uint32_t rb = unit_store(sc, u1, lane, ob, ob + 768, ob + 1536);
    STAMPIF(1, 113);
#pragma unroll
    for (int S = 0; S < 3; S++) stg64(sc + (OFF(ypart) + (a * 24 + g) * 4096 + cta * 32 + q * 8) + S * 32768, 0u, 0u);
    if (cta < 72 && t < 16) stg32(sc + (OFF(xsel) + (lane >> 3) * 2304 + cta * 32 + (lane & 7) * 4), (T & 1) ^ 1);
    uint4 sv, sw;
    int n = 0;
#pragma unroll 1
    while (true) {
      sv = ldg_rlx128(sc + (OFF(st0) + i * 2048 + t * 16)); sw = ldg_rlx128(sc + (OFF(st0) + i * 2048 + 1536 + lane * 16));
      if (__all_sync(0xffffffffu, ((sv.z ^ T) | (sw.z ^ T)) == 0)) break;
      if (++n > SPIN) TIMEOUT(__LINE__)
    }
    flag_after(sc + o_bf, ra ^ rb, 8 * T + 4, lane < 8);
    sts64(sb + SM_R + t * 8, sv.x, sv.y);
    sts64(sb + SM_R + 768 + lane * 8, sw.x, sw.y);
    STAMPIF(1, 94);
  }
  asm volatile("setmaxnreg.inc.sync.aligned.u32 %0;" ::"n"(REG_AUX));
  Winner wn;
  bool owner = false;
  uint32_t wd[5][3][8];
  auto load_wd = [&](uint32_t (*d)[8], const unsigned char* sk) {
#pragma unroll
    for (int S = 0; S < 3; S++) {
      const uint4 v0 = ldg_wd128(sk + S * 128), v1 = ldg_wd128(sk + S * 128 + 1152);
      d[S][0] = v0.x; d[S][1] = v1.x; d[S][2] = v0.y; d[S][3] = v1.y; d[S][4] = v0.z; d[S][5] = v1.z; d[S][6] = v0.w; d[S][7] = v1.w;
    }
  };
  auto perm_wd = [&](uint32_t (*d)[8]) {
#pragma unroll
    for (int S = 0; S < 3; S++)
#pragma unroll
      for (int u = 0; u < 4; u++) {
        const uint32_t x = d[S][2 * u], y = d[S][2 * u + 1];
        asm volatile("prmt.b32 %0, %2, %3, 0x5410;\nprmt.b32 %1, %2, %3, 0x7632;" : "=&r"(d[S][2 * u]), "=r"(d[S][2 * u + 1]) : "r"(x), "r"(y));
      }
  };
#pragma unroll
  for (int kb = 0; kb < 3; kb++)
#pragma unroll
    for (int S = 0; S < 3; S++)
#pragma unroll
      for (int e = 0; e < 8; e++) wd[kb][S][e] = 0u;
#pragma unroll 1
  for (int L = 0; L < 2; L++) {
    lane = pin(lane);
    const uint32_t o_part = OFF(zpart) + j * 13824, par = L ^ 1;
    const int pk = a * 18 + min(lane, 17);
    uint2 xu[3] = {make_uint2(0, 0), make_uint2(0, 0), make_uint2(0, 0)};
    if (L == 1) {
      if (cta < 72) finalize_row(P, wn, T, 0, cta, a, lane);
      const int gi = min(lane, 26);
      uint4 wv[12];
      {
        const int pc = gi < 24 ? gi >> 3 : gi - 24, tc = gi < 24 ? gi & 7 : 8;
        const unsigned char* se = (const unsigned char*)P.wqkv + (rk * 3456 + pc * 1152 + (9 * j + tc) * 16);
#pragma unroll
        for (int r = 0; r < 12; r++) wv[r] = ldg_nc128(se + r * 3456);
      }
      STAMPIF(1, 85);
      nb_sync(NB_AUX, 96);
      uint4 xq[3];
      {
        const unsigned char* dp = sc + (OFF(xsel) + 2304 + rk * 4);
        int n = 0;
#pragma unroll 1
        while (true) {
#pragma unroll
          for (int e = 0; e < 3; e++) xq[e] = ldg_rlx128(dp + e * 16);
          uint32_t d = orx(orx(orx(0, xq[0].x, T), xq[1].x, T), xq[2].x, T);
          if (owner) {
#pragma unroll
            for (int m = 0; m < 3; m++) xu[m] = ldg_rlx64(sc + (OFF(xsel) + t * 8) + m * 768);
            d = orx(orx(orx(d, xu[0].x, T), xu[1].x, T), xu[2].x, T);
          }
          if (__all_sync(0xffffffffu, (d & 1) == 0)) break;
          if (++n > SPIN) TIMEOUT(__LINE__)
        }
        if (t == 0) {
          sts32(sb + SM_SEL, owner ? (wn.ci & 1) * 64 + wn.rr : 0x7FFFFFFFu);
          if (wn.ci != 2 * i) mbar_arrive(sb + BAR_FIX);
          if (wn.ci != 2 * i + 1) mbar_arrive(sb + BAR_FIX + 8);
        }
        STAMPIF(1, 88);
      }
      float s[8];
#pragma unroll
      for (int e = 0; e < 8; e++) s[e] = 0.f;
#pragma unroll
      for (int r = 0; r < 12; r++) {
        const float x = asf((&xq[0].x)[r]);
        s[0] = fmaf(x, bf_lo(wv[r].x), s[0]); s[1] = fmaf(x, bf_hi(wv[r].x), s[1]);
        s[2] = fmaf(x, bf_lo(wv[r].y), s[2]); s[3] = fmaf(x, bf_hi(wv[r].y), s[3]);
        s[4] = fmaf(x, bf_lo(wv[r].z), s[4]); s[5] = fmaf(x, bf_hi(wv[r].z), s[5]);
        s[6] = fmaf(x, bf_lo(wv[r].w), s[6]); s[7] = fmaf(x, bf_hi(wv[r].w), s[7]);
      }
      sts128(sb + SM_R + a * 864 + gi * 32, asu(s[0]), asu(s[1]), asu(s[2]), asu(s[3]));
      sts128(sb + SM_R + a * 864 + gi * 32 + 16, asu(s[4]), asu(s[5]), asu(s[6]), asu(s[7]));
      nb_sync(NB_AUX, 96);
      const uint32_t ad = sb + SM_R + pk * 16;
      const uint4 u0 = lds128(ad), u1 = lds128(ad + 864), u2 = lds128(ad + 1728);
      stg128(sc + (o_part + i * 864 + pk * 16), ftag(asf(u0.x) + asf(u1.x) + asf(u2.x), par), ftag(asf(u0.y) + asf(u1.y) + asf(u2.y), par),
             ftag(asf(u0.z) + asf(u1.z) + asf(u2.z), par), ftag(asf(u0.w) + asf(u1.w) + asf(u2.w), par));
      STAMPIF(1, 86);
    }
    if (owner) {
      const uint2* u = xu;
      STAMPIF(1, 109);
      float s1 = 0.f, s2 = 0.f;
#pragma unroll
      for (int m = 0; m < 3; m++) {
        const float x0 = asf(u[m].x), x1 = asf(u[m].y);
        s1 += x0 + x1; s2 = fmaf(x0, x0, fmaf(x1, x1, s2));
        const unsigned cc = 96 * m + t - 36 * j;
        if (cc < 36u) sts32(sb + SM_X2S + cc * 4, __byte_perm(u[m].x, u[m].y, 0x7632));
      }
      wn.m = s1; wn.rstd = s2;
    }
    if (L == 0 || owner) {
      uint4 u[16];
      int n = 0;
#pragma unroll 1
      while (true) {
        uint32_t d0 = 0, d1 = 0;
#pragma unroll
        for (int e = 0; e < 16; e++) u[e] = ldg_rlx128(sc + (o_part + pk * 16) + e * 864);
        if (L == 1 && n == 0) {
#pragma unroll
          for (int s = 1; s < 32; s <<= 1) { wn.m += shx(wn.m, s); wn.rstd += shx(wn.rstd, s); }
          if (lane == 0) sts64(sb + SM_RED2 + a * 8, asu(wn.m), asu(wn.rstd));
        }
#pragma unroll
        for (int e = 0; e < 8; e++) { d0 = orx(d0, u[e].x, par); d1 = orx(d1, u[8 + e].x, par); }
        if (__all_sync(0xffffffffu, ((d0 | d1) & 1) == 0)) break;
        if (++n > SPIN) TIMEOUT(__LINE__)
      }
      STAMPIF(1, 118 + L);
      float4 z = make_float4(0.f, 0.f, 0.f, 0.f);
#pragma unroll
      for (int e = 0; e < 16; e++) { z.x += asf(u[e].x); z.y += asf(u[e].y); z.z += asf(u[e].z); z.w += asf(u[e].w); }
      const uint32_t h0 = pack_bf16(z.x, z.y), h1 = pack_bf16(z.z, z.w);
      const uint32_t l0 = pack_bf16(z.x - bf_lo(h0), z.y - bf_hi(h0)), l1 = pack_bf16(z.z - bf_lo(h1), z.w - bf_hi(h1));
      const uint32_t ad = sb + SM_BEXT + (pk >> 1) * 128 + (pk & 1) * 8;
      if (L == 0) {
        sts64(ad, h0, h1);
#pragma unroll
        for (int r = 3; r < 8; r++) sts64(ad + r * 16, 0u, 0u);
      }
      sts64(ad + 16 + L * 48, h0, h1); sts64(ad + 32 + L * 48, l0, l1);
      fence_async_smem();
      nb_sync(NB_AUX, 96);
      if (t == 0) {
        if (L == 1) {
          const uint4 ra = lds128(sb + SM_RED2);
          const uint2 rb = lds64(sb + SM_RED2 + 16);
          const float m2 = (asf(ra.x) + asf(ra.z) + asf(rb.x)) * (1.f / 576.f);
          const float rs2 = rsq(fmaxf((asf(ra.y) + asf(ra.w) + asf(rb.y)) * (1.f / 576.f) - m2 * m2, 0.f) + EPS);
          sts64(sb + SM_SEL + 8, asu(m2), asu(rs2));
          mbar_arrive(sb + BAR_FIX + (wn.ci & 1) * 8);
        } else {
          mbar_arrive(sb + BAR_FIX); mbar_arrive(sb + BAR_FIX + 8);
        }
        STAMP(83 + L * 4);
      }
    }
    lane = pin(lane);
    const unsigned char* const wsrc = (const unsigned char*)P.wd + ((ffn_c32(cta) + 2 * q) * 1152 + a * 384 + g * 16);
    if (L == 0) {
#pragma unroll
      for (int kb = 0; kb < 3; kb++) { load_wd(wd[kb], wsrc + (kb * 9216 + (kb ? pin0(wd[kb - 1][2][7]) : 0u))); perm_wd(wd[kb]); }
    }
    if (L == 0)
    {
    load_wd(wd[3], wsrc + 3 * 9216);
    load_wd(wd[4], wsrc + ((cta & 1) ? (ffn_c8(cta) - ffn_c32(cta)) * 1152 : 24 * 1152));
    perm_wd(wd[3]); perm_wd(wd[4]);
    }
    const uint32_t o_y = pin(OFF(ypart) + (a * 24 + g) * 4096 + cta * 32 + q * 8 + pin0(wd[4][2][7]));
    STAMPIF(1, 89 + L);
    if (a == 2) load_wo_a(cx, P, T, L, 1, lane);
    nb_sync(NB_FFN, 224);
    {
      const uint32_t ad = sb + R_FPART + min(lane, 19) * 16;
      const uint4 u0 = lds128(ad), u1 = lds128(ad + 320), u2 = lds128(ad + 640), u3 = lds128(ad + 960);
      const uint4 wv = lds128(sb + SM_WIN);
      const float g0 = rbf((asf(u0.x) + asf(u1.x)) + (asf(u2.x) + asf(u3.x))), g1 = rbf((asf(u0.z) + asf(u1.z)) + (asf(u2.z) + asf(u3.z)));
      const float v0 = rbf((asf(u0.y) + asf(u1.y)) + (asf(u2.y) + asf(u3.y))), v1 = rbf((asf(u0.w) + asf(u1.w)) + (asf(u2.w) + asf(u3.w)));
      const float s0 = rbf(g0 * rcp(1.f + ex2(-1.4426950408889634f * g0))), s1 = rbf(g1 * rcp(1.f + ex2(-1.4426950408889634f * g1)));
      const uint32_t act = lane < 16 + (cta & 1) * 4 ? pack_bf16(s0 * v0, s1 * v1) : 0u;
      uint32_t b[5];
#pragma unroll
      for (int kb = 0; kb < 5; kb++) b[kb] = __shfl_sync(0xffffffffu, act, 4 * kb + q);
#pragma unroll
      for (int S = 0; S < 3; S++) {
        float y[4][4];
#pragma unroll
        for (int u = 0; u < 4; u++) mma8z(y[u], wd[2][S][2 * u], wd[2][S][2 * u + 1], b[2]);
#pragma unroll
        for (int u = 0; u < 4; u++) mma16(y[u], wd[0][S][2 * u], wd[0][S][2 * u + 1], wd[1][S][2 * u], wd[1][S][2 * u + 1], b[0], b[1]);
#pragma unroll
        for (int u = 0; u < 4; u++) mma16(y[u], wd[3][S][2 * u], wd[3][S][2 * u + 1], wd[4][S][2 * u], wd[4][S][2 * u + 1], b[3], b[4]);
        const float y0 = self(lane & 2, self(lane & 1, y[3][0], y[2][0]), self(lane & 1, y[1][0], y[0][0]));
        const float y1 = self(lane & 2, self(lane & 1, y[3][2], y[2][2]), self(lane & 1, y[1][2], y[0][2]));
        stg64(sc + o_y + S * 32768, ftag(y0, par), ftag(y1, par));
      }
      if (L == 0) nb_arrive(NB_FFN2, 352);
      wn.r = asf(wv.x); wn.m = asf(wv.y); wn.rstd = asf(wv.z); wn.ci = wv.w >> 6; wn.rr = wv.w & 63;
    }
    STAMPIF(1, 84 + L * 8);
    owner = (wn.ci >> 1) == i;
  }
  if (cta < 72) finalize_row(P, wn, T, 1, cta, a, lane);
  STAMPIF(1, 93);
  PROF_END();
#undef t
#undef g
#undef q
}

__device__ __forceinline__ int sched_box(const uint32_t at, const int a) {
  int r = -1;
#pragma unroll
  for (int b = 0; b < 6; b++) if (((at >> (4 * b)) & 15) != 15) r = a == (int)((at >> (4 * b)) & 15) ? b : r;
  return r;
}
__host__ __device__ constexpr int sched_first(const uint32_t at) { int b = 0; while (b < 6 && ((at >> (4 * b)) & 15) != 15) b++; return b; }
__host__ __device__ constexpr int sched_last(const uint32_t at) { int b = 5; while (b >= 0 && ((at >> (4 * b)) & 15) != 15) b--; return b; }
__device__ __forceinline__ void producer_role(const Ctx& cx, const Params& P, const int lane) {
  const int i = cx.i, j = cx.j;
  nb_sync(NB_ORD, 384);
  if (elect_one()) asm volatile("prefetch.tensormap [%0];" ::"l"(&P.mx) : "memory");
  const uint32_t T = __shfl_sync(0xffffffffu, (ldg_rlx32(P.sc->cflag[i * 2][j * 4]) >> 3) + 1, 0);
  const unsigned char* const wq = P.sc->wq[j][0];
  nb_sync(NB_START, 288);
#pragma unroll
  for (int s = 0; s < 2 * NA0; s++) w_tma3d(sb + SM_A + s * 8192, &P.mx, (s >> 1) * 64, s & 1, i * 64, sb + BAR_FULL + (s >> 1) * 16);
#pragma unroll
  for (int h = 0; h < 6; h++) w_expect(sb + BAR_FULL + h * 8, h & 1 ? 13824 : 13824 + 16384);
  STAMP(97);
  wait_flags<48>(P.sc->bflag[j], 8 * T + 1, lane);
  fence_async_glob();
  STAMP(120);
#pragma unroll
  for (int h = 0; h < 6; h++) {
    w_bulk(sb + SM_B + h * 13824, wq + h * 13824, 13824, sb + BAR_FULL + h * 8);
    if (!(h & 1) && h >= 2 * NA0) {
      w_tma3d(sb + SM_A + h * 8192, &P.mx, h * 32, 0, i * 64, sb + BAR_FULL + h * 8);
      w_tma3d(sb + SM_A + h * 8192 + 8192, &P.mx, h * 32, 1, i * 64, sb + BAR_FULL + h * 8);
    }
  }
  PSTAMP(0);
  asm volatile("setmaxnreg.inc.sync.aligned.u32 %0;" ::"n"(REG_AUX));
  nb_arrive(NB_GO, 128);
  mbar_wait(sb + BAR_FULL + PF_WAIT * 8, 0);
  w_prefetch((const unsigned char*)P.wd + cx.cta * 41472, 10368);
  const unsigned char* const xb = P.sc->xbuf[i * 2];
  const unsigned char* const fp = (const unsigned char*)P.sc->bflag[j] + lane * 32;
  uint32_t f0 = 0, f1 = 0;
#pragma unroll 1
  for (int L = 0; L < 2; L++) {
#pragma unroll 1
    for (int a = 3; a < 15; a++) {
      if (a == 12) {
        load_wo_a(cx, P, T, L, 0, lane);
        if (L == 1) break;
        {
#pragma unroll 1
          for (int b = LATE_G0; b < 6; b++) {
            if (LATE_GGAP) { const int c0 = clock(); while ((int)(clock() - c0) < LATE_GGAP) {} }
            load_gu(P, cx.cta, 0, b, sb + BAR_GU);
          }
#pragma unroll 1
          for (int p = 0; p < 2; p++) {
            mbar_wait(sb + BAR_AEMPTY + (2 + 3 * p) * 8, 0);
            wait_flags<32>(P.sc->cflag[i * 2 + p], 8 * T + 1, lane);
            STAMP(104 + p);
          }
          fence_async_glob();
          mbar_wait(sb + BAR_ST, 0);
#pragma unroll 1
          for (int s = 0; s < 3; s++) {
            const uint32_t fb = sb + BAR_FULL + s * 16, ab = sb + BAR_AFULL + s * 16, db = sb + SM_B + s * 27648, da = sb + SM_A + s * 16384;
            mbar_wait(sb + BAR_EMPTY + s * 16, 1);
            w_expect(fb, 13824);
            w_bulk(db, wq + s * 27648, 13824, fb);
            w_expect(ab, 8192);
            w_bulk(da, xb + s * 8192, 8192, ab);
            w_expect(ab + 8, 8192);
            w_bulk(da + 8192, xb + (73728 + s * 8192), 8192, ab + 8);
            mbar_wait(sb + BAR_EMPTY + s * 16 + 8, 1);
            w_expect(fb + 8, 13824);
            w_bulk(db + 13824, wq + (s * 27648 + 13824), 13824, fb + 8);
          }
          break;
        }
      }
      const int r = (a * 11) >> 5, s = a - 3 * r;
      const uint32_t fb = sb + BAR_FULL + s * 16, da = sb + SM_A + s * 16384, db = sb + SM_B + s * 27648;
      const unsigned char* bsrc = wq + (a < 9 ? a : a < 12 ? 72 - 6 * j + s : s) * 27648;
      const unsigned char* asrc = xb + a * 8192;
      const int kc = (a < 9 ? a : j + a - 10) * 64;
      const int amode = a == 9 || a > 11 ? 0 : L == 0 ? 1 : a < 9 ? 2 : 0;
      mbar_wait(sb + BAR_EMPTY + s * 16, (r & 1) ^ 1);
      if (L == 0) {
        if (a == 4 || a == 8) {
          const uint32_t need = 8 * T + (a == 4 ? 3 : 4);
          if (__any_sync(0xffffffffu, (int)((f0 - need) | (f1 - need)) < 0)) wait_flags<48>(P.sc->bflag[j], need, lane);
          fence_async_glob();
          STAMP(120 + (a >> 1));
        }
        if (a == 3 || a == 7) { f0 = ldg_rlx32(fp); f1 = ldg_rlx32(fp + (lane < 16 ? 1024 : 0)); }
      }
      w_bulk(db, bsrc, 13824, fb);
      if (amode == 2) {
        w_bulk(da, asrc, 4096, fb);
        w_bulk(da + 8192, asrc + 73728, 4096, fb);
      }
      w_expect(fb, amode == 1 ? 13824 + 16384 : amode == 2 ? 13824 + 8192 : 13824);
      mbar_wait(sb + BAR_EMPTY + s * 16 + 8, (r & 1) ^ 1);
      if (amode == 1) {
        w_tma3d(da, &P.mx, kc, 0, i * 64, fb);
        w_tma3d(da + 8192, &P.mx, kc, 1, i * 64, fb);
      }
      w_bulk(db + 13824, bsrc + 13824, 13824, fb + 8);
      if (amode == 2) {
        w_bulk(da + 4096, asrc + 4096, 4096, fb + 8);
        w_bulk(da + 8192 + 4096, asrc + 73728 + 4096, 4096, fb + 8);
      }
      w_expect(fb + 8, amode == 2 ? 13824 + 8192 : 13824);
      PSTAMP(a < 12 ? L * 24 + a : 12 + a);
      if (L == 0) {
        {
          if (a >= WD_PF && a < WD_PF + 3) w_prefetch((const unsigned char*)P.wd + (cx.cta * 4 + a - WD_PF + 1) * 10368, 10368);
          if (a >= PG_0 && a < PG_0 + 6) w_prefetch((const unsigned char*)P.wg + ((a - PG_0) * 128 + cx.cta) * 6912, 6912);
        }
        if (a == 3) w_expect(sb + BAR_GU, 12 * (6144 + (cx.cta & 1) * 1536));
        {
          const int bu = sched_box(U_AT, a), bg = sched_box(G_AT, a);
          if (bu >= 0) load_gu(P, cx.cta, 1, bu, sb + BAR_GU);
          if (bg >= 0) load_gu(P, cx.cta, 0, bg, sb + BAR_GU);
          if (a == U_WIN) {
#pragma unroll 1
            for (int b = sched_first(U_AT); b <= sched_last(U_AT); b++) {
              const int c0 = clock();
              while ((int)(clock() - c0) < U_GAP) {}
              load_gu(P, cx.cta, 1, b, sb + BAR_GU);
            }
          }
        }
      }
    }
  }
}

template <bool BY_SMID>
__global__ void __launch_bounds__(384, 1) fused_kernel(const __grid_constant__ Params P) {
  extern __shared__ __align__(1024) unsigned char smem[];
  Ctx cx;
  STAMPIF(threadIdx.x == 64, 125);
  unsigned id;
  if (BY_SMID) asm volatile("mov.u32 %0, %%smid;" : "=r"(id)); else id = blockIdx.x;
  const int work = __shfl_sync(0xffffffffu, (int)P.work[min(id, 131u)], 0);
  const int warp = __shfl_sync(0xffffffffu, (int)(threadIdx.x >> 5), 0), lane = threadIdx.x & 31;
  if (work < 0) {
    if (warp == 0) {
      const int sp = -1 - work;
      if (lane == 0) { mbar_init(sb, 1); fence_async_smem(); }
      __syncwarp();
      __nanosleep(SPARE_DELAY);
#pragma unroll 1
      for (int k = 32 + sp; k < 72; k += 4) w_prefetch((const unsigned char*)P.wqkv + k * 27648, 27648);
#pragma unroll 1
      for (int k = sp; k < 24; k += 4) w_prefetch((const unsigned char*)P.wo + k * 27648, 27648);
#pragma unroll 1
      for (int k = sp; k < X_NU; k += 4) w_prefetch((const unsigned char*)P.wu + k * 27648, 27648);
      w_expect(sb, 16);
      w_bulk(sb + 128, P.wr, 16, sb);
      mbar_wait(sb, 0);
    }
    return;
  }
  cx.cta = work; cx.i = work >> 3; cx.j = work & 7;
  STAMPIF(threadIdx.x == 32, 95);
  Unit h0, h1;
  uint32_t hT = 0;
  if (warp >= 8 && warp < 11) {
    const int a = warp - 8, k0 = lane & 7, tt = min(lane >> 3, 2);
    const unsigned char* src = (const unsigned char*)P.wqkv + ((cx.i * 8 + k0) * 3456 + a * 1152 + (9 * cx.j + tt) * 16);
    h0 = unit_load(src); h1 = unit_load(src + 128 * 3456);
    hT = ldg_rlx32((const unsigned char*)P.sc + (OFF(bflag) + (cx.j * 48 + cx.i * 3 + a) * 32 + (lane & 7) * 4));
  }
  if (warp < 8) {
    asm volatile("setmaxnreg.dec.sync.aligned.u32 %0;" ::"n"(REG_CONS));
    if (warp == 0) {
      if (elect_one()) {
        if ((uint32_t)__cvta_generic_to_shared(smem) != sb) __trap();
#pragma unroll
        for (int b = 0; b < 48; b++) mbar_init(sb + SM_BAR + b * 8, b < 34 ? 1 : b < 42 ? 4 : 8);
        fence_async_smem();
      }
      __syncwarp();
    }
    consumer_role(cx, P, smem, warp >> 2, warp & 3, lane);
  } else {
    if (warp < 11) aux_role(cx, P, warp - 8, lane, h0, h1, hT);
    else producer_role(cx, P, lane);
  }
}

int work_of_smid(int smid) {
  const int t = smid >> 1;
  if (t == 60 || t == 61) return -1 - ((t - 60) * 2 + (smid & 1));
  const int gpc = t < 32 ? t & 7 : t < 60 ? 1 + (t - 32) % 7 : 0;
  const int x = 2 * (t < 32 ? t >> 3 : t < 60 ? 4 + (t - 32) / 7 : t - 58) + (smid & 1);
  const int blk[8] = {6, 0, 2, 3, 4, 7, 5, 1}, b = blk[gpc];
  return ((b >> 1) * 4 + (x & 1) + (x >> 3) * 2) * 8 + (b & 1) * 4 + ((x >> 1) & 3);
}

typedef CUresult (*EncodeFn)(CUtensorMap*, CUtensorMapDataType, cuuint32_t, void*, const cuuint64_t*, const cuuint64_t*,
                             const cuuint32_t*, const cuuint32_t*, CUtensorMapInterleave, CUtensorMapSwizzle,
                             CUtensorMapL2promotion, CUtensorMapFloatOOBfill);

void make_map(EncodeFn enc, CUtensorMap* m, const void* base, int rank, const cuuint64_t* dims, const cuuint64_t* strides,
              const cuuint32_t* box, CUtensorMapSwizzle sw, CUtensorMapL2promotion promo = CU_TENSOR_MAP_L2_PROMOTION_L2_128B) {
  const cuuint32_t es[3] = {1, 1, 1};
  enc(m, CU_TENSOR_MAP_DATA_TYPE_BFLOAT16, rank, const_cast<void*>(base), dims, strides, box, es, CU_TENSOR_MAP_INTERLEAVE_NONE, sw,
      promo, CU_TENSOR_MAP_FLOAT_OOB_FILL_NONE);
}

}

extern "C" void kernel_launch(void* const* d_in, const int* in_sizes, int n_in, void* d_out, int out_size) {
  (void)in_sizes; (void)n_in; (void)out_size;
  static EncodeFn enc = nullptr;
  static int nsm = 0;
  static void* scr = nullptr;
  if (!enc) {
    void* f = nullptr;
    cudaDriverEntryPointQueryResult qr;
    cudaGetDriverEntryPoint("cuTensorMapEncodeTiled", &f, cudaEnableDefault, &qr);
    enc = (EncodeFn)f;
    cudaGetSymbolAddress(&scr, g_scratch);
    int dev = 0;
    cudaGetDevice(&dev);
    cudaDeviceGetAttribute(&nsm, cudaDevAttrMultiProcessorCount, dev);
    cudaFuncSetAttribute(fused_kernel<true>, cudaFuncAttributeMaxDynamicSharedMemorySize, SM_TOTAL);
    cudaFuncSetAttribute(fused_kernel<false>, cudaFuncAttributeMaxDynamicSharedMemorySize, SM_TOTAL);
  }
  Params P;
  P.x = (const __nv_bfloat16*)d_in[0];
  P.wqkv = (const __nv_bfloat16*)d_in[1];
  P.wo = (const __nv_bfloat16*)d_in[2];
  P.wr = (const __nv_bfloat16*)d_in[4];
  P.wg = (const __nv_bfloat16*)d_in[5];
  P.wu = (const __nv_bfloat16*)d_in[6];
  P.wd = (const __nv_bfloat16*)d_in[7];
  P.out = (__nv_bfloat16*)d_out;
  P.sc = (Scratch*)scr;
  for (int k = 0; k < 136; k++) P.work[k] = (signed char)(nsm == 132 ? (k < 132 ? work_of_smid(k) : -1) : (k < 128 ? k : k < 132 ? 127 - k : -1));
  {
    const cuuint64_t dims[3] = {576, 2, 1024}, str[2] = {1152, 2304};
    const cuuint32_t box[3] = {64, 1, 64};
    make_map(enc, &P.mx, P.x, 3, dims, str, box, CU_TENSOR_MAP_SWIZZLE_128B);
  }
  {
    const cuuint64_t dims[2] = {4608, 576}, str[1] = {9216};
    const cuuint32_t box[2] = {32, 96}, box8[2] = {8, 96};
    make_map(enc, &P.mg, d_in[5], 2, dims, str, box, CU_TENSOR_MAP_SWIZZLE_64B);
    make_map(enc, &P.mu, d_in[6], 2, dims, str, box, CU_TENSOR_MAP_SWIZZLE_64B);
    make_map(enc, &P.mg8, d_in[5], 2, dims, str, box8, CU_TENSOR_MAP_SWIZZLE_NONE);
    make_map(enc, &P.mu8, d_in[6], 2, dims, str, box8, CU_TENSOR_MAP_SWIZZLE_NONE);
  }
  if (nsm == 132) fused_kernel<true><<<132, 384, SM_TOTAL>>>(P);
  else fused_kernel<false><<<132, 384, SM_TOTAL>>>(P);
}
```

```cpp
#include <cuda_runtime.h>
#include <cuda.h>
#include <cuda_bf16.h>
#include <stdint.h>
#include <stddef.h>

namespace {

#define NPRE_ 4
constexpr int NPRE = NPRE_;
#define X_NU 192
#define CAND_W 8
#define X_DELAY 200
#define X_STEP 100
#define HOLD_C 13
#define NA0 3
#define LATE_WAIT 1
#define U_AT 0xFFFF75
#define G_AT 0xEEEEEB
#define PG_0 6
#define WD_PF 3
#define U_WIN 11
#define U_GAP 400
#define LATE_G0 1
#define LATE_GGAP 600
#define REG_AUX 200
#define REG_CONS 152
#define D_STATS 400
#define D_Y0 500
#define D_OF0 0
#define D_OF1 600
#define D_XS 0
#define PF_WAIT 0
#define POLL_GAP 100
#define SPARE_DELAY 400
constexpr float EPS = 1e-5f;
constexpr int SPIN = 1 << 22;
#define TIMEOUT(line) __trap();

struct __align__(128) Scratch {
  uint32_t bflag[8][48][8];
  uint32_t cflag[32][32][8];
  uint32_t halo[32][8][672];
  uint32_t stats[32][4][8][64];
  uint32_t cand[8][32][CAND_W];
  uint32_t xcand[32][8][48];
  uint32_t ypart[72][128][8];
  uint32_t zpart[8][16][216];
  uint32_t st0[2048][4];
  uint32_t xsel[2][576];
  unsigned char wq[8][9][27648];
  unsigned char wo[8][3][27648];
  unsigned char obuf[32][73728];
  unsigned char xbuf[32][73728];
};
__device__ Scratch g_scratch;
#define OFF(f) ((uint32_t)offsetof(Scratch, f))
#define STAMPD(v, k) do {} while (0)
#define STAMPIF(c, k) do {} while (0)
#define STAMP(k) do {} while (0)

constexpr uint32_t sb = 1024;
constexpr uint32_t SM_A = 0;
constexpr uint32_t SM_B = 49152;
constexpr uint32_t SM_G = 132096;
constexpr uint32_t SM_BEXT = 224256;

constexpr uint32_t SM_WIN = 227712;
constexpr uint32_t SM_XW = 228320;
constexpr uint32_t SM_YRED = 228448;
constexpr uint32_t SM_X2S = 228576;
constexpr uint32_t SM_RED2 = 228736;
constexpr uint32_t SM_WR = 228864;
constexpr uint32_t SM_R = 229168;
constexpr uint32_t SM_BEST = 231760;
constexpr uint32_t SM_SEL = 231824;
constexpr uint32_t SM_BAR = 231840;
constexpr uint32_t SM_TOTAL = 232448;
constexpr uint32_t R_FPART = SM_R;
constexpr uint32_t BAR_FULL = SM_BAR  , BAR_AFULL = SM_BAR + 48  , BAR_WFULL = SM_BAR + 96  , BAR_ST = SM_BAR + 240, BAR_GU = SM_BAR + 248,
                   BAR_FIX = SM_BAR + 256  , BAR_AEMPTY = SM_BAR + 272  , BAR_HDONE = SM_BAR + 320  ,
                   BAR_EMPTY = SM_BAR + 336  ;
enum { NB_WG = 1  , NB_STAG = 3, NB_AUX = 4, NB_FFN2 = 5, NB_FFN = 8, NB_START = 9, NB_GO = 6, NB_ORD = 7, NB_PF = 11, NB_INIT = 12 };

struct Params {
  const __nv_bfloat16 *wqkv, *x, *wr, *wo;
  Scratch* sc;
  const __nv_bfloat16 *wd, *wg, *wu;
  __nv_bfloat16* out;
  signed char work[136];
  CUtensorMap mx, mg, mu, mg8, mu8;
};

__device__ __forceinline__ void mbar_init(uint32_t bar, int cnt) { asm volatile("mbarrier.init.shared::cta.b64 [%0], %1;" ::"r"(bar), "r"(cnt) : "memory"); }
__device__ __forceinline__ void mbar_arrive(uint32_t bar) { asm volatile("mbarrier.arrive.shared::cta.b64 _, [%0];" ::"r"(bar) : "memory"); }
__device__ __forceinline__ void mbar_wait(uint32_t bar, uint32_t par) {
  asm volatile("{\n.reg .pred p;\nLOOP:\nmbarrier.try_wait.parity.shared::cta.b64 p, [%0], %1;\n@!p bra.uni LOOP;\n}\n" ::"r"(bar), "r"(par) : "memory");
}
__device__ __forceinline__ uint32_t mbar_test(uint32_t bar, uint32_t par) {
  uint32_t ok;
  asm volatile("{\n.reg .pred p;\nmbarrier.test_wait.parity.shared::cta.b64 p, [%1], %2;\nselp.u32 %0,1,0,p;\n}" : "=r"(ok) : "r"(bar), "r"(par) : "memory");
  return ok;
}
__device__ __forceinline__ bool elect_one() {
  uint32_t ok;
  asm volatile("{\n.reg .pred p;\nelect.sync _|p, 0xffffffff;\nselp.u32 %0, 1, 0, p;\n}" : "=r"(ok));
  return ok;
}
__device__ __forceinline__ float ex2(float x) { float r; asm("ex2.approx.ftz.f32 %0, %1;" : "=f"(r) : "f"(x)); return r; }
__device__ __forceinline__ float rsq(float x) { float r; asm("rsqrt.approx.ftz.f32 %0, %1;" : "=f"(r) : "f"(x)); return r; }
__device__ __forceinline__ float rcp(float x) { float r; asm("rcp.approx.ftz.f32 %0, %1;" : "=f"(r) : "f"(x)); return r; }
__device__ __forceinline__ void w_expect(uint32_t bar, uint32_t bytes) {
  asm volatile("{\n.reg .pred p;\nelect.sync _|p, 0xffffffff;\n@p mbarrier.arrive.expect_tx.shared::cta.b64 _, [%0], %1;\n}" ::"r"(bar), "r"(bytes) : "memory");
}
__device__ __forceinline__ void w_bulk(uint32_t dst, const void* src, uint32_t bytes, uint32_t bar) {
  asm volatile("{\n.reg .pred p;\nelect.sync _|p, 0xffffffff;\n@p cp.async.bulk.shared::cluster.global.mbarrier::complete_tx::bytes [%0], [%1], %2, [%3];\n}" ::"r"(dst), "l"(src), "r"(bytes), "r"(bar) : "memory");
}
__device__ __forceinline__ void w_tma2d(uint32_t dst, const CUtensorMap* m, int c0, int c1, uint32_t bar) {
  asm volatile("{\n.reg .pred p;\nelect.sync _|p, 0xffffffff;\n@p cp.async.bulk.tensor.2d.shared::cluster.global.mbarrier::complete_tx::bytes [%0], [%1, {%3, %4}], [%2];\n}" ::"r"(dst), "l"(m), "r"(bar), "r"(c0), "r"(c1) : "memory");
}
__device__ __forceinline__ void w_tma3d(uint32_t dst, const CUtensorMap* m, int c0, int c1, int c2, uint32_t bar) {
  asm volatile("{\n.reg .pred p;\nelect.sync _|p, 0xffffffff;\n@p cp.async.bulk.tensor.3d.shared::cluster.global.mbarrier::complete_tx::bytes [%0], [%1, {%3, %4, %5}], [%2];\n}" ::"r"(dst), "l"(m), "r"(bar), "r"(c0), "r"(c1), "r"(c2) : "memory");
}
__device__ __forceinline__ void w_prefetch(const void* src, uint32_t bytes) {
  asm volatile("{\n.reg .pred p;\nelect.sync _|p, 0xffffffff;\n@p cp.async.bulk.prefetch.L2.global [%0], %1;\n}" ::"l"(src), "r"(bytes) : "memory");
}
__device__ __forceinline__ void nb_sync(int id, int n) { asm volatile("bar.sync %0, %1;" ::"r"(id), "r"(n) : "memory"); }
__device__ __forceinline__ void nb_arrive(int id, int n) { asm volatile("bar.arrive %0, %1;" ::"r"(id), "r"(n) : "memory"); }
__device__ __forceinline__ void fence_async_smem() { asm volatile("fence.proxy.async.shared::cta;" ::: "memory"); }
__device__ __forceinline__ void fence_async_glob() { asm volatile("fence.proxy.async.global;" ::: "memory"); }
__device__ __forceinline__ void flag_after(void* p, uint32_t readback, uint32_t T, bool writer) {
  asm volatile("{\n.reg .pred p;\n.reg .u32 v;\nsetp.ne.u32 p, %3, 0;\nor.b32 v, %1, %2;\nmin.u32 v, v, %2;\n@p st.relaxed.gpu.global.u32 [%0], v;\n}"
               ::"l"(p), "r"(readback), "r"(T), "r"((uint32_t)writer) : "memory");
}
__device__ __forceinline__ uint4 ldg_rlx128(const void* p) { uint4 v; asm volatile("ld.relaxed.gpu.global.v4.b32 {%0,%1,%2,%3}, [%4];" : "=r"(v.x), "=r"(v.y), "=r"(v.z), "=r"(v.w) : "l"(p) : "memory"); return v; }
__device__ __forceinline__ uint2 ldg_rlx64(const void* p) { uint2 v; asm volatile("ld.relaxed.gpu.global.v2.b32 {%0,%1}, [%2];" : "=r"(v.x), "=r"(v.y) : "l"(p) : "memory"); return v; }
__device__ __forceinline__ void rld128(uint4& v, const void* p) { asm volatile("ld.relaxed.gpu.global.v4.b32 {%0,%1,%2,%3}, [%4];" : "+r"(v.x), "+r"(v.y), "+r"(v.z), "+r"(v.w) : "l"(p) : "memory"); }
__device__ __forceinline__ uint32_t ldg_rlx32(const void* p) { uint32_t v; asm volatile("ld.relaxed.gpu.global.b32 %0, [%1];" : "=r"(v) : "l"(p) : "memory"); return v; }
#define NC_HINT ""
__device__ __forceinline__ uint4 ldg_nc128(const void* p) { uint4 v; asm volatile("ld.global.nc" NC_HINT ".v4.b32 {%0,%1,%2,%3}, [%4];" : "=r"(v.x), "=r"(v.y), "=r"(v.z), "=r"(v.w) : "l"(p)); return v; }
#define WD_HINT ".nc.L1::no_allocate"
__device__ __forceinline__ uint4 ldg_wd128(const void* p) { uint4 v; asm volatile("ld.global" WD_HINT ".v4.b32 {%0,%1,%2,%3}, [%4];" : "=r"(v.x), "=r"(v.y), "=r"(v.z), "=r"(v.w) : "l"(p)); return v; }
__device__ __forceinline__ uint32_t ldg_nc32(const void* p) { uint32_t v; asm volatile("ld.global.nc.L1::no_allocate.b32 %0, [%1];" : "=r"(v) : "l"(p)); return v; }
__device__ __forceinline__ void stg128(void* p, uint32_t a, uint32_t b, uint32_t c, uint32_t d) { asm volatile("st.relaxed.gpu.global.v4.b32 [%0], {%1,%2,%3,%4};" ::"l"(p), "r"(a), "r"(b), "r"(c), "r"(d) : "memory"); }
__device__ __forceinline__ void stg64(void* p, uint32_t a, uint32_t b) { asm volatile("st.relaxed.gpu.global.v2.b32 [%0], {%1,%2};" ::"l"(p), "r"(a), "r"(b) : "memory"); }
__device__ __forceinline__ void stg32(void* p, uint32_t a) { asm volatile("st.relaxed.gpu.global.b32 [%0], %1;" ::"l"(p), "r"(a) : "memory"); }
__device__ __forceinline__ void sts128(uint32_t a, uint32_t x, uint32_t y, uint32_t z, uint32_t w) { asm volatile("st.shared.v4.b32 [%0], {%1,%2,%3,%4};" ::"r"(a), "r"(x), "r"(y), "r"(z), "r"(w) : "memory"); }
__device__ __forceinline__ void sts64(uint32_t a, uint32_t x, uint32_t y) { asm volatile("st.shared.v2.b32 [%0], {%1,%2};" ::"r"(a), "r"(x), "r"(y) : "memory"); }
__device__ __forceinline__ void sts32(uint32_t a, uint32_t x) { asm volatile("st.shared.b32 [%0], %1;" ::"r"(a), "r"(x) : "memory"); }
__device__ __forceinline__ void stsf(uint32_t a, float x) { sts32(a, __float_as_uint(x)); }
__device__ __forceinline__ uint4 lds128(uint32_t a) { uint4 v; asm volatile("ld.shared.v4.b32 {%0,%1,%2,%3}, [%4];" : "=r"(v.x), "=r"(v.y), "=r"(v.z), "=r"(v.w) : "r"(a) : "memory"); return v; }
__device__ __forceinline__ uint2 lds64(uint32_t a) { uint2 v; asm volatile("ld.shared.v2.b32 {%0,%1}, [%2];" : "=r"(v.x), "=r"(v.y) : "r"(a) : "memory"); return v; }
__device__ __forceinline__ uint32_t lds32(uint32_t a) { uint32_t v; asm volatile("ld.shared.b32 %0, [%1];" : "=r"(v) : "r"(a) : "memory"); return v; }
__device__ __forceinline__ uint32_t pack_bf16(float lo, float hi) { uint32_t r; asm("cvt.rn.bf16x2.f32 %0, %1, %2;" : "=r"(r) : "f"(hi), "f"(lo)); return r; }
__device__ __forceinline__ float bf_lo(uint32_t w) { return __uint_as_float(w << 16); }
__device__ __forceinline__ float bf_hi(uint32_t w) { return __uint_as_float(w & 0xFFFF0000u); }
__device__ __forceinline__ float rbf(float x) { return bf_lo(pack_bf16(x, 0.f)); }
__device__ __forceinline__ float asf(uint32_t u) { return __uint_as_float(u); }
__device__ __forceinline__ uint32_t asu(float f) { return __float_as_uint(f); }
__device__ __forceinline__ float shx(float v, int m) { return __shfl_xor_sync(0xffffffffu, v, m); }
__device__ __forceinline__ uint32_t movm(uint32_t a) { uint32_t o; asm volatile("movmatrix.sync.aligned.m8n8.trans.b16 %0, %1;" : "=r"(o) : "r"(a)); return o; }
__device__ __forceinline__ void ldsm2(uint32_t& a, uint32_t& b, uint32_t addr) { asm volatile("ldmatrix.sync.aligned.m8n8.x2.shared.b16 {%0,%1}, [%2];" : "=r"(a), "=r"(b) : "r"(addr) : "memory"); }
__device__ __forceinline__ void ldsm4t(uint32_t* r, uint32_t addr) { asm volatile("ldmatrix.sync.aligned.m8n8.x4.trans.shared.b16 {%0,%1,%2,%3}, [%4];" : "=r"(r[0]), "=r"(r[1]), "=r"(r[2]), "=r"(r[3]) : "r"(addr) : "memory"); }
__device__ __forceinline__ void stsm4(uint32_t addr, uint32_t a, uint32_t b, uint32_t c, uint32_t d) { asm volatile("stmatrix.sync.aligned.m8n8.x4.shared.b16 [%0], {%1,%2,%3,%4};" ::"r"(addr), "r"(a), "r"(b), "r"(c), "r"(d) : "memory"); }
__device__ __forceinline__ void stsm2(uint32_t addr, uint32_t a, uint32_t b) { asm volatile("stmatrix.sync.aligned.m8n8.x2.shared.b16 [%0], {%1,%2};" ::"r"(addr), "r"(a), "r"(b) : "memory"); }
__device__ __forceinline__ void mma16(float* d, uint32_t a0, uint32_t a1, uint32_t a2, uint32_t a3, uint32_t b0, uint32_t b1) {
  asm volatile("mma.sync.aligned.m16n8k16.row.col.f32.bf16.bf16.f32 {%0,%1,%2,%3},{%4,%5,%6,%7},{%8,%9},{%0,%1,%2,%3};"
               : "+f"(d[0]), "+f"(d[1]), "+f"(d[2]), "+f"(d[3]) : "r"(a0), "r"(a1), "r"(a2), "r"(a3), "r"(b0), "r"(b1));
}
__device__ __forceinline__ void mma16z(float* d, uint32_t a0, uint32_t a1, uint32_t a2, uint32_t a3, uint32_t b0, uint32_t b1) {
  asm volatile("mma.sync.aligned.m16n8k16.row.col.f32.bf16.bf16.f32 {%0,%1,%2,%3},{%4,%5,%6,%7},{%8,%9},{%10,%10,%10,%10};"
               : "=f"(d[0]), "=f"(d[1]), "=f"(d[2]), "=f"(d[3]) : "r"(a0), "r"(a1), "r"(a2), "r"(a3), "r"(b0), "r"(b1), "f"(0.f));
}
__device__ __forceinline__ void mma8(float* d, uint32_t a0, uint32_t a1, uint32_t b0) {
  asm volatile("mma.sync.aligned.m16n8k8.row.col.f32.bf16.bf16.f32 {%0,%1,%2,%3},{%4,%5},{%6},{%0,%1,%2,%3};"
               : "+f"(d[0]), "+f"(d[1]), "+f"(d[2]), "+f"(d[3]) : "r"(a0), "r"(a1), "r"(b0));
}
__device__ __forceinline__ uint32_t pin(uint32_t v) { uint32_t r; asm volatile("shfl.sync.bfly.b32 %0, %1, 0, 31, 0xffffffff;" : "=r"(r) : "r"(v)); return r; }
__device__ __forceinline__ uint32_t pin0(uint32_t v) { uint32_t r; asm volatile("{\n.reg .u32 t;\nor.b32 t, %1, 1;\nbfind.shiftamt.u32 %0, t;\nshr.u32 %0, %0, 5;\n}" : "=r"(r) : "r"(v)); return r; }
__device__ __forceinline__ void mma8z(float* d, uint32_t a0, uint32_t a1, uint32_t b0) {
  asm volatile("mma.sync.aligned.m16n8k8.row.col.f32.bf16.bf16.f32 {%0,%1,%2,%3},{%4,%5},{%6},{%7,%7,%7,%7};"
               : "=f"(d[0]), "=f"(d[1]), "=f"(d[2]), "=f"(d[3]) : "r"(a0), "r"(a1), "r"(b0), "f"(0.f));
}
__device__ __forceinline__ void wg_fence() { asm volatile("wgmma.fence.sync.aligned;" ::: "memory"); }
__device__ __forceinline__ void wg_commit() { asm volatile("wgmma.commit_group.sync.aligned;" ::: "memory"); }
template <int N> __device__ __forceinline__ void wg_wait() { asm volatile("wgmma.wait_group.sync.aligned %0;" ::"n"(N) : "memory"); }
template <int N> __device__ __forceinline__ void fence_regs(float* d) {
#pragma unroll
  for (int k = 0; k < N; k++) asm volatile("" : "+f"(d[k])::"memory");
}
__host__ __device__ constexpr uint32_t DLO(uint32_t addr, uint32_t lbo) { return (addr >> 4) | ((lbo >> 4) << 16); }
__host__ __device__ constexpr uint32_t DHI(uint32_t sbo, uint32_t swz) { return (sbo >> 4) | (swz << 30); }
template <int N>
__device__ __forceinline__ void wait_flags(const void* base, const uint32_t V, const int lane) {
  const unsigned char* p = (const unsigned char*)base + lane * 32;
  const unsigned char* p2 = p + (lane < N - 32 ? 1024 : 0);
  uint32_t a0 = ldg_rlx32(p), a1 = N > 32 ? ldg_rlx32(p2) : V;
  __nanosleep(POLL_GAP);
  int n = 0;
#pragma unroll 1
  while (true) {
    const uint32_t b0 = ldg_rlx32(p), b1 = N > 32 ? ldg_rlx32(p2) : V;
    if (__all_sync(0xffffffffu, (int)((a0 - V) | (a1 - V)) >= 0)) break;
    a0 = ldg_rlx32(p); a1 = N > 32 ? ldg_rlx32(p2) : V;
    if (__all_sync(0xffffffffu, (int)((b0 - V) | (b1 - V)) >= 0)) break;
    if (++n > SPIN) TIMEOUT(__LINE__)
  }
}
__device__ __forceinline__ uint32_t ftag(float v, uint32_t par) { return (asu(v) & ~1u) | par; }
__device__ __forceinline__ uint32_t selu(uint32_t c, uint32_t a, uint32_t b) { uint32_t r; asm("{\n.reg .pred p;\nsetp.ne.u32 p, %1, 0;\nselp.b32 %0, %2, %3, p;\n}" : "=r"(r) : "r"(c), "r"(a), "r"(b)); return r; }
__device__ __forceinline__ float self(uint32_t c, float a, float b) { return asf(selu(c, asu(a), asu(b))); }
__device__ __forceinline__ uint32_t orx(uint32_t acc, uint32_t a, uint32_t ref) { uint32_t r; asm("lop3.b32 %0, %1, %2, %3, 0xF6;" : "=r"(r) : "r"(acc), "r"(a), "r"(ref)); return r; }
__device__ __forceinline__ uint32_t fkey(float r) {
  uint32_t u = asu(r);
  u = (u & 0x80000000u) ? ~u : (u | 0x80000000u);
  return (r == r) ? u : 0u;
}
__host__ __device__ constexpr int GI(int part, int t) { return t < 8 ? part * 8 + t : 24 + part; }

__device__ __forceinline__ void wgmma_ss_216(float* d, uint32_t al, uint32_t ah, uint32_t bl, uint32_t bh) {
  asm volatile("{\n.reg .b64 da, db;\nmov.b64 da, {%108, %109};\nmov.b64 db, {%110, %111};\n"
      "wgmma.mma_async.sync.aligned.m64n216k16.f32.bf16.bf16 {"
      "%0,%1,%2,%3,%4,%5,%6,%7,%8,%9,%10,%11,%12,%13,%14,%15,%16,%17,%18,%19,%20,%21,%22,%23,%24,%25,%26,"
      "%27,%28,%29,%30,%31,%32,%33,%34,%35,%36,%37,%38,%39,%40,%41,%42,%43,%44,%45,%46,%47,%48,%49,%50,%51,%52,%53,"
      "%54,%55,%56,%57,%58,%59,%60,%61,%62,%63,%64,%65,%66,%67,%68,%69,%70,%71,%72,%73,%74,%75,%76,%77,%78,%79,%80,"
      "%81,%82,%83,%84,%85,%86,%87,%88,%89,%90,%91,%92,%93,%94,%95,%96,%97,%98,%99,%100,%101,%102,%103,%104,%105,%106,%107"
      "}, da, db, 1, 1, 1, 0, 1;\n}\n"
      : "+f"(d[0]), "+f"(d[1]), "+f"(d[2]), "+f"(d[3]), "+f"(d[4]), "+f"(d[5]), "+f"(d[6]), "+f"(d[7]), "+f"(d[8]),
        "+f"(d[9]), "+f"(d[10]), "+f"(d[11]), "+f"(d[12]), "+f"(d[13]), "+f"(d[14]), "+f"(d[15]), "+f"(d[16]), "+f"(d[17]),
        "+f"(d[18]), "+f"(d[19]), "+f"(d[20]), "+f"(d[21]), "+f"(d[22]), "+f"(d[23]), "+f"(d[24]), "+f"(d[25]), "+f"(d[26]),
        "+f"(d[27]), "+f"(d[28]), "+f"(d[29]), "+f"(d[30]), "+f"(d[31]), "+f"(d[32]), "+f"(d[33]), "+f"(d[34]), "+f"(d[35]),
        "+f"(d[36]), "+f"(d[37]), "+f"(d[38]), "+f"(d[39]), "+f"(d[40]), "+f"(d[41]), "+f"(d[42]), "+f"(d[43]), "+f"(d[44]),
        "+f"(d[45]), "+f"(d[46]), "+f"(d[47]), "+f"(d[48]), "+f"(d[49]), "+f"(d[50]), "+f"(d[51]), "+f"(d[52]), "+f"(d[53]),
        "+f"(d[54]), "+f"(d[55]), "+f"(d[56]), "+f"(d[57]), "+f"(d[58]), "+f"(d[59]), "+f"(d[60]), "+f"(d[61]), "+f"(d[62]),
        "+f"(d[63]), "+f"(d[64]), "+f"(d[65]), "+f"(d[66]), "+f"(d[67]), "+f"(d[68]), "+f"(d[69]), "+f"(d[70]), "+f"(d[71]),
        "+f"(d[72]), "+f"(d[73]), "+f"(d[74]), "+f"(d[75]), "+f"(d[76]), "+f"(d[77]), "+f"(d[78]), "+f"(d[79]), "+f"(d[80]),
        "+f"(d[81]), "+f"(d[82]), "+f"(d[83]), "+f"(d[84]), "+f"(d[85]), "+f"(d[86]), "+f"(d[87]), "+f"(d[88]), "+f"(d[89]),
        "+f"(d[90]), "+f"(d[91]), "+f"(d[92]), "+f"(d[93]), "+f"(d[94]), "+f"(d[95]), "+f"(d[96]), "+f"(d[97]), "+f"(d[98]),
        "+f"(d[99]), "+f"(d[100]), "+f"(d[101]), "+f"(d[102]), "+f"(d[103]), "+f"(d[104]), "+f"(d[105]), "+f"(d[106]), "+f"(d[107])
      : "r"(al), "r"(ah), "r"(bl), "r"(bh));
}
__device__ __forceinline__ void wgmma_ss_72(float* d, uint32_t al, uint32_t ah, uint32_t bl, uint32_t bh) {
  asm volatile("{\n.reg .b64 da, db;\nmov.b64 da, {%36, %37};\nmov.b64 db, {%38, %39};\n"
      "wgmma.mma_async.sync.aligned.m64n72k16.f32.bf16.bf16 {"
      "%0,%1,%2,%3,%4,%5,%6,%7,%8,%9,%10,%11,%12,%13,%14,%15,%16,%17,%18,%19,%20,%21,%22,%23,%24,%25,%26,"
      "%27,%28,%29,%30,%31,%32,%33,%34,%35"
      "}, da, db, 1, 1, 1, 0, 1;\n}\n"
      : "+f"(d[0]), "+f"(d[1]), "+f"(d[2]), "+f"(d[3]), "+f"(d[4]), "+f"(d[5]), "+f"(d[6]), "+f"(d[7]), "+f"(d[8]),
        "+f"(d[9]), "+f"(d[10]), "+f"(d[11]), "+f"(d[12]), "+f"(d[13]), "+f"(d[14]), "+f"(d[15]), "+f"(d[16]), "+f"(d[17]),
        "+f"(d[18]), "+f"(d[19]), "+f"(d[20]), "+f"(d[21]), "+f"(d[22]), "+f"(d[23]), "+f"(d[24]), "+f"(d[25]), "+f"(d[26]),
        "+f"(d[27]), "+f"(d[28]), "+f"(d[29]), "+f"(d[30]), "+f"(d[31]), "+f"(d[32]), "+f"(d[33]), "+f"(d[34]), "+f"(d[35])
      : "r"(al), "r"(ah), "r"(bl), "r"(bh));
}
template <uint32_t BH>
__device__ __forceinline__ void wgmma_rs_216(float* d, uint32_t a0, uint32_t a1, uint32_t a2, uint32_t a3, uint32_t bl) {
  asm volatile("{\n.reg .b64 db;\nmov.b64 db, {%112, %113};\n"
      "wgmma.mma_async.sync.aligned.m64n216k16.f32.bf16.bf16 {"
      "%0,%1,%2,%3,%4,%5,%6,%7,%8,%9,%10,%11,%12,%13,%14,%15,%16,%17,%18,%19,%20,%21,%22,%23,%24,%25,%26,"
      "%27,%28,%29,%30,%31,%32,%33,%34,%35,%36,%37,%38,%39,%40,%41,%42,%43,%44,%45,%46,%47,%48,%49,%50,%51,%52,%53,"
      "%54,%55,%56,%57,%58,%59,%60,%61,%62,%63,%64,%65,%66,%67,%68,%69,%70,%71,%72,%73,%74,%75,%76,%77,%78,%79,%80,"
      "%81,%82,%83,%84,%85,%86,%87,%88,%89,%90,%91,%92,%93,%94,%95,%96,%97,%98,%99,%100,%101,%102,%103,%104,%105,%106,%107"
      "}, {%108,%109,%110,%111}, db, 1, 1, 1, 1;\n}\n"
      : "+f"(d[0]), "+f"(d[1]), "+f"(d[2]), "+f"(d[3]), "+f"(d[4]), "+f"(d[5]), "+f"(d[6]), "+f"(d[7]), "+f"(d[8]),
        "+f"(d[9]), "+f"(d[10]), "+f"(d[11]), "+f"(d[12]), "+f"(d[13]), "+f"(d[14]), "+f"(d[15]), "+f"(d[16]), "+f"(d[17]),
        "+f"(d[18]), "+f"(d[19]), "+f"(d[20]), "+f"(d[21]), "+f"(d[22]), "+f"(d[23]), "+f"(d[24]), "+f"(d[25]), "+f"(d[26]),
        "+f"(d[27]), "+f"(d[28]), "+f"(d[29]), "+f"(d[30]), "+f"(d[31]), "+f"(d[32]), "+f"(d[33]), "+f"(d[34]), "+f"(d[35]),
        "+f"(d[36]), "+f"(d[37]), "+f"(d[38]), "+f"(d[39]), "+f"(d[40]), "+f"(d[41]), "+f"(d[42]), "+f"(d[43]), "+f"(d[44]),
        "+f"(d[45]), "+f"(d[46]), "+f"(d[47]), "+f"(d[48]), "+f"(d[49]), "+f"(d[50]), "+f"(d[51]), "+f"(d[52]), "+f"(d[53]),
        "+f"(d[54]), "+f"(d[55]), "+f"(d[56]), "+f"(d[57]), "+f"(d[58]), "+f"(d[59]), "+f"(d[60]), "+f"(d[61]), "+f"(d[62]),
        "+f"(d[63]), "+f"(d[64]), "+f"(d[65]), "+f"(d[66]), "+f"(d[67]), "+f"(d[68]), "+f"(d[69]), "+f"(d[70]), "+f"(d[71]),
        "+f"(d[72]), "+f"(d[73]), "+f"(d[74]), "+f"(d[75]), "+f"(d[76]), "+f"(d[77]), "+f"(d[78]), "+f"(d[79]), "+f"(d[80]),
        "+f"(d[81]), "+f"(d[82]), "+f"(d[83]), "+f"(d[84]), "+f"(d[85]), "+f"(d[86]), "+f"(d[87]), "+f"(d[88]), "+f"(d[89]),
        "+f"(d[90]), "+f"(d[91]), "+f"(d[92]), "+f"(d[93]), "+f"(d[94]), "+f"(d[95]), "+f"(d[96]), "+f"(d[97]), "+f"(d[98]),
        "+f"(d[99]), "+f"(d[100]), "+f"(d[101]), "+f"(d[102]), "+f"(d[103]), "+f"(d[104]), "+f"(d[105]), "+f"(d[106]), "+f"(d[107])
      : "r"(a0), "r"(a1), "r"(a2), "r"(a3), "r"(bl), "n"(BH));
}

struct Ctx {
  int i, j, cta;
};
#define TSTAMP(k) do {} while (0)
#define PSTAMP(k) do {} while (0)
#define PROF_DUMP() do {} while (0)
#define PROF_END() do {} while (0)
#define GSTAMP(k) do {} while (0)
#define CSTAMP(k) STAMPIF(1, L * 40 + p * 20 + (k))

__device__ __forceinline__ int ffn_c32(int cta) { return 32 * cta; }
__device__ __forceinline__ int ffn_c8(int cta) { return 4096 + 8 * (cta >> 1); }
__device__ __forceinline__ void load_gu(const Params& P, const int cta_, const int mat, const int b, const uint32_t bar) {
  const int cta = cta_;
  w_tma2d(sb + SM_G + mat * 46080 + b * 6144, &P.mg + mat, ffn_c32(cta), b * 96, bar);
  if (cta & 1) w_tma2d(sb + SM_G + mat * 46080 + 36864 + b * 1536, &P.mg8 + mat, ffn_c8(cta), b * 96, bar);
}

struct Winner { float r, m, rstd; int ci, rr; };

__device__ __forceinline__ Winner poll_winner(const void* p, uint4 v, const uint32_t tg) {
  int n = 0;
#pragma unroll 1
  while (!__all_sync(0xffffffffu, ((v.y ^ (tg << 6)) >> 6) == 0)) {
    rld128(v, p);
    if (++n > SPIN) TIMEOUT(__LINE__)
  }
  uint32_t key = fkey(asf(v.x));
  uint32_t mx = __reduce_max_sync(0xffffffffu, key);
  int src = __ffs(__ballot_sync(0xffffffffu, key == mx)) - 1;
  Winner w;
  w.ci = src;
  w.r = asf(__shfl_sync(0xffffffffu, v.x, src));
  w.rr = (int)__shfl_sync(0xffffffffu, v.y, src) & 63;
  w.m = asf(__shfl_sync(0xffffffffu, v.z, src));
  w.rstd = asf(__shfl_sync(0xffffffffu, v.w, src));
  return w;
}

__device__ __forceinline__ float2 row_stats(const Params& P, const int r, const int lane) {
  const unsigned char* src = (const unsigned char*)P.x + (((r & ~127) + 2 * (r & 63) + ((r >> 6) & 1)) * 1152 + (lane & 15) * 16);
  uint4 v[4];
#pragma unroll
  for (int m = 0; m < 4; m++) v[m] = ldg_nc128(src + m * 256);
  uint2 v4;
  asm volatile("ld.global.nc.v2.b32 {%0,%1}, [%2];" : "=r"(v4.x), "=r"(v4.y) : "l"(src + (1024 - (lane & 15) * 8)));
  nb_arrive(NB_START, 288 + pin0(v4.x));
  const float sft = __shfl_sync(0xffffffffu, bf_lo(v[0].x), lane & 16);
  float s1 = 0.f, s2 = 0.f, s3 = 0.f;
#pragma unroll
  for (int e = 0; e < 18; e++) {
    const uint32_t u = e < 16 ? (&v[0].x)[e] : (&v4.x)[e - 16];
    const float d0 = bf_lo(u) - sft, d1 = bf_hi(u) - sft;
    s1 += d0 + d1; s2 = fmaf(d0, d0, s2); s3 = fmaf(d1, d1, s3);
  }
  s2 += s3;
#pragma unroll
  for (int o = 1; o < 16; o <<= 1) { s1 += shx(s1, o); s2 += shx(s2, o); }
  s1 *= (1.f / 576.f);
  return make_float2(s1 + sft, rsq(fmaxf(s2 * (1.f / 576.f) - s1 * s1, 0.f) + EPS));
}

struct Unit { uint4 v[3]; };
__device__ __forceinline__ Unit unit_load(const unsigned char* src) {
  Unit u;
#pragma unroll
  for (int m = 0; m < 3; m++) u.v[m] = ldg_nc128(src + m * 48);
  return u;
}
__device__ __forceinline__ uint32_t unit_store(unsigned char* sc, const Unit& u, const int lane, const uint32_t o0, const uint32_t o1, const uint32_t o2) {
  stg128(sc + o0, u.v[0].x, u.v[0].y, u.v[0].z, u.v[0].w);
  stg128(sc + o1, u.v[1].x, u.v[1].y, u.v[1].z, u.v[1].w);
  stg128(sc + o2, u.v[2].x, u.v[2].y, u.v[2].z, u.v[2].w);
  return ldg_rlx32(sc + ((lane & 3) == 0 ? o0 : (lane & 3) == 1 ? o1 : o2));
}

__device__ __forceinline__ void store_rows(const uint32_t stg, unsigned char* obase, const int skip, const int lane) {
#pragma unroll
  for (int m = 0; m < 5; m++) {
    const int e = lane + 32 * m, r = (e * 57) >> 9;
    const uint4 v = lds128(stg + min(e, 143) * 16);
    if (e < 144 && r != skip) *(uint4*)(obase + (r * (2304 - 144) + e * 16)) = v;
  }
}

__device__ __forceinline__ void consumer_role(const Ctx& cx, const Params& P, const unsigned char* smem, const int p, const int w, const int lane_) {
  int lane = lane_;
#define g (lane >> 2)
#define q (lane & 3)
#define first_lane (lane == 0)
  const int i = cx.i, j = cx.j, ip = i * 2 + p;
  unsigned char* const sc = (unsigned char*)P.sc;
  float m_lo = 0.f, m_hi = 0.f, rs_lo = 0.f, rs_hi = 0.f;
  nb_sync(NB_ORD, 384);
  uint32_t T = ldg_rlx32(P.sc->cflag[ip][j * 4 + w]);
  if (X_DELAY) { const int c0 = clock(); while ((int)(clock() - c0) < X_DELAY + (p * 4 + w) * X_STEP) {} }
  {
    const int t = min(w * 32 + lane, 95);
    uint32_t u0 = 0, u1 = 0, u2 = 0, u = 0;
    if (p == 0) {
      u0 = ldg_nc32((const uint32_t*)P.wr + t); u1 = ldg_nc32((const uint32_t*)P.wr + 96 + t); u2 = ldg_nc32((const uint32_t*)P.wr + 192 + t);
      u = ldg_nc32((const uint32_t*)P.wr + 36 * j + min(t, 35));
    }
    const int r = cx.cta * 16 + (p * 4 + w) * 2 + (lane >> 4);
    const float2 st = row_stats(P, r, lane);
    T = __shfl_sync(0xffffffffu, (T >> 3) + 1, 0);
    if ((lane & 15) == 0) stg128(sc + (OFF(st0) + r * 16), asu(st.x), asu(st.y), T, 0u);
    STAMPIF(1, 111);
    if (p == 0) {
      float s = (bf_lo(u0) + bf_hi(u0)) + (bf_lo(u1) + bf_hi(u1)) + (bf_lo(u2) + bf_hi(u2));
#pragma unroll
      for (int o = 1; o < 32; o <<= 1) s += shx(s, o);
      stsf(sb + SM_WR + 288 + w * 4, s);
      sts64(sb + SM_WR + min(t, 35) * 8, u << 16, u & 0xFFFF0000u);
    }
  }
#pragma unroll 1
  for (int L = 0; L < 2; L++) {
    lane = pin(lane);
    const uint32_t tg = 2 * T + L;
    float c_lo = 0.f, c_hi = 0.f;
    bool sel_lo = false, sel_hi = false;
    float acc[108];
#pragma unroll
    for (int k = 0; k < 108; k++) acc[k] = 0.f;
    fence_regs<108>(acc);
    {
      const uint32_t ah = L == 0 ? DHI(1024, 1) : DHI(128, 0);
      const uint32_t astep = L == 0 ? 2 : 128;
      const uint32_t a0 = (L == 0 ? DLO(sb + SM_A, 16) : DLO(sb + SM_A, 1024)) + p * 512;
      constexpr uint32_t bh = DHI(512, 0);
      if (L == 1) {
        const float ul = 1.f + rs_lo, uh = 1.f + rs_hi;
        const float vl = fmaxf(rcp(rs_lo * rs_lo) - EPS, 0.f), vh = fmaxf(rcp(rs_hi * rs_hi) - EPS, 0.f);
        c_lo = ul * rsq(vl * ul * ul + EPS);
        c_hi = uh * rsq(vh * uh * uh + EPS);
      }
      if (L == 1) mbar_wait(sb + BAR_AFULL + p * 8, 0);
      mbar_wait(sb + BAR_FULL, 0);
      if (L == 1) nb_sync(NB_FFN2, 352);
      CSTAMP(0); GSTAMP(120 + 2 * L);
      uint32_t e0 = 0, e1 = 0;
      bool prepped = false, gone = false;
      auto prep_ext = [&]() {
        const int row = p * 64 + w * 16 + g;
        if (L == 0) {
          const uint2 u0 = lds64(sb + SM_R + row * 8), u1 = lds64(sb + SM_R + row * 8 + 64);
          m_lo = asf(u0.x); c_lo = asf(u0.y); m_hi = asf(u1.x); c_hi = asf(u1.y);
        } else {
          const uint4 sv = lds128(sb + SM_SEL);
          sel_lo = (int)sv.x == row; sel_hi = (int)sv.x == row + 8;
          if (sel_lo) { m_lo = asf(sv.z); c_lo = asf(sv.w); }
          if (sel_hi) { m_hi = asf(sv.z); c_hi = asf(sv.w); }
        }
        const float hl = rbf(-m_lo), hh = rbf(-m_hi);
        const uint32_t em = selu(lane & 1, 0x0000FFFFu, 0xFFFFFFFFu);
        e0 = selu(lane & 2, selu(sel_lo && !(lane & 1), 0x3F803F80u, 0u), pack_bf16(hl, -m_lo - hl) & em);
        e1 = selu(lane & 2, selu(sel_hi && !(lane & 1), 0x3F803F80u, 0u), pack_bf16(hh, -m_hi - hh) & em);
      };
      bool pend = false;
#pragma unroll 1
      for (int r = 0; r < 3; r++) {
#pragma unroll
        for (int h = 0; h < 6; h++) {
          const uint32_t al = a0 + (h >> 1) * 1024 + (h & 1) * 2 * astep, bl = DLO(sb + SM_B, 128) + h * 864;
          const uint32_t nb = sb + BAR_FULL + ((h + 1) % 6) * 8, np = (r + (h == 5)) & 1;
          TSTAMP((6 * r + h) * 2);
          wg_fence();
          wgmma_ss_216(acc, al, ah, bl, bh);
          wgmma_ss_216(acc, al + astep, ah, bl + 16, bh);
          wg_commit();
          if (h == 5 && r == 2) break;
          const uint32_t ok = mbar_test(nb, np);
          if ((h == 1 || h == 3) && r == 0 && L == 1) mbar_wait(sb + BAR_AFULL + (h + 1 + p) * 8, 0);
          if (h == 0 && r == 1 && L == 0) {
          if (lane < 16) stg128(sc + (OFF(stats) + (ip * 4 + w) * 2048 + j * 256 + lane * 16), 0u, 0u, 0u, 0u);
          if (w == 3 && i < 15 && lane < 28) {
#pragma unroll
            for (int e = 0; e < 6; e++) stg128(sc + (OFF(halo) + ((ip + 2) * 8 + j) * 2688 + lane * 16) + e * 448, 0u, 0u, 0u, 0u);
          }
          if (w == 0 && lane < 2) stg128(sc + (OFF(cand) + (j * 32 + ip) * (CAND_W * 4) + lane * 16), 0u, 0u, 0u, 0u);
          }
          wg_wait<1>();
          if (first_lane && pend) mbar_arrive(sb + BAR_EMPTY + ((h + 5) % 6) * 8);
          pend = true;
          const bool hold = h == HOLD_C % 6 && r == HOLD_C / 6 && p == 1;
          if (hold || (!ok && !mbar_test(nb, np))) {
            wg_wait<0>();
            if (first_lane) mbar_arrive(sb + BAR_EMPTY + h * 8);
            pend = false;
            TSTAMP((6 * r + h) * 2 + 1);
            mbar_wait(nb, np);
            if (hold) {
              if (mbar_test(sb + BAR_FIX + 8, L)) { prep_ext(); prepped = true; }
              nb_sync(NB_STAG, 256);
            }
          }
        }
      }
      if (!prepped) {
        if (p == 0 && !gone && !mbar_test(sb + BAR_FIX, L)) { nb_arrive(NB_STAG, 256); gone = true; }
        mbar_wait(sb + BAR_FIX + p * 8, L);
        prep_ext();
      }
      wg_fence();
      wgmma_rs_216<DHI(128, 0)>(acc, e0, e1, 0u, 0u, DLO(sb + SM_BEXT, 0));
      wg_commit();
      if (p == 0 && !gone) nb_arrive(NB_STAG, 256);
      wg_wait<2>();
      if (first_lane && pend) mbar_arrive(sb + BAR_EMPTY + 32);
    }
    lane = pin(lane);
    const uint32_t fragoff = ip * 73728 + (9 * j) * 1024 + w * 256 + lane * 4;
    const uint32_t rboff = (min(lane, 17) >> 1) * 1024 + (lane < 18 ? lane & 1 : 0) * 128;
    const uint32_t hl16 = (lane < 4 ? lane : lane - 4) * 16;
    const uint32_t o_halo = pin(OFF(halo) + ((ip + (w == 3 ? 2 : 0)) * 8 + j) * 2688 + hl16);
    const uint32_t o_o = pin(OFF(obuf) + fragoff);
    nb_sync(NB_WG + p, 128);
    if ((o_halo | o_o) == 0xFFFFFFFFu) __trap();
    wg_wait<0>();
    fence_regs<108>(acc);
    if (first_lane) mbar_arrive(sb + BAR_EMPTY + 40);
    CSTAMP(1); GSTAMP(121 + 2 * L);
    {
      uint32_t Kh[9], Vh[9], Kl[9], Vl[9], Kx[9], Vx[9], Ql[9], Qh[9];
#pragma unroll
      for (int t = 0; t < 9; t++) {
        Kh[t] = pack_bf16(acc[4 * GI(1, t) + 2] * c_hi, acc[4 * GI(1, t) + 3] * c_hi);
        Vh[t] = pack_bf16(acc[4 * GI(2, t) + 2] * c_hi, acc[4 * GI(2, t) + 3] * c_hi);
        Ql[t] = pack_bf16(acc[4 * GI(0, t)], acc[4 * GI(0, t) + 1]);
        Qh[t] = pack_bf16(acc[4 * GI(0, t) + 2], acc[4 * GI(0, t) + 3]);
      }
      const uint32_t hbuf = sb + SM_A + p * 8192 + w * 2688 + hl16;
      if (w < 3) {
        if (lane >= 4) {
#pragma unroll
          for (int e = 0; e < 4; e++) sts128(hbuf + e * 448, Kh[2 * e], Kh[2 * e + 1], Vh[e], tg);
          sts128(hbuf + 4 * 448, Kh[8], Vh[4], Vh[5], tg);
          sts128(hbuf + 5 * 448, Vh[6], Vh[7], Vh[8], tg);
        }
      } else if (i < 15 && lane >= 4) {
#pragma unroll
        for (int e = 0; e < 4; e++) stg128(sc + o_halo + e * 448, Kh[2 * e], Kh[2 * e + 1], Vh[e], tg);
        stg128(sc + o_halo + 4 * 448, Kh[8], Vh[4], Vh[5], tg);
        stg128(sc + o_halo + 5 * 448, Vh[6], Vh[7], Vh[8], tg);
      }
      nb_sync(NB_WG + p, 128);
#pragma unroll
      for (int t = 0; t < 9; t++) {
        Kl[t] = pack_bf16(acc[4 * GI(1, t)] * c_lo, acc[4 * GI(1, t) + 1] * c_lo);
      }
      uint32_t dep = (Kl[0] ^ Kl[1] ^ Kl[2]) | (Kl[3] ^ Kl[4] ^ Kl[5]) | (Kl[6] ^ Kl[7] ^ Kl[8]);
      const unsigned char* hp = (w > 0 ? smem + (hbuf - 2688 - sb) : sc + o_halo) + pin0(dep);
      uint4 hv[6];
#pragma unroll
      for (int e = 0; e < 6; e++)
        asm volatile("ld.relaxed.gpu.v4.b32 {%0,%1,%2,%3}, [%4];" : "=r"(hv[e].x), "=r"(hv[e].y), "=r"(hv[e].z), "=r"(hv[e].w) : "l"(hp + e * 448) : "memory");
      CSTAMP(2);
#pragma unroll
      for (int t = 0; t < 9; t++) {
        Vl[t] = pack_bf16(acc[4 * GI(2, t)] * c_lo, acc[4 * GI(2, t) + 1] * c_lo);
        Vl[t] = movm(Vl[t]);
        Vh[t] = movm(Vh[t]);
      }
      uint32_t qa[4][2], qb[4][2];
      float s1[4][4], s2[4][4];
#pragma unroll
      for (int h = 0; h < 4; h++) {
        qa[h][0] = q >= h ? Ql[2 * h] : 0u; qa[h][1] = q >= h ? Qh[2 * h] : 0u;
        qb[h][0] = q <= h ? Ql[2 * h + 2] : 0u; qb[h][1] = q <= h ? Qh[2 * h + 2] : 0u;
      }
      const bool first = (i == 0 && w == 0);
      if (w == 0 && i > 0) {
        int n = 0;
#pragma unroll 1
        while (__any_sync(0xffffffffu, (orx(orx(orx(0, hv[0].w, tg), hv[1].w, tg), hv[2].w, tg) | orx(orx(orx(0, hv[3].w, tg), hv[4].w, tg), hv[5].w, tg)) != 0)) {
#pragma unroll
          for (int e = 0; e < 6; e++) rld128(hv[e], sc + o_halo + e * 448);
          if (++n > SPIN) TIMEOUT(__LINE__)
        }
      }
#pragma unroll
      for (int e = 0; e < 4; e++) { Kx[2 * e] = hv[e].x; Kx[2 * e + 1] = hv[e].y; Vx[e] = hv[e].z; }
      Kx[8] = hv[4].x; Vx[4] = hv[4].y; Vx[5] = hv[4].z; Vx[6] = hv[5].x; Vx[7] = hv[5].y; Vx[8] = hv[5].z;
      CSTAMP(3);
#pragma unroll
      for (int t = 0; t < 9; t++) Vx[t] = movm(Vx[t]);
#pragma unroll
      for (int h = 0; h < 4; h++) { mma8z(s1[h], qb[h][0], qb[h][1], Kl[2 * h + 2]); mma8z(s2[h], qb[h][0], qb[h][1], Kh[2 * h + 2]); }
#pragma unroll
      for (int h = 0; h < 4; h++) {
        mma16(s1[h], qa[h][0], qa[h][1], Ql[2 * h + 1], Qh[2 * h + 1], Kl[2 * h], Kl[2 * h + 1]);
        mma16(s2[h], qa[h][0], qa[h][1], Ql[2 * h + 1], Qh[2 * h + 1], Kh[2 * h], Kh[2 * h + 1]);
      }
      float s0[4][4];
#pragma unroll
      for (int h = 0; h < 4; h++) mma8z(s0[h], qb[h][0], qb[h][1], Kx[2 * h + 2]);
#pragma unroll
      for (int h = 0; h < 4; h++) mma16(s0[h], qa[h][0], qa[h][1], Ql[2 * h + 1], Qh[2 * h + 1], Kx[2 * h], Kx[2 * h + 1]);
      const bool pv0 = 2 * q > g, pv1 = 2 * q + 1 > g;
      const uint32_t PM = (pv0 ? 0x0000FFFFu : 0u) | (pv1 ? 0xFFFF0000u : 0u);
      const float kS = 0.23570226039551584f * 1.4426950408889634f;
      const float sc_lo = c_lo * kS, sc_hi = c_hi * kS;
      float sl[4][2], sh[4][2], ml[4], mh[4];
#pragma unroll
      for (int h = 0; h < 4; h++) {
        sh[h][0] = pv0 ? s1[h][2] : s2[h][2];
        sh[h][1] = pv1 ? s1[h][3] : s2[h][3];
        mh[h] = fmaxf(sh[h][0], sh[h][1]);
        sl[h][0] = pv0 ? (first ? -INFINITY : s0[h][0]) : s1[h][0];
        sl[h][1] = pv1 ? (first ? -INFINITY : s0[h][1]) : s1[h][1];
        ml[h] = fmaxf(sl[h][0], sl[h][1]);
      }
#pragma unroll
      for (int s = 1; s <= 2; s <<= 1) {
        float tl[4], th[4];
#pragma unroll
        for (int h = 0; h < 4; h++) { th[h] = shx(mh[h], s); tl[h] = shx(ml[h], s); }
#pragma unroll
        for (int h = 0; h < 4; h++) { mh[h] = fmaxf(mh[h], th[h]); ml[h] = fmaxf(ml[h], tl[h]); }
      }
      float o[4][3][4], den[4][4];
      uint32_t px[4];
#pragma unroll
      for (int h = 0; h < 4; h++) {
        const float bl = -ml[h] * sc_lo, bh = -mh[h] * sc_hi;
        const uint32_t pl = pack_bf16(ex2(fmaf(sl[h][0], sc_lo, bl)), ex2(fmaf(sl[h][1], sc_lo, bl)));
        const uint32_t ph = pack_bf16(ex2(fmaf(sh[h][0], sc_hi, bh)), ex2(fmaf(sh[h][1], sc_hi, bh)));
        mma8z(den[h], pl, ph, 0x3F803F80u);
        px[h] = pl & PM;
#pragma unroll
        for (int u = 0; u < 3; u++) mma16z(o[h][u], pl & ~PM, ph & PM, 0u, ph & ~PM, Vl[2 * h + u], Vh[2 * h + u]);
      }
#pragma unroll
      for (int h = 0; h < 4; h++)
#pragma unroll
        for (int u = 0; u < 3; u++) mma8(o[h][u], px[h], 0u, Vx[2 * h + u]);
      float il[4], ih[4];
#pragma unroll
      for (int h = 0; h < 4; h++) { il[h] = rcp(den[h][0]); ih[h] = rcp(den[h][2]); }
#pragma unroll
      for (int t = 0; t < 9; t++) {
        const int h = t == 8 ? 3 : t >> 1, u = t == 8 ? 2 : t & 1;
        float v0 = o[h][u][0], v1 = o[h][u][1], v2 = o[h][u][2], v3 = o[h][u][3], kl = il[h], kh = ih[h];
        if (u == 0 && h > 0 && q < h) {
          v0 = o[h - 1][2][0]; v1 = o[h - 1][2][1]; v2 = o[h - 1][2][2]; v3 = o[h - 1][2][3]; kl = il[h - 1]; kh = ih[h - 1];
        }
        stg32(sc + o_o + t * 1024, pack_bf16(v0 * kl, v1 * kl));
        stg32(sc + o_o + t * 1024 + 128, pack_bf16(v2 * kh, v3 * kh));
      }
    }
    CSTAMP(4);
    const uint32_t rbo = ldg_rlx32(sc + (o_o + rboff));
    lane = pin(lane);
    const uint32_t o_x = o_o + (OFF(xbuf) - OFF(obuf)), o_xrb = o_x + rboff;
    const uint32_t o_cf = OFF(cflag) + (ip * 32 + j * 4 + w) * 32 + lane * 4;
    if (L == 1 && first_lane) mbar_arrive(sb + BAR_HDONE + p * 8);
    flag_after(sc + o_cf, rbo, 8 * T + 2 * L, lane < 8);
    STAMPD(asf(rbo), L * 40 + p * 20 + 13);
    uint32_t resid[18];
    mbar_wait(sb + BAR_FULL + 16, 1); mbar_wait(sb + BAR_FULL + 32, 1);
    if (L == 0) {
      const uint32_t ra = sb + SM_A + (2 + p) * 8192 + (w * 16 + (lane & 15)) * 128;
#pragma unroll
      for (int t = 0; t < 9; t++) ldsm2(resid[2 * t], resid[2 * t + 1], ra + ((j + t) >> 3) * 16384 + ((((j + t) ^ lane) & 7) << 4));
      if (first_lane) mbar_arrive(sb + BAR_HDONE + p * 8 + pin0(resid[17]));
    } else {
#pragma unroll
      for (int t = 0; t < 9; t++) { resid[2 * t] = ldg_rlx32(sc + o_x + t * 1024); resid[2 * t + 1] = ldg_rlx32(sc + o_x + t * 1024 + 128); }
    }
    const uint32_t o_st = OFF(stats) + (ip * 4 + w) * 2048;
    const uint32_t o_stw = pin(o_st + j * 256 + (g + 8 * (q & 1)) * 16), o_str = pin(o_st + q * 512 + g * 16);
    const uint32_t o_cand = pin(OFF(cand) + (j * 32 + ip) * (CAND_W * 4) + q * 16);
    const uint32_t o_xc = pin(OFF(xcand) + (ip * 8 + j) * 192 + q * 16);
    float accw[36];
    float wr[18];
#pragma unroll
    for (int t = 0; t < 9; t++) { const uint2 u = lds64(sb + SM_WR + t * 32 + q * 8); wr[2 * t] = asf(u.x); wr[2 * t + 1] = asf(u.y); }
    const uint4 ws4 = lds128(sb + SM_WR + 288);
    const float wsum = asf(pin(asu(asf(ws4.x) + asf(ws4.y) + asf(ws4.z))));
    {
      float ul = 1.f, uh = 1.f, vl = 0.f, vh = 0.f;
      if (L == 1) {
        ul += rs_lo; uh += rs_hi; vl = -m_lo * rs_lo; vh = -m_hi * rs_hi;
        if (sel_lo || sel_hi) {
#pragma unroll
          for (int t = 0; t < 9; t++) {
            const uint32_t z = lds32(sb + SM_X2S + t * 16 + q * 4);
            if (sel_hi) resid[2 * t + 1] = z; else resid[2 * t] = z;
          }
          if (sel_hi) { uh = 1.f; vh = 0.f; } else { ul = 1.f; vl = 0.f; }
        }
        __syncwarp();
      }
#pragma unroll
      for (int t = 0; t < 9; t++) {
        accw[4 * t] = fmaf(bf_lo(resid[2 * t]), ul, vl); accw[4 * t + 1] = fmaf(bf_hi(resid[2 * t]), ul, vl);
        accw[4 * t + 2] = fmaf(bf_lo(resid[2 * t + 1]), uh, vh); accw[4 * t + 3] = fmaf(bf_hi(resid[2 * t + 1]), uh, vh);
      }
    }
    fence_regs<36>(accw);
    mbar_wait(sb + BAR_FULL, 1); mbar_wait(sb + BAR_FULL + 8, 1); mbar_wait(sb + BAR_FULL + 24, 1); mbar_wait(sb + BAR_FULL + 40, 1);
    {
      uint32_t wf = sb + BAR_WFULL + p * 72;
      uint32_t bl = DLO(sb + SM_B, 128);
      uint32_t half = p;
      mbar_wait(wf, L);
      CSTAMP(5);
#pragma unroll 1
      for (int c3 = 0; c3 < 3; c3++) {
        const uint32_t al = DLO(sb + SM_A, 1024) + half * 512;
        const uint32_t ae = sb + BAR_AEMPTY + half * 24;
#pragma unroll
        for (int cc = 0; cc < 3; cc++) {
          TSTAMP(36 + (c3 * 3 + cc) * 2);
          wg_fence();
          wgmma_ss_72(accw, al + cc * 1024, DHI(128, 0), bl + cc * 576, DHI(256, 0));
          wgmma_ss_72(accw, al + cc * 1024 + 128, DHI(128, 0), bl + cc * 576 + 144, DHI(256, 0));
          const uint32_t ok = mbar_test(wf + cc * 8 + 8, L);
          wgmma_ss_72(accw, al + cc * 1024 + 256, DHI(128, 0), bl + cc * 576 + 288, DHI(256, 0));
          wgmma_ss_72(accw, al + cc * 1024 + 384, DHI(128, 0), bl + cc * 576 + 432, DHI(256, 0));
          wg_commit();
          wg_wait<1>();
          if (cc > 0) { if (first_lane) { mbar_arrive(ae + cc * 8 - 8); if (cc == 2) mbar_arrive(sb + BAR_EMPTY + c3 * 16); } }
          else if (first_lane && c3 > 0) { mbar_arrive(sb + BAR_AEMPTY + 40 - half * 24); mbar_arrive(sb + BAR_EMPTY + c3 * 16 - 8); }
          if (!ok && (cc < 2 || c3 < 2)) mbar_wait(wf + cc * 8 + 8, L);
        }
        wf += 24; bl += 1728; half ^= 1;
      }
    }
    wg_wait<0>();
    fence_regs<36>(accw);
    if (first_lane) { mbar_arrive(sb + BAR_AEMPTY + (2 + 3 * p) * 8); mbar_arrive(sb + BAR_EMPTY + 40); }
    CSTAMP(6);
    uint32_t xw[18];
    uint32_t rb = 0;
    if (L == 0 && p == 0) {
#pragma unroll
      for (int t = 0; t < 9; t++) {
        stg32(sc + o_x + t * 1024, pack_bf16(accw[4 * t], accw[4 * t + 1]));
        stg32(sc + o_x + t * 1024 + 128, pack_bf16(accw[4 * t + 2], accw[4 * t + 3]));
      }
      rb = ldg_rlx32(sc + o_xrb);
      fence_regs<36>(accw);
    }
    {
      float a0[2] = {0.f, 0.f}, a1[2] = {0.f, 0.f}, a2[2] = {0.f, 0.f}, b0[2] = {0.f, 0.f}, b1[2] = {0.f, 0.f}, b2[2] = {0.f, 0.f};
#pragma unroll
      for (int t = 0; t < 9; t++) {
#pragma unroll
        for (int e = 0; e < 2; e++) {
          const float x = accw[4 * t + e], y = accw[4 * t + 2 + e];
          a0[e] += x; a1[e] = fmaf(x, x, a1[e]); a2[e] = fmaf(x, wr[2 * t + e], a2[e]);
          b0[e] += y; b1[e] = fmaf(y, y, b1[e]); b2[e] = fmaf(y, wr[2 * t + e], b2[e]);
        }
      }
      const bool od = q & 1;
      const float A0 = a0[0] + a0[1], A1 = a1[0] + a1[1], A2 = a2[0] + a2[1], B0 = b0[0] + b0[1], B1 = b1[0] + b1[1], B2 = b2[0] + b2[1];
      float k0 = od ? B0 : A0, k1 = od ? B1 : A1, k2 = od ? B2 : A2;
      k0 += shx(od ? A0 : B0, 1); k1 += shx(od ? A1 : B1, 1); k2 += shx(od ? A2 : B2, 1);
      k0 += shx(k0, 2); k1 += shx(k1, 2); k2 += shx(k2, 2);
      if (q < 2) stg128(sc + o_stw, asu(k0), asu(k1), asu(k2), tg);
      STAMPD(k0, L * 40 + p * 20 + 14);
    }
#pragma unroll
    for (int t = 0; t < 9; t++) {
      xw[2 * t] = pack_bf16(accw[4 * t], accw[4 * t + 1]);
      xw[2 * t + 1] = pack_bf16(accw[4 * t + 2], accw[4 * t + 3]);
    }
    float r_lo, r_hi;
    {
      if (D_STATS) { const int c0 = clock(); while ((int)(clock() - c0) < D_STATS) {} }
      uint4 u0 = ldg_rlx128(sc + o_str), u1 = ldg_rlx128(sc + o_str + 256), u2 = ldg_rlx128(sc + o_str + 128), u3 = ldg_rlx128(sc + o_str + 384);
      flag_after(sc + o_cf, rb, 8 * T + 1, lane < 8 && L == 0 && p == 0);
      STAMPD(asf(u3.w), L * 40 + p * 20 + 15);
      int n = 0;
#pragma unroll 1
      while (__any_sync(0xffffffffu, orx(orx(orx(orx(0, u0.w, tg), u1.w, tg), u2.w, tg), u3.w, tg) != 0)) {
        rld128(u0, sc + o_str); rld128(u1, sc + o_str + 256); rld128(u2, sc + o_str + 128); rld128(u3, sc + o_str + 384);
        if (++n > SPIN) TIMEOUT(__LINE__)
      }
      float a0 = asf(u0.x) + asf(u1.x), a1 = asf(u0.y) + asf(u1.y), a2 = asf(u0.z) + asf(u1.z);
      float b0 = asf(u2.x) + asf(u3.x), b1 = asf(u2.y) + asf(u3.y), b2 = asf(u2.z) + asf(u3.z);
#pragma unroll
      for (int s = 1; s <= 2; s <<= 1) {
        const float t0 = shx(a0, s), t1 = shx(a1, s), t2 = shx(a2, s), t3 = shx(b0, s), t4 = shx(b1, s), t5 = shx(b2, s);
        a0 += t0; a1 += t1; a2 += t2; b0 += t3; b1 += t4; b2 += t5;
      }
      m_lo = a0 * (1.f / 576.f); m_hi = b0 * (1.f / 576.f);
      rs_lo = rsq(fmaxf(a1 * (1.f / 576.f) - m_lo * m_lo, 0.f) + EPS);
      rs_hi = rsq(fmaxf(b1 * (1.f / 576.f) - m_hi * m_hi, 0.f) + EPS);
      r_lo = (a2 - m_lo * wsum) * rs_lo; r_hi = (b2 - m_hi * wsum) * rs_hi;
    }
    CSTAMP(7);
    int candrow = -1;
    {
      const uint32_t kl = fkey(r_lo), kh = fkey(r_hi);
      const bool hi = kh > kl;
      const uint32_t kb = hi ? kh : kl;
      const uint32_t mx = __reduce_max_sync(0xffffffffu, kb);
      if (first_lane) sts32(sb + SM_BEST + p * 16 + w * 4, mx);
      const uint32_t bal = __ballot_sync(0xffffffffu, kb == mx);
      const bool mine = (bal & ((1u << (lane & 28)) - 1u)) == 0u && kb == mx;
      const uint32_t x0 = hi ? xw[1] : xw[0], x1 = hi ? xw[3] : xw[2], x2 = hi ? xw[5] : xw[4], x3 = hi ? xw[7] : xw[6], x4 = hi ? xw[9] : xw[8];
      const uint32_t x5 = hi ? xw[11] : xw[10], x6 = hi ? xw[13] : xw[12], x7 = hi ? xw[15] : xw[14], x8 = hi ? xw[17] : xw[16];
      nb_sync(NB_WG + p, 128);
      const uint4 bs = lds128(sb + SM_BEST + p * 16);
      const bool best = (w > 0 ? bs.x < mx : true) && (w > 1 ? bs.y < mx : bs.y <= mx) && (w > 2 ? bs.z < mx : bs.z <= mx) && bs.w <= mx;
      if (best && mine) {
        if (q < 2) stg128(sc + o_cand, asu(hi ? r_hi : r_lo), (tg << 6) + (uint32_t)(w * 16 + g + (hi ? 8 : 0)), asu(hi ? m_hi : m_lo), asu(hi ? rs_hi : rs_lo));
        stg128(sc + o_xc, x0, x1, x2, tg);
        stg128(sc + o_xc + 64, x3, x4, x5, tg);
        stg128(sc + o_xc + 128, x6, x7, x8, tg);
      }
      candrow = __reduce_max_sync(0xffffffffu, best && mine ? g + (hi ? 8 : 0) : -1);
    }
    if (L == 0 && p == 1) {
#pragma unroll
      for (int t = 0; t < 9; t++) { stg32(sc + o_x + t * 1024, xw[2 * t]); stg32(sc + o_x + t * 1024 + 128, xw[2 * t + 1]); }
      rb = ldg_rlx32(sc + o_xrb);
    }
    const uint32_t stg = sb + SM_B + p * 13824 + w * 2304;
    unsigned char* obase = (unsigned char*)P.out + ((128 * i + 32 * w + p) * 1152 + 144 * j);
    if (L == 1) {
      const float ul = 1.f + rs_lo, uh = 1.f + rs_hi, vl = -m_lo * rs_lo, vh = -m_hi * rs_hi;
#pragma unroll
      for (int t = 0; t < 9; t++) {
        xw[2 * t] = pack_bf16(fmaf(accw[4 * t], ul, vl), fmaf(accw[4 * t + 1], ul, vl));
        xw[2 * t + 1] = pack_bf16(fmaf(accw[4 * t + 2], uh, vh), fmaf(accw[4 * t + 3], uh, vh));
      }
      mbar_wait(sb + BAR_EMPTY + p * 8, 1);
      const uint32_t sa = stg + (lane & 15) * 144;
#pragma unroll
      for (int t = 0; t < 8; t += 2) stsm4(sa + (lane >> 4) * 16 + t * 16, xw[2 * t], xw[2 * t + 1], xw[2 * t + 2], xw[2 * t + 3]);
      stsm2(sa + 128, xw[16], xw[17]);
      __syncwarp();
      store_rows(stg, obase, candrow, lane);
    }
    CSTAMP(8);
    lane = pin(lane);
    const unsigned char* cp = sc + (OFF(cand) + (j * 32 + lane) * (CAND_W * 4));
    if (p == 0) {
      if (L == 1 && candrow >= 0) {
        const Winner wn = poll_winner(cp, ldg_rlx128(cp), tg);
        if (lane < 9 && wn.ci != ip) *(uint4*)(obase + (candrow * 2304 + lane * 16)) = lds128(stg + candrow * 144 + lane * 16);
      }
    } else {
      const uint32_t gr = w * 144 + (lane & 7) + (lane >> 4) * 8, gm = sb + SM_G + ((lane >> 3) & 1) * 46080;
      const uint32_t ga = gm + gr * 64 + (((lane >> 1) & 3) << 4), gl = gm + 36864 + gr * 16;
#define GADDR(s, u) ((u) < 4 ? (ga ^ ((u) << 4)) + (s) * 1024 : gl + (s) * 256)
      uint32_t wf[NPRE][5][4];
      mbar_wait(sb + BAR_GU, 0);
#pragma unroll
      for (int s = 0; s < NPRE - 2; s++)
#pragma unroll
        for (int u = 0; u < 5; u++) ldsm4t(wf[s][u], GADDR(s, u));
      const uint4 c0 = ldg_rlx128(cp);
#pragma unroll
      for (int s = NPRE - 2; s < NPRE; s++)
#pragma unroll
        for (int u = 0; u < 5; u++) ldsm4t(wf[s][u], GADDR(s, u));
      flag_after(sc + o_cf, rb, 8 * T + 1, lane < 8 && L == 0);
      const Winner wn = poll_winner(cp, c0, tg);
      if (w == 0 && first_lane) sts128(sb + SM_WIN, asu(wn.r), asu(wn.m), asu(wn.rstd), (uint32_t)(wn.ci * 64 + wn.rr));
      CSTAMP(9);
      if (L == 1 && candrow >= 0 && lane < 9 && wn.ci != ip) *(uint4*)(obase + (candrow * 2304 + lane * 16)) = lds128(stg + candrow * 144 + lane * 16);
      {
        uint32_t hb[18];
        const unsigned char* xc = sc + (OFF(xcand) + wn.ci * 1536 + q * 16);
        const int fp = min(cx.cta / 3, 23);
        uint4 u[7];
        int n = 0;
#pragma unroll 1
        while (true) {
          uint32_t d = 0;
#pragma unroll
          for (int e = 0; e < 7; e++) u[e] = ldg_rlx128(xc + (e < 6 ? w * 384 + e * 64 : fp * 64));
#pragma unroll
          for (int e = 0; e < 7; e++) d = orx(d, u[e].w, tg);
          if (__all_sync(0xffffffffu, d == 0)) break;
          if (++n > SPIN) TIMEOUT(__LINE__)
        }
        if (L == 0 && w == 0 && first_lane) mbar_arrive(sb + BAR_ST + pin0(u[0].x));
#pragma unroll
        for (int e = 0; e < 6; e++) { hb[3 * e] = u[e].x; hb[3 * e + 1] = u[e].y; hb[3 * e + 2] = u[e].z; }
        if (w == 0) sts128(sb + SM_XW + q * 16, u[6].x, u[6].y, u[6].z, u[6].w);
        const float nb = -wn.m * wn.rstd;
#pragma unroll
        for (int b = 0; b < 18; b++) hb[b] = pack_bf16(fmaf(bf_lo(hb[b]), wn.rstd, nb), fmaf(bf_hi(hb[b]), wn.rstd, nb));
        CSTAMP(10);
        float d[5][4];
#pragma unroll
        for (int u = 0; u < 5; u++) d[u][0] = d[u][1] = d[u][2] = d[u][3] = 0.f;
#pragma unroll
        for (int s = 0; s < 9; s++) {
#pragma unroll
          for (int u = 0; u < 5; u++) {
            uint32_t* f = wf[s % NPRE][u];
            mma16(d[u], f[0], f[1], f[2], f[3], hb[2 * s], hb[2 * s + 1]);
            if (s + NPRE < 9) ldsm4t(f, GADDR(s + NPRE, u));
          }
        }
        if (q == 0) {
#pragma unroll
          for (int u = 0; u < 5; u++) sts64(sb + R_FPART + w * 320 + (u * 8 + g) * 8, asu(d[u][0]), asu(d[u][2]));
        }
        nb_arrive(NB_FFN, 224);
        CSTAMP(11);
      }
    }
  }
  STAMPIF(w == 0 && lane == 0, 40 + p * 20 + 12);
  PROF_DUMP();
#undef g
#undef q
#undef first_lane
}

__device__ __forceinline__ void load_wo_a(const Ctx& cx, const Params& P, const uint32_t T, const int L, const int p, const int lane) {
  const unsigned char* src = P.sc->obuf[cx.i * 2 + p];
#pragma unroll
  for (int c = 0; c < 9; c++) w_expect(sb + BAR_WFULL + (9 * p + c) * 8, 8192);
  mbar_wait(sb + BAR_HDONE + p * 8, L);
  if (D_OF0 | D_OF1) { const int c0 = clock(); while ((int)(clock() - c0) < (L == 0 ? D_OF0 : D_OF1)) {} }
  wait_flags<32>(P.sc->cflag[cx.i * 2 + p], 8 * T + 2 * L, lane);
  fence_async_glob();
  STAMP(100 + L * 2 + p);
#pragma unroll
  for (int c = 0; c < 9; c++) {
    const int e = 9 * p + c, s = e % 6;
    if (e == 3) mbar_wait(sb + BAR_HDONE + 8, L);
    if (e >= 6) mbar_wait(sb + BAR_AEMPTY + s * 8, (L ^ (e / 6) ^ 1) & 1);
    w_bulk(sb + SM_A + (2 * (s % 3) + s / 3) * 8192, src + c * 8192, 8192, sb + BAR_WFULL + e * 8);
    PSTAMP(48 + L * 36 + 18 + e);
  }
}

__device__ __forceinline__ void finalize_row(const Params& P, const Winner& wn, const uint32_t T, const int L, const int grp, const int a, const int lane) {
  const unsigned char* yp = (const unsigned char*)P.sc->ypart[grp] + (a * 32 + lane) * 16;
  const uint32_t par = L ^ 1;
  if (L == 0 && D_Y0) { const int c0 = clock(); while ((int)(clock() - c0) < D_Y0) {} }
  uint4 u0 = ldg_rlx128(yp), u1 = ldg_rlx128(yp + 1536), u2 = make_uint4(par, 0, 0, 0);
  if (a < 2) rld128(u2, yp + 3072);
  const int col = lane & 7;
  const uint32_t xw = lds32(sb + SM_XW + (col >> 1) * 16 + (grp % 3) * 4);
  const float xsel = (col & 1) ? bf_hi(xw) : bf_lo(xw);
  const float sg = rbf(rcp(1.f + ex2(-1.4426950408889634f * rbf(wn.r))));
  const float h = rbf((xsel - wn.m) * wn.rstd);
  unsigned char* dst = L == 0 ? (unsigned char*)P.sc->xsel + (((lane >> 3) & 1) * 576 + grp * 8 + col) * 4
                              : (unsigned char*)P.out + ((128 * (wn.ci >> 1) + 2 * wn.rr + (wn.ci & 1)) * 576 + grp * 8 + col) * 2;
  int n = 0;
#pragma unroll 1
  while (__any_sync(0xffffffffu, orx(orx(orx(0, u0.x, par), u1.x, par), u2.x, par) & 1)) {
    rld128(u0, yp); rld128(u1, yp + 1536);
    if (a < 2) rld128(u2, yp + 3072);
    if (++n > SPIN) TIMEOUT(__LINE__)
  }
  const float s0 = asf(u0.x) + asf(u1.x) + asf(u2.x), s1 = asf(u0.y) + asf(u1.y) + asf(u2.y);
  const float s2 = asf(u0.z) + asf(u1.z) + asf(u2.z), s3 = asf(u0.w) + asf(u1.w) + asf(u2.w);
  const float k0 = self(lane & 2, s2, s0) + shx(self(lane & 2, s0, s2), 2), k1 = self(lane & 2, s3, s1) + shx(self(lane & 2, s1, s3), 2);
  float k = self(lane & 4, k1, k0) + shx(self(lane & 4, k0, k1), 4);
  k += shx(k, 8); k += shx(k, 16);
  if (lane < 8) stsf(sb + SM_YRED + ((lane & 1) * 4 + (lane & 2) + (lane >> 2)) * 16 + a * 4, k);
  nb_sync(NB_AUX, 96);
  if (a == 0) {
    const uint4 yy = lds128(sb + SM_YRED + col * 16);
    const float xn = rbf(xsel + rbf(h + rbf(rbf(asf(yy.x) + asf(yy.y) + asf(yy.z)) * sg)));
    if (L == 0) { if (lane < 16) stg32(dst, ftag(lane < 8 ? xn : xn - xsel, T & 1)); }
    else if (lane < 8) *(unsigned short*)dst = (unsigned short)(asu(xn) >> 16);
  }
}

__device__ __forceinline__ void aux_role(const Ctx& cx, const Params& P, const int a, const int lane_, const Unit& h0, const Unit& h1, const uint32_t hT) {
  int lane = lane_;
#define t (a * 32 + lane)
#define g (lane >> 2)
#define q (lane & 3)
  const int i = cx.i, j = cx.j, cta = cx.cta;
  unsigned char* const sc = (unsigned char*)P.sc;
  const int rk = 36 * i + 12 * a;
  const uint32_t o_bf = OFF(bflag) + (j * 48 + i * 3 + a) * 32 + (lane & 7) * 4;
  uint32_t T;
  {
    const int k0 = lane & 7, tt = min(lane >> 3, 2), col = (9 * j + tt) * 16;
    const unsigned char* src = (const unsigned char*)P.wqkv + ((i * 8 + k0) * 3456 + a * 1152 + col);
    const Unit b0 = h0, b1 = h1;
    T = hT;
    nb_arrive(NB_ORD, 384);
    STAMPIF(1, 96);
    const uint32_t d2 = tt == 2 ? (22 - 7 * a) * 512 : 3072;
    const uint32_t o = OFF(wq) + (j * 18 + (i >> 2)) * 13824 + ((i & 3) * 8 + k0) * 16 + (a * 8 + tt) * 512;
    const uint32_t r0 = unit_store(sc, b0, lane, o, o + 1536, o + d2);
    STAMPD(asf(b0.v[2].w ^ b1.v[2].w), 80);
    const uint32_t r1 = unit_store(sc, b1, lane, o + 55296, o + 55296 + 1536, o + 55296 + d2);
    T = __shfl_sync(0xffffffffu, (T >> 3) + 1, 0);
    flag_after(sc + o_bf, r0 ^ r1, 8 * T + 1, lane < 8);
    STAMPD(asf(r0 ^ r1), 98);
    const Unit b2 = unit_load(src + 256 * 3456), b3 = unit_load(src + 384 * 3456);
    const bool qkv = k0 < 4;
    const int q0 = rk + k0 - 4, q1 = rk + 4 + k0;
    const Unit u0 = unit_load(qkv ? (const unsigned char*)P.wqkv + ((512 + 4 * i + k0) * 3456 + a * 1152 + col) : (const unsigned char*)P.wo + (q0 * 1152 + col));
    const Unit u1 = unit_load((const unsigned char*)P.wo + (q1 * 1152 + col));
    const uint32_t r2 = unit_store(sc, b2, lane, o + 2 * 55296, o + 2 * 55296 + 1536, o + 2 * 55296 + d2);
    const uint32_t r3 = unit_store(sc, b3, lane, o + 3 * 55296, o + 3 * 55296 + 1536, o + 3 * 55296 + d2);
    float cs[3][8];
#pragma unroll
    for (int m = 0; m < 3; m++) {
      const uint32_t* w0 = &b0.v[m].x; const uint32_t* w1 = &b1.v[m].x; const uint32_t* w2 = &b2.v[m].x; const uint32_t* w3 = &b3.v[m].x; const uint32_t* w4 = &u0.v[m].x;
#pragma unroll
      for (int e = 0; e < 4; e++) {
        const uint32_t z = qkv ? w4[e] : 0u;
        cs[m][2 * e] = (bf_lo(w0[e]) + bf_lo(w1[e])) + (bf_lo(w2[e]) + bf_lo(w3[e])) + bf_lo(z);
        cs[m][2 * e + 1] = (bf_hi(w0[e]) + bf_hi(w1[e])) + (bf_hi(w2[e]) + bf_hi(w3[e])) + bf_hi(z);
      }
    }
#pragma unroll
    for (int st = 4; st >= 1; st >>= 1) {
      const bool up = lane & st;
#pragma unroll
      for (int m = 0; m < 3; m++)
#pragma unroll
        for (int e = 0; e < st; e++) cs[m][e] = (up ? cs[m][e + st] : cs[m][e]) + shx(up ? cs[m][e] : cs[m][e + st], st);
    }
    {
      const uint32_t oz = OFF(zpart) + j * 13824 + i * 864 + (a * 8 + tt) * 32 + k0 * 4;
      stg32(sc + oz, ftag(cs[0][0], 1)); stg32(sc + (oz + 96), ftag(cs[1][0], 1)); stg32(sc + (oz + (d2 >> 4)), ftag(cs[2][0], 1));
    }
    STAMPIF(1, 81);
    flag_after(sc + o_bf, r2 ^ r3, 8 * T + 3, lane < 8);
    STAMPIF(1, 82);
    nb_sync(NB_GO, 128);
    mbar_wait(sb + BAR_FULL + LATE_WAIT * 8, 0);
    const uint32_t ow = OFF(wo) + j * 82944 + tt * 256;
    const uint32_t oa = qkv ? OFF(wq) + (j * 18 + 16 + (i >> 3)) * 13824 + (4 * (i & 7) + k0) * 16 + (a * 8 + tt) * 512 : ow + (q0 >> 4) * 2304 + (q0 & 15) * 16;
    const uint32_t ob = ow + (q1 >> 4) * 2304 + (q1 & 15) * 16;
    const uint32_t ra = unit_store(sc, u0, lane, oa, oa + (qkv ? 1536 : 768), oa + (qkv ? d2 : 1536));
    const uint32_t rb = unit_store(sc, u1, lane, ob, ob + 768, ob + 1536);
    STAMPIF(1, 113);
#pragma unroll
    for (int S = 0; S < 3; S++) stg64(sc + (OFF(ypart) + (a * 24 + g) * 4096 + cta * 32 + q * 8) + S * 32768, 0u, 0u);
    if (cta < 72 && t < 16) stg32(sc + (OFF(xsel) + (lane >> 3) * 2304 + cta * 32 + (lane & 7) * 4), (T & 1) ^ 1);
    uint4 sv, sw;
    int n = 0;
#pragma unroll 1
    while (true) {
      sv = ldg_rlx128(sc + (OFF(st0) + i * 2048 + t * 16)); sw = ldg_rlx128(sc + (OFF(st0) + i * 2048 + 1536 + lane * 16));
      if (__all_sync(0xffffffffu, ((sv.z ^ T) | (sw.z ^ T)) == 0)) break;
      if (++n > SPIN) TIMEOUT(__LINE__)
    }
    flag_after(sc + o_bf, ra ^ rb, 8 * T + 4, lane < 8);
    sts64(sb + SM_R + t * 8, sv.x, sv.y);
    sts64(sb + SM_R + 768 + lane * 8, sw.x, sw.y);
    STAMPIF(1, 94);
  }
  asm volatile("setmaxnreg.inc.sync.aligned.u32 %0;" ::"n"(REG_AUX));
  Winner wn;
  bool owner = false;
  uint32_t wd[5][3][8];
  auto load_wd = [&](uint32_t (*d)[8], const unsigned char* sk) {
#pragma unroll
    for (int S = 0; S < 3; S++) {
      const uint4 v0 = ldg_wd128(sk + S * 128), v1 = ldg_wd128(sk + S * 128 + 1152);
      d[S][0] = v0.x; d[S][1] = v1.x; d[S][2] = v0.y; d[S][3] = v1.y; d[S][4] = v0.z; d[S][5] = v1.z; d[S][6] = v0.w; d[S][7] = v1.w;
    }
  };
  auto perm_wd = [&](uint32_t (*d)[8]) {
#pragma unroll
    for (int S = 0; S < 3; S++)
#pragma unroll
      for (int u = 0; u < 4; u++) {
        const uint32_t x = d[S][2 * u], y = d[S][2 * u + 1];
        asm volatile("prmt.b32 %0, %2, %3, 0x5410;\nprmt.b32 %1, %2, %3, 0x7632;" : "=&r"(d[S][2 * u]), "=r"(d[S][2 * u + 1]) : "r"(x), "r"(y));
      }
  };
#pragma unroll
  for (int kb = 0; kb < 3; kb++)
#pragma unroll
    for (int S = 0; S < 3; S++)
#pragma unroll
      for (int e = 0; e < 8; e++) wd[kb][S][e] = 0u;
#pragma unroll 1
  for (int L = 0; L < 2; L++) {
    lane = pin(lane);
    const uint32_t o_part = OFF(zpart) + j * 13824, par = L ^ 1;
    const int pk = a * 18 + min(lane, 17);
    uint2 xu[3] = {make_uint2(0, 0), make_uint2(0, 0), make_uint2(0, 0)};
    if (L == 1) {
      if (cta < 72) finalize_row(P, wn, T, 0, cta, a, lane);
      const int gi = min(lane, 26);
      uint4 wv[12];
      {
        const int pc = gi < 24 ? gi >> 3 : gi - 24, tc = gi < 24 ? gi & 7 : 8;
        const unsigned char* se = (const unsigned char*)P.wqkv + (rk * 3456 + pc * 1152 + (9 * j + tc) * 16);
#pragma unroll
        for (int r = 0; r < 12; r++) wv[r] = ldg_nc128(se + r * 3456);
      }
      STAMPIF(1, 85);
      nb_sync(NB_AUX, 96);
      uint4 xq[3];
      {
        if (D_XS) { const int c0 = clock(); while ((int)(clock() - c0) < (cta < 72 ? 0 : D_XS)) {} }
        const unsigned char* dp = sc + (OFF(xsel) + 2304 + rk * 4);
        int n = 0;
#pragma unroll 1
        while (true) {
#pragma unroll
          for (int e = 0; e < 3; e++) xq[e] = ldg_rlx128(dp + e * 16);
          uint32_t d = orx(orx(orx(0, xq[0].x, T), xq[1].x, T), xq[2].x, T);
          if (owner) {
#pragma unroll
            for (int m = 0; m < 3; m++) xu[m] = ldg_rlx64(sc + (OFF(xsel) + t * 8) + m * 768);
            d = orx(orx(orx(d, xu[0].x, T), xu[1].x, T), xu[2].x, T);
          }
          if (__all_sync(0xffffffffu, (d & 1) == 0)) break;
          if (++n > SPIN) TIMEOUT(__LINE__)
        }
        if (t == 0) {
          sts32(sb + SM_SEL, owner ? (wn.ci & 1) * 64 + wn.rr : 0x7FFFFFFFu);
          if (wn.ci != 2 * i) mbar_arrive(sb + BAR_FIX);
          if (wn.ci != 2 * i + 1) mbar_arrive(sb + BAR_FIX + 8);
        }
        STAMPIF(1, 88);
      }
      float s[8];
#pragma unroll
      for (int e = 0; e < 8; e++) s[e] = 0.f;
#pragma unroll
      for (int r = 0; r < 12; r++) {
        const float x = asf((&xq[0].x)[r]);
        s[0] = fmaf(x, bf_lo(wv[r].x), s[0]); s[1] = fmaf(x, bf_hi(wv[r].x), s[1]);
        s[2] = fmaf(x, bf_lo(wv[r].y), s[2]); s[3] = fmaf(x, bf_hi(wv[r].y), s[3]);
        s[4] = fmaf(x, bf_lo(wv[r].z), s[4]); s[5] = fmaf(x, bf_hi(wv[r].z), s[5]);
        s[6] = fmaf(x, bf_lo(wv[r].w), s[6]); s[7] = fmaf(x, bf_hi(wv[r].w), s[7]);
      }
      sts128(sb + SM_R + a * 864 + gi * 32, asu(s[0]), asu(s[1]), asu(s[2]), asu(s[3]));
      sts128(sb + SM_R + a * 864 + gi * 32 + 16, asu(s[4]), asu(s[5]), asu(s[6]), asu(s[7]));
      nb_sync(NB_AUX, 96);
      const uint32_t ad = sb + SM_R + pk * 16;
      const uint4 u0 = lds128(ad), u1 = lds128(ad + 864), u2 = lds128(ad + 1728);
      stg128(sc + (o_part + i * 864 + pk * 16), ftag(asf(u0.x) + asf(u1.x) + asf(u2.x), par), ftag(asf(u0.y) + asf(u1.y) + asf(u2.y), par),
             ftag(asf(u0.z) + asf(u1.z) + asf(u2.z), par), ftag(asf(u0.w) + asf(u1.w) + asf(u2.w), par));
      STAMPIF(1, 86);
    }
    if (owner) {
      const uint2* u = xu;
      STAMPIF(1, 109);
      float s1 = 0.f, s2 = 0.f;
#pragma unroll
      for (int m = 0; m < 3; m++) {
        const float x0 = asf(u[m].x), x1 = asf(u[m].y);
        s1 += x0 + x1; s2 = fmaf(x0, x0, fmaf(x1, x1, s2));
        const unsigned cc = 96 * m + t - 36 * j;
        if (cc < 36u) sts32(sb + SM_X2S + cc * 4, __byte_perm(u[m].x, u[m].y, 0x7632));
      }
      wn.m = s1; wn.rstd = s2;
    }
    if (L == 0 || owner) {
      uint4 u[16];
      int n = 0;
#pragma unroll 1
      while (true) {
        uint32_t d0 = 0, d1 = 0;
#pragma unroll
        for (int e = 0; e < 16; e++) u[e] = ldg_rlx128(sc + (o_part + pk * 16) + e * 864);
        if (L == 1 && n == 0) {
#pragma unroll
          for (int s = 1; s < 32; s <<= 1) { wn.m += shx(wn.m, s); wn.rstd += shx(wn.rstd, s); }
          if (lane == 0) sts64(sb + SM_RED2 + a * 8, asu(wn.m), asu(wn.rstd));
        }
#pragma unroll
        for (int e = 0; e < 8; e++) { d0 = orx(d0, u[e].x, par); d1 = orx(d1, u[8 + e].x, par); }
        if (__all_sync(0xffffffffu, ((d0 | d1) & 1) == 0)) break;
        if (++n > SPIN) TIMEOUT(__LINE__)
      }
      STAMPIF(1, 118 + L);
      float4 z = make_float4(0.f, 0.f, 0.f, 0.f);
#pragma unroll
      for (int e = 0; e < 16; e++) { z.x += asf(u[e].x); z.y += asf(u[e].y); z.z += asf(u[e].z); z.w += asf(u[e].w); }
      const uint32_t h0 = pack_bf16(z.x, z.y), h1 = pack_bf16(z.z, z.w);
      const uint32_t l0 = pack_bf16(z.x - bf_lo(h0), z.y - bf_hi(h0)), l1 = pack_bf16(z.z - bf_lo(h1), z.w - bf_hi(h1));
      const uint32_t ad = sb + SM_BEXT + (pk >> 1) * 128 + (pk & 1) * 8;
      if (L == 0) {
        sts64(ad, h0, h1);
#pragma unroll
        for (int r = 3; r < 8; r++) sts64(ad + r * 16, 0u, 0u);
      }
      sts64(ad + 16 + L * 48, h0, h1); sts64(ad + 32 + L * 48, l0, l1);
      fence_async_smem();
      nb_sync(NB_AUX, 96);
      if (t == 0) {
        if (L == 1) {
          const uint4 ra = lds128(sb + SM_RED2);
          const uint2 rb = lds64(sb + SM_RED2 + 16);
          const float m2 = (asf(ra.x) + asf(ra.z) + asf(rb.x)) * (1.f / 576.f);
          const float rs2 = rsq(fmaxf((asf(ra.y) + asf(ra.w) + asf(rb.y)) * (1.f / 576.f) - m2 * m2, 0.f) + EPS);
          sts64(sb + SM_SEL + 8, asu(m2), asu(rs2));
          mbar_arrive(sb + BAR_FIX + (wn.ci & 1) * 8);
        } else {
          mbar_arrive(sb + BAR_FIX); mbar_arrive(sb + BAR_FIX + 8);
        }
        STAMP(83 + L * 4);
      }
    }
    lane = pin(lane);
    const unsigned char* const wsrc = (const unsigned char*)P.wd + ((ffn_c32(cta) + 2 * q) * 1152 + a * 384 + g * 16);
    if (L == 0) {
#pragma unroll
      for (int kb = 0; kb < 3; kb++) { load_wd(wd[kb], wsrc + (kb * 9216 + (kb ? pin0(wd[kb - 1][2][7]) : 0u))); perm_wd(wd[kb]); }
    }
    if (L == 0)
    {
    load_wd(wd[3], wsrc + 3 * 9216);
    load_wd(wd[4], wsrc + ((cta & 1) ? (ffn_c8(cta) - ffn_c32(cta)) * 1152 : 24 * 1152));
    perm_wd(wd[3]); perm_wd(wd[4]);
    }
    const uint32_t o_y = pin(OFF(ypart) + (a * 24 + g) * 4096 + cta * 32 + q * 8 + pin0(wd[4][2][7]));
    STAMPIF(1, 89 + L);
    if (a == 2) load_wo_a(cx, P, T, L, 1, lane);
    nb_sync(NB_FFN, 224);
    {
      const uint32_t ad = sb + R_FPART + min(lane, 19) * 16;
      const uint4 u0 = lds128(ad), u1 = lds128(ad + 320), u2 = lds128(ad + 640), u3 = lds128(ad + 960);
      const uint4 wv = lds128(sb + SM_WIN);
      const float g0 = rbf((asf(u0.x) + asf(u1.x)) + (asf(u2.x) + asf(u3.x))), g1 = rbf((asf(u0.z) + asf(u1.z)) + (asf(u2.z) + asf(u3.z)));
      const float v0 = rbf((asf(u0.y) + asf(u1.y)) + (asf(u2.y) + asf(u3.y))), v1 = rbf((asf(u0.w) + asf(u1.w)) + (asf(u2.w) + asf(u3.w)));
      const float s0 = rbf(g0 * rcp(1.f + ex2(-1.4426950408889634f * g0))), s1 = rbf(g1 * rcp(1.f + ex2(-1.4426950408889634f * g1)));
      const uint32_t act = lane < 16 + (cta & 1) * 4 ? pack_bf16(s0 * v0, s1 * v1) : 0u;
      uint32_t b[5];
#pragma unroll
      for (int kb = 0; kb < 5; kb++) b[kb] = __shfl_sync(0xffffffffu, act, 4 * kb + q);
#pragma unroll
      for (int S = 0; S < 3; S++) {
        float y[4][4];
#pragma unroll
        for (int u = 0; u < 4; u++) mma8z(y[u], wd[2][S][2 * u], wd[2][S][2 * u + 1], b[2]);
#pragma unroll
        for (int u = 0; u < 4; u++) mma16(y[u], wd[0][S][2 * u], wd[0][S][2 * u + 1], wd[1][S][2 * u], wd[1][S][2 * u + 1], b[0], b[1]);
#pragma unroll
        for (int u = 0; u < 4; u++) mma16(y[u], wd[3][S][2 * u], wd[3][S][2 * u + 1], wd[4][S][2 * u], wd[4][S][2 * u + 1], b[3], b[4]);
        const float y0 = self(lane & 2, self(lane & 1, y[3][0], y[2][0]), self(lane & 1, y[1][0], y[0][0]));
        const float y1 = self(lane & 2, self(lane & 1, y[3][2], y[2][2]), self(lane & 1, y[1][2], y[0][2]));
        stg64(sc + o_y + S * 32768, ftag(y0, par), ftag(y1, par));
      }
      if (L == 0) nb_arrive(NB_FFN2, 352);
      wn.r = asf(wv.x); wn.m = asf(wv.y); wn.rstd = asf(wv.z); wn.ci = wv.w >> 6; wn.rr = wv.w & 63;
    }
    STAMPIF(1, 84 + L * 8);
    owner = (wn.ci >> 1) == i;
  }
  if (cta < 72) finalize_row(P, wn, T, 1, cta, a, lane);
  STAMPIF(1, 93);
  PROF_END();
#undef t
#undef g
#undef q
}

__device__ __forceinline__ int sched_box(const uint32_t at, const int a) {
  int r = -1;
#pragma unroll
  for (int b = 0; b < 6; b++) if (((at >> (4 * b)) & 15) != 15) r = a == (int)((at >> (4 * b)) & 15) ? b : r;
  return r;
}
__host__ __device__ constexpr int sched_first(const uint32_t at) { int b = 0; while (b < 6 && ((at >> (4 * b)) & 15) != 15) b++; return b; }
__host__ __device__ constexpr int sched_last(const uint32_t at) { int b = 5; while (b >= 0 && ((at >> (4 * b)) & 15) != 15) b--; return b; }
__device__ __forceinline__ void producer_role(const Ctx& cx, const Params& P, const int lane) {
  const int i = cx.i, j = cx.j;
  nb_sync(NB_ORD, 384);
  if (elect_one()) asm volatile("prefetch.tensormap [%0];" ::"l"(&P.mx) : "memory");
  const uint32_t T = __shfl_sync(0xffffffffu, (ldg_rlx32(P.sc->cflag[i * 2][j * 4]) >> 3) + 1, 0);
  const unsigned char* const wq = P.sc->wq[j][0];
  nb_sync(NB_START, 288);
#pragma unroll
  for (int s = 0; s < 2 * NA0; s++) w_tma3d(sb + SM_A + s * 8192, &P.mx, (s >> 1) * 64, s & 1, i * 64, sb + BAR_FULL + (s >> 1) * 16);
#pragma unroll
  for (int h = 0; h < 6; h++) w_expect(sb + BAR_FULL + h * 8, h & 1 ? 13824 : 13824 + 16384);
  STAMP(97);
  wait_flags<48>(P.sc->bflag[j], 8 * T + 1, lane);
  fence_async_glob();
  STAMP(120);
#pragma unroll
  for (int h = 0; h < 6; h++) {
    w_bulk(sb + SM_B + h * 13824, wq + h * 13824, 13824, sb + BAR_FULL + h * 8);
    if (!(h & 1) && h >= 2 * NA0) {
      w_tma3d(sb + SM_A + h * 8192, &P.mx, h * 32, 0, i * 64, sb + BAR_FULL + h * 8);
      w_tma3d(sb + SM_A + h * 8192 + 8192, &P.mx, h * 32, 1, i * 64, sb + BAR_FULL + h * 8);
    }
  }
  PSTAMP(0);
  asm volatile("setmaxnreg.inc.sync.aligned.u32 %0;" ::"n"(REG_AUX));
  nb_arrive(NB_GO, 128);
  mbar_wait(sb + BAR_FULL + PF_WAIT * 8, 0);
  w_prefetch((const unsigned char*)P.wd + cx.cta * 41472, 10368);
  const unsigned char* const xb = P.sc->xbuf[i * 2];
  const unsigned char* const fp = (const unsigned char*)P.sc->bflag[j] + lane * 32;
  uint32_t f0 = 0, f1 = 0;
#pragma unroll 1
  for (int L = 0; L < 2; L++) {
#pragma unroll 1
    for (int a = 3; a < 15; a++) {
      if (a == 12) {
        load_wo_a(cx, P, T, L, 0, lane);
        if (L == 1) break;
        {
#pragma unroll 1
          for (int b = LATE_G0; b < 6; b++) {
            if (LATE_GGAP) { const int c0 = clock(); while ((int)(clock() - c0) < LATE_GGAP) {} }
            load_gu(P, cx.cta, 0, b, sb + BAR_GU);
          }
#pragma unroll 1
          for (int p = 0; p < 2; p++) {
            mbar_wait(sb + BAR_AEMPTY + (2 + 3 * p) * 8, 0);
            wait_flags<32>(P.sc->cflag[i * 2 + p], 8 * T + 1, lane);
            STAMP(104 + p);
          }
          fence_async_glob();
          mbar_wait(sb + BAR_ST, 0);
#pragma unroll 1
          for (int s = 0; s < 3; s++) {
            const uint32_t fb = sb + BAR_FULL + s * 16, ab = sb + BAR_AFULL + s * 16, db = sb + SM_B + s * 27648, da = sb + SM_A + s * 16384;
            mbar_wait(sb + BAR_EMPTY + s * 16, 1);
            w_expect(fb, 13824);
            w_bulk(db, wq + s * 27648, 13824, fb);
            w_expect(ab, 8192);
            w_bulk(da, xb + s * 8192, 8192, ab);
            w_expect(ab + 8, 8192);
            w_bulk(da + 8192, xb + (73728 + s * 8192), 8192, ab + 8);
            mbar_wait(sb + BAR_EMPTY + s * 16 + 8, 1);
            w_expect(fb + 8, 13824);
            w_bulk(db + 13824, wq + (s * 27648 + 13824), 13824, fb + 8);
          }
          break;
        }
      }
      const int r = (a * 11) >> 5, s = a - 3 * r;
      const uint32_t fb = sb + BAR_FULL + s * 16, da = sb + SM_A + s * 16384, db = sb + SM_B + s * 27648;
      const unsigned char* bsrc = wq + (a < 9 ? a : a < 12 ? 72 - 6 * j + s : s) * 27648;
      const unsigned char* asrc = xb + a * 8192;
      const int kc = (a < 9 ? a : j + a - 10) * 64;
      const int amode = a == 9 || a > 11 ? 0 : L == 0 ? 1 : a < 9 ? 2 : 0;
      mbar_wait(sb + BAR_EMPTY + s * 16, (r & 1) ^ 1);
      if (L == 0) {
        if (a == 4 || a == 8) {
          const uint32_t need = 8 * T + (a == 4 ? 3 : 4);
          if (__any_sync(0xffffffffu, (int)((f0 - need) | (f1 - need)) < 0)) wait_flags<48>(P.sc->bflag[j], need, lane);
          fence_async_glob();
          STAMP(120 + (a >> 1));
        }
        if (a == 3 || a == 7) { f0 = ldg_rlx32(fp); f1 = ldg_rlx32(fp + (lane < 16 ? 1024 : 0)); }
      }
      w_bulk(db, bsrc, 13824, fb);
      if (amode == 2) {
        w_bulk(da, asrc, 4096, fb);
        w_bulk(da + 8192, asrc + 73728, 4096, fb);
      }
      w_expect(fb, amode == 1 ? 13824 + 16384 : amode == 2 ? 13824 + 8192 : 13824);
      mbar_wait(sb + BAR_EMPTY + s * 16 + 8, (r & 1) ^ 1);
      if (amode == 1) {
        w_tma3d(da, &P.mx, kc, 0, i * 64, fb);
        w_tma3d(da + 8192, &P.mx, kc, 1, i * 64, fb);
      }
      w_bulk(db + 13824, bsrc + 13824, 13824, fb + 8);
      if (amode == 2) {
        w_bulk(da + 4096, asrc + 4096, 4096, fb + 8);
        w_bulk(da + 8192 + 4096, asrc + 73728 + 4096, 4096, fb + 8);
      }
      w_expect(fb + 8, amode == 2 ? 13824 + 8192 : 13824);
      PSTAMP(a < 12 ? L * 24 + a : 12 + a);
      if (L == 0) {
        {
          if (a >= WD_PF && a < WD_PF + 3) w_prefetch((const unsigned char*)P.wd + (cx.cta * 4 + a - WD_PF + 1) * 10368, 10368);
          if (a >= PG_0 && a < PG_0 + 6) w_prefetch((const unsigned char*)P.wg + ((a - PG_0) * 128 + cx.cta) * 6912, 6912);
        }
        if (a == 3) w_expect(sb + BAR_GU, 12 * (6144 + (cx.cta & 1) * 1536));
        {
          const int bu = sched_box(U_AT, a), bg = sched_box(G_AT, a);
          if (bu >= 0) load_gu(P, cx.cta, 1, bu, sb + BAR_GU);
          if (bg >= 0) load_gu(P, cx.cta, 0, bg, sb + BAR_GU);
          if (a == U_WIN) {
#pragma unroll 1
            for (int b = sched_first(U_AT); b <= sched_last(U_AT); b++) {
              const int c0 = clock();
              while ((int)(clock() - c0) < U_GAP) {}
              load_gu(P, cx.cta, 1, b, sb + BAR_GU);
            }
          }
        }
      }
    }
  }
}

template <bool BY_SMID>
__global__ void __launch_bounds__(384, 1) fused_kernel(const __grid_constant__ Params P) {
  extern __shared__ __align__(1024) unsigned char smem[];
  Ctx cx;
  STAMPIF(threadIdx.x == 64, 125);
  unsigned id;
  if (BY_SMID) asm volatile("mov.u32 %0, %%smid;" : "=r"(id)); else id = blockIdx.x;
  const int work = __shfl_sync(0xffffffffu, (int)P.work[min(id, 131u)], 0);
  const int warp = __shfl_sync(0xffffffffu, (int)(threadIdx.x >> 5), 0), lane = threadIdx.x & 31;
  if (work < 0) {
    if (warp == 0) {
      const int sp = -1 - work;
      if (lane == 0) { mbar_init(sb, 1); fence_async_smem(); }
      __syncwarp();
      __nanosleep(SPARE_DELAY);
#pragma unroll 1
      for (int k = 32 + sp; k < 72; k += 4) w_prefetch((const unsigned char*)P.wqkv + k * 27648, 27648);
#pragma unroll 1
      for (int k = sp; k < 24; k += 4) w_prefetch((const unsigned char*)P.wo + k * 27648, 27648);
#pragma unroll 1
      for (int k = sp; k < X_NU; k += 4) w_prefetch((const unsigned char*)P.wu + k * 27648, 27648);
      w_expect(sb, 16);
      w_bulk(sb + 128, P.wr, 16, sb);
      mbar_wait(sb, 0);
    }
    return;
  }
  cx.cta = work; cx.i = work >> 3; cx.j = work & 7;
  STAMPIF(threadIdx.x == 32, 95);
  Unit h0, h1;
  uint32_t hT = 0;
  if (warp >= 8 && warp < 11) {
    const int a = warp - 8, k0 = lane & 7, tt = min(lane >> 3, 2);
    const unsigned char* src = (const unsigned char*)P.wqkv + ((cx.i * 8 + k0) * 3456 + a * 1152 + (9 * cx.j + tt) * 16);
    h0 = unit_load(src); h1 = unit_load(src + 128 * 3456);
    hT = ldg_rlx32((const unsigned char*)P.sc + (OFF(bflag) + (cx.j * 48 + cx.i * 3 + a) * 32 + (lane & 7) * 4));
  }
  if (warp < 8) {
    asm volatile("setmaxnreg.dec.sync.aligned.u32 %0;" ::"n"(REG_CONS));
    if (warp == 0) {
      if (elect_one()) {
        if ((uint32_t)__cvta_generic_to_shared(smem) != sb) __trap();
#pragma unroll
        for (int b = 0; b < 48; b++) mbar_init(sb + SM_BAR + b * 8, b < 34 ? 1 : b < 42 ? 4 : 8);
        fence_async_smem();
      }
      __syncwarp();
    }
    consumer_role(cx, P, smem, warp >> 2, warp & 3, lane);
  } else {
    if (warp < 11) aux_role(cx, P, warp - 8, lane, h0, h1, hT);
    else producer_role(cx, P, lane);
  }
}

int work_of_smid(int smid) {
  const int t = smid >> 1;
  if (t == 60 || t == 61) return -1 - ((t - 60) * 2 + (smid & 1));
  const int gpc = t < 32 ? t & 7 : t < 60 ? 1 + (t - 32) % 7 : 0;
  const int x = 2 * (t < 32 ? t >> 3 : t < 60 ? 4 + (t - 32) / 7 : t - 58) + (smid & 1);
  const int blk[8] = {6, 0, 2, 3, 4, 7, 5, 1}, b = blk[gpc];
  return ((b >> 1) * 4 + (x & 1) + (x >> 3) * 2) * 8 + (b & 1) * 4 + ((x >> 1) & 3);
}

typedef CUresult (*EncodeFn)(CUtensorMap*, CUtensorMapDataType, cuuint32_t, void*, const cuuint64_t*, const cuuint64_t*,
                             const cuuint32_t*, const cuuint32_t*, CUtensorMapInterleave, CUtensorMapSwizzle,
                             CUtensorMapL2promotion, CUtensorMapFloatOOBfill);

void make_map(EncodeFn enc, CUtensorMap* m, const void* base, int rank, const cuuint64_t* dims, const cuuint64_t* strides,
              const cuuint32_t* box, CUtensorMapSwizzle sw, CUtensorMapL2promotion promo = CU_TENSOR_MAP_L2_PROMOTION_L2_128B) {
  const cuuint32_t es[3] = {1, 1, 1};
  enc(m, CU_TENSOR_MAP_DATA_TYPE_BFLOAT16, rank, const_cast<void*>(base), dims, strides, box, es, CU_TENSOR_MAP_INTERLEAVE_NONE, sw,
      promo, CU_TENSOR_MAP_FLOAT_OOB_FILL_NONE);
}

}

extern "C" void kernel_launch(void* const* d_in, const int* in_sizes, int n_in, void* d_out, int out_size) {
  (void)in_sizes; (void)n_in; (void)out_size;
  static EncodeFn enc = nullptr;
  static int nsm = 0;
  static void* scr = nullptr;
  if (!enc) {
    void* f = nullptr;
    cudaDriverEntryPointQueryResult qr;
    cudaGetDriverEntryPoint("cuTensorMapEncodeTiled", &f, cudaEnableDefault, &qr);
    enc = (EncodeFn)f;
    cudaGetSymbolAddress(&scr, g_scratch);
    int dev = 0;
    cudaGetDevice(&dev);
    cudaDeviceGetAttribute(&nsm, cudaDevAttrMultiProcessorCount, dev);
    cudaFuncSetAttribute(fused_kernel<true>, cudaFuncAttributeMaxDynamicSharedMemorySize, SM_TOTAL);
    cudaFuncSetAttribute(fused_kernel<false>, cudaFuncAttributeMaxDynamicSharedMemorySize, SM_TOTAL);
  }
  Params P;
  P.x = (const __nv_bfloat16*)d_in[0];
  P.wqkv = (const __nv_bfloat16*)d_in[1];
  P.wo = (const __nv_bfloat16*)d_in[2];
  P.wr = (const __nv_bfloat16*)d_in[4];
  P.wg = (const __nv_bfloat16*)d_in[5];
  P.wu = (const __nv_bfloat16*)d_in[6];
  P.wd = (const __nv_bfloat16*)d_in[7];
  P.out = (__nv_bfloat16*)d_out;
  P.sc = (Scratch*)scr;
  for (int k = 0; k < 136; k++) P.work[k] = (signed char)(nsm == 132 ? (k < 132 ? work_of_smid(k) : -1) : (k < 128 ? k : k < 132 ? 127 - k : -1));
  {
    const cuuint64_t dims[3] = {576, 2, 1024}, str[2] = {1152, 2304};
    const cuuint32_t box[3] = {64, 1, 64};
    make_map(enc, &P.mx, P.x, 3, dims, str, box, CU_TENSOR_MAP_SWIZZLE_128B);
  }
  {
    const cuuint64_t dims[2] = {4608, 576}, str[1] = {9216};
    const cuuint32_t box[2] = {32, 96}, box8[2] = {8, 96};
    make_map(enc, &P.mg, d_in[5], 2, dims, str, box, CU_TENSOR_MAP_SWIZZLE_64B);
    make_map(enc, &P.mu, d_in[6], 2, dims, str, box, CU_TENSOR_MAP_SWIZZLE_64B);
    make_map(enc, &P.mg8, d_in[5], 2, dims, str, box8, CU_TENSOR_MAP_SWIZZLE_NONE);
    make_map(enc, &P.mu8, d_in[6], 2, dims, str, box8, CU_TENSOR_MAP_SWIZZLE_NONE);
  }
  if (nsm == 132) fused_kernel<true><<<132, 384, SM_TOTAL>>>(P);
  else fused_kernel<false><<<132, 384, SM_TOTAL>>>(P);
}
```
